```python
import torch

def _softmax(x, axis=-1):
    return torch.softmax(x, dim=axis)
def _gelu(x):
    return torch.nn.functional.gelu(x, approximate="tanh")
def _silu(x):
    return torch.nn.functional.silu(x)
def _sigmoid(x):
    return torch.sigmoid(x)
def _layernorm(x, axis=-1, eps=1e-5):
    m = x.mean(dim=axis, keepdim=True)
    v = x.var(dim=axis, keepdim=True, unbiased=False)
    return (x - m) / torch.sqrt(v + eps)
def _scatter_add(tgt, idx, src, axis=0):
    return tgt.clone().index_add_(axis, idx, src)
def _segment_sum(src, seg, n):
    out = torch.zeros((n,) + src.shape[1:], dtype=src.dtype)
    return out.index_add_(0, seg, src)
def _pad(x, pw):
    flat = tuple(v for pair in reversed(pw) for v in pair)
    return torch.nn.functional.pad(x, flat)

kernel_name = 'gated_mix__ssm_conv_s5__moe_arch_mod__prompt'

def setup_inputs():

    _w = (lambda a: (lambda t: t.to(torch.bfloat16) if t.is_floating_point() else t)(torch.as_tensor(a)))
    def _A_setup():
        B, S, D = 1, 2048, 1024
        P = D
        Lambda_re = -0.5 * (lambda _x: torch.exp(torch.as_tensor(_x)))((lambda *s: torch.randn(*s, dtype=torch.bfloat16) * 0.8)(P))
        Lambda_im = (lambda *s: torch.randn(*s, dtype=torch.bfloat16) * 0.8)(P) * 1.0
        B_re = (lambda *s: torch.randn(*s, dtype=torch.bfloat16) * 0.8)(P, D) * (D ** -0.5)
        B_im = (lambda *s: torch.randn(*s, dtype=torch.bfloat16) * 0.8)(P, D) * (D ** -0.5)
        C_re = (lambda *s: torch.randn(*s, dtype=torch.bfloat16) * 0.8)(D, P) * (P ** -0.5)
        C_im = (lambda *s: torch.randn(*s, dtype=torch.bfloat16) * 0.8)(D, P) * (P ** -0.5)
        log_dt = (lambda *s: torch.randn(*s, dtype=torch.bfloat16) * 0.8)(P) * 0.3 - 2.0
        Dskip = (lambda *s: torch.randn(*s, dtype=torch.bfloat16) * 0.8)(D)
        return {
            "x": _w((lambda *s: torch.randn(*s, dtype=torch.bfloat16) * 0.05)(B, S, D)),
            "Lambda_re": _w(Lambda_re),
            "Lambda_im": _w(Lambda_im),
            "B_re": _w(B_re),
            "B_im": _w(B_im),
            "C_re": _w(C_re),
            "C_im": _w(C_im),
            "log_dt": _w(log_dt),
            "Dskip": _w(Dskip),
        }
    _A_in = _A_setup()

    def _B_setup():
        B, S, D, F, C = 1, 2048, 1024, 3584, 8
        return {
            "x": _w((lambda *s: torch.randn(*s, dtype=torch.bfloat16) * 0.05)(B, S, D)),
            "w_r": _w((lambda *s: torch.randn(*s, dtype=torch.bfloat16) * 1.6)(D)),
            "w_gate": _w((lambda *s: torch.randn(*s, dtype=torch.bfloat16) * 0.1)(D, F)),
            "w_up": _w((lambda *s: torch.randn(*s, dtype=torch.bfloat16) * 0.1)(D, F)),
            "w_down": _w((lambda *s: torch.randn(*s, dtype=torch.bfloat16) * 0.1)(F, D)),
        }
    _B_in = _B_setup()

    return {
        "A_x": _A_in["x"],
        "A_Lambda_re": _A_in["Lambda_re"],
        "A_Lambda_im": _A_in["Lambda_im"],
        "A_B_re": _A_in["B_re"],
        "A_B_im": _A_in["B_im"],
        "A_C_re": _A_in["C_re"],
        "A_C_im": _A_in["C_im"],
        "A_log_dt": _A_in["log_dt"],
        "A_Dskip": _A_in["Dskip"],
        "B_x": _B_in["x"],
        "B_w_r": _B_in["w_r"],
        "B_w_gate": _B_in["w_gate"],
        "B_w_up": _B_in["w_up"],
        "B_w_down": _B_in["w_down"],
        "gate_w": _w((lambda *s: torch.randn(*s, dtype=torch.bfloat16) * 0.05)(1024) * 16.0),
    }

def reference(A_x, A_Lambda_re, A_Lambda_im, A_B_re, A_B_im, A_C_re, A_C_im, A_log_dt, A_Dskip, B_x, B_w_r, B_w_gate, B_w_up, B_w_down, gate_w):
    def _A_ref(x, Lambda_re, Lambda_im, B_re, B_im, C_re, C_im, log_dt, Dskip):
        Bsz, L, H = x.shape
        Lam = Lambda_re + 1j * Lambda_im
        Bmat = B_re + 1j * B_im
        Cmat = C_re + 1j * C_im
        dt = torch.exp(log_dt)
        Lam_bar = torch.exp(dt * Lam)
        B_bar = ((Lam_bar - 1.0) / Lam)[:, None] * Bmat
        Bu = torch.einsum("bld,pd->blp", x + 0j, B_bar)
        h = torch.zeros_like(Bu[:, 0, :])
        hs = []
        for t in range(L):
            h = Lam_bar[None, :] * h + Bu[:, t, :]
            hs.append(h)
        hseq = torch.stack(hs, 1)
        y = 2.0 * torch.einsum("blp,dp->bld", hseq, Cmat).real + x * Dskip[None, None, :]
        return y

    def _B_ref(x, w_r, w_gate, w_up, w_down):
        B, S, D = x.shape
        C = 8
        r = x @ w_r
        idx = torch.argsort(-r, axis=-1)[:, :C]
        idx_e = (lambda x, n, axis: torch.repeat_interleave(x, n, dim=axis))(idx.reshape(B, C, 1), D, axis=2)
        x_sel = (lambda x, i, axis: torch.take_along_dim(x, i, dim=axis))(x, idx_e, axis=1)
        g = _silu(x_sel @ w_gate)
        u = x_sel @ w_up
        y = (g * u) @ w_down
        r_sel = _sigmoid((lambda x, i, axis: torch.take_along_dim(x, i, dim=axis))(r, idx, axis=1))
        y = y * r_sel.reshape(B, C, 1)
        b_off = (torch.arange(B) * S).reshape(B, 1)
        flat_idx = (idx + b_off).reshape(B * C)
        zero = (x * 0.0).reshape(B * S, D)
        upd = _scatter_add(zero, flat_idx, y.reshape(B * C, D), axis=0)
        return x + upd.reshape(B, S, D)

    x = A_x
    g = _sigmoid((x * gate_w).sum(-1, keepdims=True))
    a = _A_ref(x, A_Lambda_re, A_Lambda_im, A_B_re, A_B_im, A_C_re, A_C_im, A_log_dt, A_Dskip)
    b = _B_ref(x, B_w_r, B_w_gate, B_w_up, B_w_down)
    return g * a + (1 - g) * b
```

```cpp
#include <cuda_runtime.h>
#include <cuda_bf16.h>
#include <cuda.h>
#include <stdint.h>

namespace {

constexpr int S_ = 2048, D_ = 1024, F_ = 3584;
constexpr int NCTA = 128;
constexpr int NBIG = 56, NENT = 72;
constexpr int NST = 5;
constexpr int NFT = 5;
constexpr uint32_t SLOT = 32768, TILE = 8192;
constexpr uint32_t OFF_FT = NST * SLOT;
constexpr uint32_t OFF_XS = OFF_FT + NFT * TILE;
constexpr uint32_t OFF_LIST = OFF_XS + 8192;
constexpr uint32_t OFF_RED = OFF_XS + 4096;
constexpr uint32_t OFF_CONST = OFF_XS + 16384;
constexpr uint32_t OFF_M = OFF_CONST + 8192, OFF_ONE = OFF_M + 512;
constexpr uint32_t OFF_HID = OFF_CONST;
constexpr uint32_t OFF_E = OFF_CONST;
constexpr uint32_t OFF_G = OFF_ONE + 16;
constexpr uint32_t OFF_DK = OFF_G + 256;
constexpr uint32_t OFF_FULL = OFF_DK + 256;
constexpr uint32_t OFF_EMPTY = OFF_FULL + 90 * 8;
constexpr uint32_t OFF_KEYS = OFF_EMPTY + 94 * 8;
constexpr uint32_t OFF_SEL = OFF_KEYS + 32;
constexpr uint32_t OFF_EPOCH = OFF_SEL + 32;
constexpr uint32_t OFF_PROF = OFF_EPOCH + 16;
constexpr uint32_t SMEM_BYTES = OFF_PROF + 464;
static_assert(SMEM_BYTES <= 232448, "smem");

static_assert(NBIG % NST == 1, "tail layout");
__host__ __device__ constexpr uint32_t tail_c(int j) { return j < 6 ? 2 * SLOT + j * 2 * TILE : (j - 6) * 2 * TILE; }
__host__ __device__ constexpr uint32_t tail_h(int n) { return n % 7 < 3 ? OFF_FT + n % 7 * TILE : SLOT + (n % 7 - 3) * TILE; }

constexpr uint32_t SPIN_LIMIT = 1u << 18;

struct Scratch {
    uint2 carry[16 * 1024];
    uint2 hid[NCTA * 128];
    uint32_t y[8 * 8 * D_];
    uint2 flag[16 * 8 * 32];
    uint32_t key[NCTA * 8];
    uint32_t gate[S_];
    uint2 armed[NCTA * 4];
    unsigned int epoch[256];
    uint4 start[32 * 2];
    uint4 h[16 * 32 * 1024];
};
__device__ __align__(1024) Scratch g_scratch;
#define STAMPW(cond, w) do {} while (0)
#define GSTAMP(cond, w) do {} while (0)
#define STAMPIF(cond, i) STAMPW(cond, 96 + (i))
#define STAMP(i) STAMPW(1, 96 + (i))
#define KSTAMP(i) STAMPW((threadIdx.x & 127) == 0, i)
#define PSTAMP(i) STAMPW(1, 160 + (i))

struct Params {
    const __nv_bfloat16 *x, *lam_re, *lam_im, *b_re, *b_im, *c_re, *c_im, *log_dt, *dskip, *w_r, *gate_w;
    float* out;
    Scratch* s;
    int fetch[23], use[23];
    int swapped;
};

__device__ __forceinline__ uint32_t smem_u32(const void* p) { return (uint32_t)__cvta_generic_to_shared(p); }
__device__ __forceinline__ void mbar_init(uint32_t bar, uint32_t cnt) { asm volatile("mbarrier.init.shared::cta.b64 [%0], %1;" ::"r"(bar), "r"(cnt) : "memory"); }
__device__ __forceinline__ void mbar_expect_tx(uint32_t bar, uint32_t bytes) { asm volatile("mbarrier.arrive.expect_tx.shared::cta.b64 _, [%0], %1;" ::"r"(bar), "r"(bytes) : "memory"); }
__device__ __forceinline__ void mbar_arrive(uint32_t bar) { asm volatile("mbarrier.arrive.shared::cta.b64 _, [%0];" ::"r"(bar) : "memory"); }
__device__ __forceinline__ bool mbar_try(uint32_t bar, uint32_t parity) {
    uint32_t ok;
    asm volatile("{ .reg .pred p; mbarrier.try_wait.parity.shared::cta.b64 p, [%1], %2; selp.u32 %0, 1, 0, p; }" : "=r"(ok) : "r"(bar), "r"(parity) : "memory");
    return ok;
}
__device__ __forceinline__ bool mbar_test(uint32_t bar, uint32_t parity) {
    uint32_t ok;
    asm volatile("{ .reg .pred p; mbarrier.test_wait.parity.shared::cta.b64 p, [%1], %2; selp.u32 %0, 1, 0, p; }" : "=r"(ok) : "r"(bar), "r"(parity) : "memory");
    return __all_sync(0xffffffffu, ok);
}
__device__ __forceinline__ void mbar_wait(uint32_t bar, uint32_t parity = 0) {
    if (mbar_try(bar, parity)) return;
#pragma unroll 1
    for (uint32_t it = 0; it < SPIN_LIMIT; ++it)
        if (mbar_try(bar, parity)) return;
    __trap();
}
__device__ __forceinline__ bool elect_one() {
    uint32_t pred;
    asm volatile("{ .reg .pred P; elect.sync _|P, 0xffffffff; selp.b32 %0, 1, 0, P; }" : "=r"(pred));
    return pred;
}
__device__ __forceinline__ void named_bar(int id, int n) { asm volatile("bar.sync %0, %1;" ::"r"(id), "r"(n) : "memory"); }
__device__ __forceinline__ void fence_mbar_init() { asm volatile("fence.mbarrier_init.release.cluster;" ::: "memory"); }
__device__ __forceinline__ void fence_async_smem() { asm volatile("fence.proxy.async.shared::cta;" ::: "memory"); }

__device__ __forceinline__ void bulk_load(uint32_t dst, const void* src, uint32_t bytes, uint32_t bar) {
    asm volatile("cp.async.bulk.shared::cluster.global.mbarrier::complete_tx::bytes [%0], [%1], %2, [%3];" ::"r"(dst), "l"(src), "r"(bytes), "r"(bar) : "memory");
}
__device__ __forceinline__ void cp_async16(uint32_t dst, const void* src) { asm volatile("cp.async.cg.shared.global [%0], [%1], 16;" ::"r"(dst), "l"(src) : "memory"); }
__device__ __forceinline__ void sts128(uint32_t a, uint32_t x, uint32_t y, uint32_t z, uint32_t w) {
    asm volatile("st.shared.v4.u32 [%0], {%1,%2,%3,%4};" ::"r"(a), "r"(x), "r"(y), "r"(z), "r"(w) : "memory");
}
__device__ __forceinline__ uint2 lds64(uint32_t a) {
    uint2 v;
    asm volatile("ld.shared.v2.u32 {%0,%1}, [%2];" : "=r"(v.x), "=r"(v.y) : "r"(a) : "memory");
    return v;
}
__device__ __forceinline__ uint32_t lds32(uint32_t a) {
    uint32_t v;
    asm volatile("ld.volatile.shared.u32 %0, [%1];" : "=r"(v) : "r"(a) : "memory");
    return v;
}
__device__ __forceinline__ void stg128(void* p, uint32_t x, uint32_t y, uint32_t z, uint32_t w) {
    asm volatile("st.global.v4.u32 [%0], {%1,%2,%3,%4};" ::"l"(p), "r"(x), "r"(y), "r"(z), "r"(w) : "memory");
}
__device__ __forceinline__ void st_relaxed(void* p, uint32_t x) { asm volatile("st.relaxed.gpu.global.b32 [%0], %1;" ::"l"(p), "r"(x) : "memory"); }
__device__ __forceinline__ void st_relaxed2(void* p, uint32_t x, uint32_t y) { asm volatile("st.relaxed.gpu.global.v2.b32 [%0], {%1, %2};" ::"l"(p), "r"(x), "r"(y) : "memory"); }
__device__ __forceinline__ void st_relaxed4(void* p, uint32_t x, uint32_t y, uint32_t z, uint32_t w) {
    asm volatile("st.relaxed.gpu.global.v4.b32 [%0], {%1, %2, %3, %4};" ::"l"(p), "r"(x), "r"(y), "r"(z), "r"(w) : "memory");
}
__device__ __forceinline__ uint32_t ld_relaxed(const void* p) {
    uint32_t v;
    asm volatile("ld.relaxed.gpu.global.b32 %0, [%1];" : "=r"(v) : "l"(p) : "memory");
    return v;
}
__device__ __forceinline__ uint2 ld_relaxed2(const void* p) {
    uint2 v;
    asm volatile("ld.relaxed.gpu.global.v2.b32 {%0, %1}, [%2];" : "=r"(v.x), "=r"(v.y) : "l"(p) : "memory");
    return v;
}
__device__ __forceinline__ uint4 ld_relaxed4(const void* p) {
    uint4 v;
    asm volatile("ld.relaxed.gpu.global.v4.b32 {%0, %1, %2, %3}, [%4];" : "=r"(v.x), "=r"(v.y), "=r"(v.z), "=r"(v.w) : "l"(p) : "memory");
    return v;
}
__device__ __forceinline__ uint32_t clk32() { uint32_t c; asm volatile("mov.u32 %0, %%clock;" : "=r"(c)); return c; }
__device__ __forceinline__ uint32_t gtime32() { uint32_t c; asm volatile("mov.u32 %0, %%globaltimer_lo;" : "=r"(c)); return c; }
__device__ __forceinline__ void sched_fence(uint32_t t) { while ((int)(clk32() - t) < 0) {} }
__device__ __forceinline__ void sleep_until(uint32_t t) { while ((int)(clk32() - t) < 0) __nanosleep(40); }

__device__ __forceinline__ void tma2(uint32_t dst, const CUtensorMap* m, int c0, int c1, uint32_t bar) {
    asm volatile("{ .reg .b64 pol; createpolicy.fractional.L2::evict_first.b64 pol;\n"
                 "cp.async.bulk.tensor.2d.shared::cluster.global.mbarrier::complete_tx::bytes.L2::cache_hint [%0], [%1, {%3, %4}], [%2], pol; }"
                 ::"r"(dst), "l"(m), "r"(bar), "r"(c0), "r"(c1) : "memory");
}
__device__ __forceinline__ void tma3(uint32_t dst, const CUtensorMap* m, int c0, int c1, uint32_t bar) {
    asm volatile("cp.async.bulk.tensor.3d.shared::cluster.global.mbarrier::complete_tx::bytes [%0], [%1, {%3, %4, %5}], [%2];"
                 ::"r"(dst), "l"(m), "r"(bar), "r"(c0), "r"(c1), "r"(0) : "memory");
}
__device__ __forceinline__ void tma4(uint32_t dst, const CUtensorMap* m, int c0, int c3, uint32_t bar) {
    asm volatile("cp.async.bulk.tensor.4d.shared::cluster.global.mbarrier::complete_tx::bytes [%0], [%1, {%3, %5, %5, %4}], [%2];"
                 ::"r"(dst), "l"(m), "r"(bar), "r"(c0), "r"(c3), "r"(0) : "memory");
}
__device__ __forceinline__ void tma5(uint32_t dst, const CUtensorMap* m, int c0, int c4, uint32_t bar) {
    asm volatile("cp.async.bulk.tensor.5d.shared::cluster.global.mbarrier::complete_tx::bytes [%0], [%1, {%3, %5, %5, %5, %4}], [%2];"
                 ::"r"(dst), "l"(m), "r"(bar), "r"(c0), "r"(c4), "r"(0) : "memory");
}
__device__ __forceinline__ void tma5b(uint32_t dst, const CUtensorMap* m, int c0, int c3, uint32_t bar) {
    asm volatile("cp.async.bulk.tensor.5d.shared::cluster.global.mbarrier::complete_tx::bytes [%0], [%1, {%3, %5, %5, %4, %5}], [%2];"
                 ::"r"(dst), "l"(m), "r"(bar), "r"(c0), "r"(c3), "r"(0) : "memory");
}
__device__ __forceinline__ void prefetch_l2(const void* p) { asm volatile("prefetch.global.L2 [%0];" ::"l"(p)); }
__device__ __forceinline__ void prefetch_slice(const CUtensorMap* m, int line, int row) {
    asm volatile("cp.async.bulk.prefetch.tensor.4d.L2.global [%0, {%3, %1, %2, %3}];" ::"l"(m), "r"(line), "r"(row), "r"(0) : "memory");
}
__device__ __forceinline__ void prefetch_map(const CUtensorMap* m) { asm volatile("prefetch.tensormap [%0];" ::"l"(m)); }
__device__ __forceinline__ uint32_t uni(uint32_t v) { return __shfl_sync(0xffffffffu, v, 0); }

__device__ __forceinline__ uint64_t make_desc(uint32_t addr) {
    return (uint64_t)((addr & 0x3FFFF) >> 4) | ((uint64_t)1 << 16) | ((uint64_t)64 << 32) | ((uint64_t)1 << 62);
}
__device__ __forceinline__ uint64_t make_desc_h(uint32_t addr) {
    return (uint64_t)((addr & 0x3FFFF) >> 4) | ((uint64_t)32 << 16) | ((uint64_t)64 << 32) | ((uint64_t)2 << 62);
}
__device__ __forceinline__ void wgmma_fence() { asm volatile("wgmma.fence.sync.aligned;" ::: "memory"); }
__device__ __forceinline__ void wgmma_commit() { asm volatile("wgmma.commit_group.sync.aligned;" ::: "memory"); }
template <int N> __device__ __forceinline__ void wgmma_wait() { asm volatile("wgmma.wait_group.sync.aligned %0;" ::"n"(N) : "memory"); }

#define R8(d, i) "+f"(d[i]), "+f"(d[i + 1]), "+f"(d[i + 2]), "+f"(d[i + 3]), "+f"(d[i + 4]), "+f"(d[i + 5]), "+f"(d[i + 6]), "+f"(d[i + 7])
#define R64(d) R8(d, 0), R8(d, 8), R8(d, 16), R8(d, 24), R8(d, 32), R8(d, 40), R8(d, 48), R8(d, 56)
template <int TA>
__device__ __forceinline__ void wgmma_n128(float (&d)[64], uint64_t da, uint64_t db, int scale_d = 1) {
    asm volatile("{ .reg .pred p; setp.ne.b32 p, %66, 0;\n"
                 "wgmma.mma_async.sync.aligned.m64n128k16.f32.bf16.bf16 "
                 "{%0,%1,%2,%3,%4,%5,%6,%7,%8,%9,%10,%11,%12,%13,%14,%15,%16,%17,%18,%19,%20,%21,%22,%23,%24,%25,%26,%27,%28,%29,%30,%31,"
                 "%32,%33,%34,%35,%36,%37,%38,%39,%40,%41,%42,%43,%44,%45,%46,%47,%48,%49,%50,%51,%52,%53,%54,%55,%56,%57,%58,%59,%60,%61,%62,%63}, "
                 "%64, %65, p, 1, 1, %67, 0; }"
                 : R64(d)
                 : "l"(da), "l"(db), "r"(scale_d), "n"(TA));
}
__device__ __forceinline__ void pin4(float (&d)[4]) { asm volatile("" : "+f"(d[0]), "+f"(d[1]), "+f"(d[2]), "+f"(d[3])::"memory"); }
__device__ __forceinline__ void pin64(float (&d)[64]) { asm volatile("" : R64(d)::"memory"); }

template <int TA>
__device__ __forceinline__ void wgmma_n8(float (&d)[4], uint64_t da, uint64_t db, int scale_d = 1) {
    asm volatile("{ .reg .pred p; setp.ne.b32 p, %7, 0;\n"
                 "wgmma.mma_async.sync.aligned.m64n8k16.f32.bf16.bf16 {%0,%1,%2,%3}, %4, %5, p, 1, 1, %6, 0; }"
                 : "+f"(d[0]), "+f"(d[1]), "+f"(d[2]), "+f"(d[3])
                 : "l"(da), "l"(db), "n"(TA), "r"(scale_d));
}

__device__ __forceinline__ float bf_lo(uint32_t u) { return __uint_as_float(u << 16); }
__device__ __forceinline__ float bf_hi(uint32_t u) { return __uint_as_float(u & 0xFFFF0000u); }
__device__ __forceinline__ float rbf(float v) { return __bfloat162float(__float2bfloat16_rn(v)); }
__device__ __forceinline__ uint32_t pack_bf(float lo, float hi) {
    uint32_t r;
    asm("cvt.rn.bf16x2.f32 %0, %1, %2;" : "=r"(r) : "f"(hi), "f"(lo));
    return r;
}
__device__ __forceinline__ uint32_t mul_bf2(uint32_t a, uint32_t b) {
    uint32_t r;
    asm("mul.rn.bf16x2 %0, %1, %2;" : "=r"(r) : "r"(a), "r"(b));
    return r;
}
__device__ __forceinline__ uint32_t fma_bf2(uint32_t a, uint32_t b, uint32_t c) {
    uint32_t r;
    asm("fma.rn.bf16x2 %0, %1, %2, %3;" : "=r"(r) : "r"(a), "r"(b), "r"(c));
    return r;
}
__device__ __forceinline__ float2 cmul(float2 a, float2 b) { return make_float2(a.x * b.x - a.y * b.y, a.x * b.y + a.y * b.x); }
__device__ __forceinline__ float2 cfma(float2 a, float2 b, float2 c) {
    return make_float2(fmaf(a.x, b.x, fmaf(-a.y, b.y, c.x)), fmaf(a.x, b.y, fmaf(a.y, b.x, c.y)));
}
__device__ __forceinline__ float sigmoidf_(float v) { return __fdividef(1.0f, 1.0f + expf(-v)); }

#define SCHED_NAMES RT0, RT1, RT2, RT3, PF0, PF1, PF2, PF3, T_SMALL, T_INIT, T_X0, T_BASE, G_NS, GT0, GT1, GT2, G0, GAP0, GAP1, RS_E, \
    PB_E0, PB_STEP, PC_E0, PC_STEP, PC_N, PC_E1, PC_S1, GU_E0, W_NUM, GC0, N1, N2, GCS, GCS2, GCS3, GCS4, HG, DL0, DLS, DC0, DCS, DN_E0, WDBG, HDBG
enum { SCHED_NAMES, NTUNE };
constexpr int sched_default[NTUNE] = {
    1000, 2500, 3000, 3000,
    0, 1100, 1300, 2800,
    200, 500, 1, 2500, 3,
    6900, 0, 0,
    1500, 50, 50, 4,
    4, 1, 9, 4, 5, 50, 3,
    4, 9, 16, 5, 5, 8, 8, 4, 4, 43, 37, 9, 40, 1, 50,
    0, 0};
template <int I> struct Sched { static constexpr int v = sched_default[I]; };
#define TN(i) (Sched<i>::v)
#define DBG 0
#define NKK 4
#define GE 8
#define DOUBLE 0
#define RAISE_J 1
#define GREEDY 0
#define POLL_S 24
#define REL_KK 1
#define PROMO CU_TENSOR_MAP_L2_PROMOTION_L2_256B

template <int TA, bool FRESH>
__device__ __forceinline__ void run_entries(uint32_t sb, int lo, int hi, int slot, float (&accA)[64], float (&accB)[64]) {
    const uint64_t da0 = TA ? make_desc_h(sb) : make_desc(sb), db0 = make_desc(sb + 2 * TILE);
    const bool leader = (threadIdx.x & 31) == 0;
    uint32_t prev = FRESH ? sb + OFF_FULL + 8 * 80 : sb + OFF_EMPTY + 8 * (lo - 1);
#pragma unroll 1
    for (int i = lo; i < hi; i++) {
        const uint32_t bar = sb + OFF_FULL + 8 * i;
        mbar_wait(bar);
        KSTAMP(i);
        const uint64_t da = da0 + (uint64_t)(slot * (SLOT >> 4)), db = db0 + (uint64_t)(slot * (SLOT >> 4));
        slot = slot == NST - 1 ? 0 : slot + 1;
        wgmma_fence();
#pragma unroll
        for (int kk = 0; kk < 4; kk++) {
            wgmma_n128<TA>(accA, da + kk * (TA ? 128 : 2), db + kk * 2, !FRESH || kk > 0 || i != lo);
            wgmma_n128<TA>(accB, da + 512 + kk * (TA ? 128 : 2), db + kk * 2, !FRESH || kk > 0 || i != lo);
            if (kk == REL_KK) {
                wgmma_commit();
                wgmma_wait<1>();
                if (leader) mbar_arrive(prev);
            }
        }
        if (REL_KK < 3) wgmma_commit();
        prev = bar + (OFF_EMPTY - OFF_FULL);
    }
}

template <int TA>
__device__ __forceinline__ void small_tile(float (&acc)[4], uint64_t da, uint64_t db, bool first) {
#pragma unroll
    for (int kk = 0; kk < 4; kk++) wgmma_n8<TA>(acc, da + kk * (TA ? 128 : 2), db + kk * 2, kk > 0 || !first);
}

__global__ void __launch_bounds__(512, 1)
fused_kernel(const __grid_constant__ CUtensorMap mX, const __grid_constant__ CUtensorMap mB, const __grid_constant__ CUtensorMap mCre,
             const __grid_constant__ CUtensorMap mCim, const __grid_constant__ CUtensorMap mWg, const __grid_constant__ CUtensorMap mWu,
             const __grid_constant__ CUtensorMap mWd, const __grid_constant__ CUtensorMap mXr, const __grid_constant__ CUtensorMap mPB,
             const __grid_constant__ CUtensorMap mPC, const __grid_constant__ CUtensorMap mXe, const __grid_constant__ Params prm) {
    extern __shared__ __align__(1024) uint8_t smem[];
    uint32_t sb;
    asm volatile("mov.u32 %0, %1;" : "=r"(sb) : "r"(smem_u32(smem)));
    const int tid = threadIdx.x, warp = __shfl_sync(0xffffffffu, tid >> 5, 0), lane = tid & 31;
    const int cta = blockIdx.x;
    const uint32_t cstart = clk32();
    const int chunk = (cta >> 2) & 15;
    const int dt = (cta >> 6) * 4 + (cta & 3);
    const int rid = chunk * 8 + dt;
    const bool has_gu = cta < 112;
    const uint32_t full = sb + OFF_FULL, empty = sb + OFF_EMPTY;
    const uint32_t ffull = full + 8 * 85, fempty = empty + 8 * 65;
    const uint32_t bar_epoch = full + 8 * 72, dfull = full + 8 * 73, bar_base = full + 8 * 82, bar_x = full + 8 * 83;
    const uint32_t bar_order = empty + 8 * 70, bar_const = empty + 8 * 93, bar_stored = empty + 8 * 72, bar_dfree = empty + 8 * 73,
                    bar_g = empty + 8 * 92, bar_out = empty + 8 * 76, bar_ready = empty + 8 * 84;
    const int w = warp & 3, g = lane >> 2, c = lane & 3, at = tid & 127;

    STAMPIF(tid == 0, 0);
    GSTAMP(tid == 0, 94);
    auto init_barriers = [&]() {
        if (elect_one()) {
            const uint32_t base = warp < 6 ? full + min(8 * NST + 128 * warp, 8 * 74) : empty + min(128 * (warp - 6), 8 * 78), cnt = warp < 6 ? 1 : 4;
#pragma unroll
            for (int i = 0; i < 16; i++) mbar_init(base + 8 * i, cnt);
            fence_mbar_init();
        }
        __syncwarp();
    };
    if (warp != 12) {
        if (warp >= 14) {
            const int r = cta * 8 + g;
            if (warp == 15 && !(cta & 3) && lane < 8) st_relaxed((uint32_t*)&prm.s->start[cta >> 1] + lane, (lane & 1) ? gtime32() : cstart);
            prefetch_l2(warp == 14 ? (const char*)prm.x + (rid * 16 + (lane >> 1)) * 2048 + (c & 1) * 128
                                   : (const char*)((r & 512) ? prm.b_im : prm.b_re) + (r & 511) * 2048 + (c & TN(T_X0)) * 128);
        }
        sleep_until(cstart + (warp == 13 ? TN(T_SMALL) : TN(T_INIT)));
    }
    if (warp < 8) {
        init_barriers();
        asm volatile("setmaxnreg.inc.sync.aligned.u32 200;");
        named_bar(0, 480);
        STAMPIF(tid == 0 && lds32(sb + OFF_KEYS + 16) == 0, 8);
        const int wg = warp >> 2;
        const int p = wg * 512 + dt * 32 + w * 8 + g;
        uint32_t cp = sb + OFF_CONST + 8 * (wg * 64 + w * 8 + g);
        const int j1 = chunk - 1 - c;
        uint2* cq = &prm.s->carry[j1 * 1024 + p];
        char* hd = reinterpret_cast<char*>(prm.s->h) + (size_t)chunk * 524288 + wg * 262144 + (dt >> 1) * 16384 + ((dt & 1) * 4 + w) * 1024 + g * 64 + ((c ^ (g >> 1)) << 4);
        const bool never = uni(cstart == 0 && sb == 0);
        asm volatile("" : "+l"(cq), "+l"(hd), "+r"(cp));
        if (wg == 1) {
            const int pc = w * 256 + dt * 32 + lane;
            const float lr = __bfloat162float(prm.lam_re[pc]), li = __bfloat162float(prm.lam_im[pc]), ld = __bfloat162float(prm.log_dt[pc]);
            const uint32_t dk = __ldg(reinterpret_cast<const uint32_t*>(prm.dskip + dt * 128) + (at & 63));
            reinterpret_cast<uint32_t*>(smem + OFF_DK)[at & 63] = dk;
            const float dtv = rbf(expf(ld));
            const float er = expf(dtv * lr);
            float sn, cs;
            sincosf(dtv * li, &sn, &cs);
            const float ar = er * cs, ai = er * sn;
            const float nr = ar - 1.0f, ni = ai;
            const bool big = fabsf(lr) >= fabsf(li);
            const float t = (big ? li : lr) / (big ? lr : li), dn = big ? lr + li * t : lr * t + li;
            const float cr = (big ? nr + ni * t : nr * t + ni) / dn, ci = (big ? ni - nr * t : ni * t - nr) / dn;
            float2* ct = reinterpret_cast<float2*>(smem + OFF_CONST) + at;
            float2 pw = make_float2(ar, prm.swapped ? -ai : ai);
            ct[0] = pw;
            const float mx = prm.swapped ? -2.f * ci : 2.f * cr, my = prm.swapped ? 2.f * cr : -2.f * ci;
            reinterpret_cast<uint32_t*>(smem + OFF_M)[at] = pack_bf(mx, my);
            *reinterpret_cast<float2*>(smem + OFF_ONE) = make_float2(1.f, 0.f);
#pragma unroll
            for (int i = 0; i < 5; i++) pw = cmul(pw, pw);
#pragma unroll
            for (int i = 0; i < 2; i++) {
                const float2 p2 = cmul(pw, pw);
                ct[128 + 384 * i] = pw; ct[256 + 384 * i] = p2; ct[384 + 384 * i] = cmul(p2, pw);
                pw = cmul(p2, p2);
            }
            ct[896] = pw;
            mbar_wait(bar_epoch);
            __syncwarp();
            mbar_wait(empty + 8 * TN(RS_E));
            st_relaxed2(&prm.s->hid[cta * 128 + at], ~0u, ~0u);
            st_relaxed4(&prm.s->y[((at >> 4) * 8 + (cta >> 4)) * D_ + (cta & 15) * 64 + (at & 15) * 4], 0u, 0u, 0u, 0u);
            st_relaxed2(&prm.s->carry[chunk * 1024 + pc], 0u, 0u);
            if (at < 32) st_relaxed2(&prm.s->flag[(chunk * 8 + (at >> 2)) * 32 + dt * 4 + (at & 3)], 0u, 0u);
            __syncwarp();
            if (lane == 0) mbar_arrive(bar_const);

            STAMPIF(at == 0, 3);
            mbar_wait(bar_order);
        }

        float accA[64], accB[64];
        run_entries<0, true>(sb, wg * 16, wg * 16 + GE, wg, accA, accB);
        mbar_wait(bar_const);
        const uint32_t t2 = lds32(sb + OFF_EPOCH + 4), tag = lds32(sb + OFF_EPOCH);
        float2 a[2], a32[2], a64[2], a512[2], pw32[2], pw128[2];
        uint32_t mm[2];
        {
            auto ldc = [](uint32_t a) { const uint2 v = lds64(a); return make_float2(__uint_as_float(v.x), __uint_as_float(v.y)); };
#pragma unroll
            for (int h = 0; h < 2; h++) {
                a[h] = ldc(cp + 256 * h); a32[h] = ldc(cp + 256 * h + 1024); a64[h] = ldc(cp + 256 * h + 2048); a512[h] = ldc(cp + 256 * h + 7168);
                pw32[h] = ldc(c ? cp + 256 * h + 1024 * c : sb + OFF_ONE);
                pw128[h] = ldc(c ? cp + 256 * h + 3072 + 1024 * c : sb + OFF_ONE);
                mm[h] = lds32(sb + OFF_M + 4 * (wg * 64 + w * 8 + g + 32 * h));
            }
        }
        mbar_wait(bar_base);
        sched_fence(lds32(sb + OFF_EPOCH + 8) + (wg ? TN(GT1) : TN(GT0)));
        run_entries<0, false>(sb, wg * 16 + GE, wg * 16 + 16, (wg + GE) % NST, accA, accB);
        if (lane == 0) mbar_arrive(bar_order + 8 * wg);
        uint2 v[2][4];
#pragma unroll
        for (int m = 0; m < 8; m++) v[m >> 2][m & 3] = make_uint2(t2, t2);
        wgmma_wait<0>();
        pin64(accA); pin64(accB);
        if (lane == 0) mbar_arrive(empty + 8 * (wg * 16 + 15));
        STAMPIF(at == 0, 30 + 10 * wg);

        auto cut = [&]() { if (never) sched_fence(cstart); };
        auto poll = [&](uint2 (&u)[4], int h) {
#pragma unroll
            for (int m = 0; m < 4; m++)
                asm volatile("{ .reg .pred p; setp.ge.s32 p, %3, %4; @p ld.relaxed.gpu.global.v2.b32 {%0, %1}, [%2]; }"
                             : "+r"(u[m].x), "+r"(u[m].y) : "l"(cq + 256 * h - 4096 * m), "r"(j1), "r"(4 * m) : "memory");
        };
        auto check = [&](const uint2 (&u)[4]) {
            uint32_t bad = 0;
#pragma unroll
            for (int m = 0; m < 4; m++) bad |= (u[m].x ^ t2) | (u[m].y ^ t2);
            return bad;
        };
        auto valid = [&](const uint2 (&u)[4]) { return __all_sync(0xffffffffu, (check(u) & 3u) == 0); };

        auto horner = [&](const uint2 (&u)[4], int h) {
            float2 r = make_float2(__uint_as_float(u[3].x), __uint_as_float(u[3].y));
#pragma unroll
            for (int m = 2; m >= 0; m--) r = cfma(a512[h], r, make_float2(__uint_as_float(u[m].x), __uint_as_float(u[m].y)));
            return r;
        };
        float2 w0[2];
#pragma unroll
        for (int h = 0; h < 2; h++) {
            float (&acc)[64] = h ? accB : accA;
            float2 e = make_float2(acc[0], acc[2]);
#pragma unroll
            for (int s = 1; s < 32; s++) {
                const int i0 = 4 * (s >> 1) + (s & 1);
                e = cfma(a[h], e, make_float2(acc[i0], acc[i0 + 2]));
                if (!GREEDY && h == 1 && s == POLL_S) { cut(); poll(v[0], 0); }
            }
            float2 y = make_float2(__shfl_up_sync(0xffffffffu, e.x, 1, 4), __shfl_up_sync(0xffffffffu, e.y, 1, 4));
            if (c >= 1) e = cfma(a32[h], y, e);
            y = make_float2(__shfl_up_sync(0xffffffffu, e.x, 2, 4), __shfl_up_sync(0xffffffffu, e.y, 2, 4));
            if (c >= 2) e = cfma(a64[h], y, e);
            if (c == 3) st_relaxed2(cq + 4096 + 256 * h, (__float_as_uint(e.x) & ~3u) | t2, (__float_as_uint(e.y) & ~3u) | t2);
            if (h || !GREEDY) cut();
            w0[h] = make_float2(__shfl_up_sync(0xffffffffu, e.x, 1, 4), __shfl_up_sync(0xffffffffu, e.y, 1, 4));
            if (c == 0) w0[h] = make_float2(0.f, 0.f);
            STAMPIF(at == 0 && (h || !GREEDY), 31 + h + 10 * wg);
        }
        if (GREEDY) { __nanosleep(100); poll(v[0], 0); __nanosleep(100); }
        const char* rb = hd + (c >> 1) * 8192 + (c & 1) * 512;
        uint2* fp = &prm.s->flag[(chunk * 8 + 4 * wg) * 32 + dt * 4 + w];
        uint32_t sx[2][16], sy[2][16], mr[2][4], tp, back = 0;
        const uint32_t gap = wg ? TN(GAP1) : TN(GAP0);
#pragma unroll
        for (int h = 0; h < 2; h++) {
            const uint32_t sg = prm.swapped ? 0x80008000u : 0u;
            mr[h][0] = __byte_perm(mm[h], 0, 0x1010); mr[h][1] = __byte_perm(mm[h], 0, 0x3232);
            mr[h][2] = mr[h][1] ^ sg; mr[h][3] = mr[h][0] ^ sg ^ 0x80008000u;
        }
        auto read_back = [&](int e) {
            asm volatile("{ .reg .pred p; setp.eq.u32 p, %2, 0; @p ld.relaxed.gpu.global.b32 %0, [%1]; }" : "+r"(back) : "l"(rb + e * 65536), "r"((g & 1) | (TN(HDBG) & 16)) : "memory");
        };
        auto put = [&](int e, int j) {
            uint32_t d[4];
#pragma unroll
            for (int u = 0; u < 4; u++) d[u] = fma_bf2(mr[e >> 1][2 * (e & 1)], sx[e >> 1][4 * j + u], mul_bf2(mr[e >> 1][2 * (e & 1) + 1], sy[e >> 1][4 * j + u]));
            if (!(TN(HDBG) & 4) || d[0] == 0x12345) stg128(hd + e * 65536 + (j >> 1) * 8192 + (j & 1) * 512, d[0], d[1], d[2], d[3]);
            if (j == 3 && e < 3) read_back(e);
        };
        auto raise = [&](int e) {
            if (lane == 0) {
                st_relaxed2(fp + 32 * e, tag, back);
                mbar_arrive(bar_out + 32 * wg + 8 * e);
            }
            STAMPIF(at == 0 && e == 0 && back != 0x1234567, 18 + wg);
        };
#pragma unroll
        for (int h = 0; h < 2; h++) {
            float (&acc)[64] = h ? accB : accA;
            float2 hin;
            uint32_t it = 0;
            if (h == 0 && DOUBLE) {
                while (true) {
                    poll(v[1], 0);
                    if (valid(v[0])) { hin = horner(v[0], 0); break; }
                    poll(v[0], 0);
                    if (valid(v[1])) { hin = horner(v[1], 0); it++; break; }
                    if (++it > SPIN_LIMIT) __trap();
                }
            } else {
                if (h) raise(1);
                while (!valid(v[0])) {
                    poll(v[0], h);
                    if (++it > SPIN_LIMIT) __trap();
                }
                hin = horner(v[0], h);
            }
            STAMPIF(at == 0 && it > 0 && h == 0, 39 + 10 * wg);
            hin = cmul(pw128[h], hin);
            hin.x += __shfl_xor_sync(0xffffffffu, hin.x, 1); hin.y += __shfl_xor_sync(0xffffffffu, hin.y, 1);
            hin.x += __shfl_xor_sync(0xffffffffu, hin.x, 2); hin.y += __shfl_xor_sync(0xffffffffu, hin.y, 2);
            float2 st = cfma(pw32[h], hin, w0[h]);
            STAMPIF(at == 0, 33 + 3 * h + 10 * wg);
#pragma unroll
            for (int j = 0; j < 4; j++) {
#pragma unroll
                for (int u = 0; u < 4; u++) {
                    const int i0 = 16 * j + 4 * u;
                    const float2 y = cfma(a[h], st, make_float2(acc[i0], acc[i0 + 2]));
                    st = cfma(a[h], y, make_float2(acc[i0 + 1], acc[i0 + 3]));
                    sx[h][4 * j + u] = pack_bf(y.x, st.x); sy[h][4 * j + u] = pack_bf(y.y, st.y);
                }
                if (h) sleep_until(tp += gap);
                put(2 * h, j);
                cut();
            }
            STAMPIF(at == 0, 34 + 3 * h + 10 * wg);
            tp = clk32();
#pragma unroll
            for (int j = 0; j < 4; j++) {
                if (j == RAISE_J) {
                    raise(2 * h);
                    if (h == 0) poll(v[0], 1);
                }
                sleep_until(tp += gap);
                put(2 * h + 1, j);
            }
        }
        STAMPIF(at == 0, 38 + 10 * wg);

        if (wg == 1) {
            read_back(3);
            raise(3);
        } else {
            __syncwarp();
            if (lane == 0) mbar_arrive(bar_out + 24);
            const int tl = 64 * (w & 1) + 8 * (w >> 1) + g;
            float gf[4];
            mbar_wait(bar_g);
#pragma unroll
            for (int r = 0; r < 4; r++) gf[r] = __bfloat162float(reinterpret_cast<const __nv_bfloat16*>(smem + OFF_G)[tl + (r & 1) * 32 + (r >> 1) * 16]);
            float* op = prm.out + (size_t)(chunk * 128 + tl) * D_ + dt * 128 + 4 * c;
            const int xr = 2 * (g & 3) + (g >> 2);
            uint32_t xs = sb + OFF_FT + 3 * TILE + (32 * (w & 1) + 8 * (w >> 1) + xr) * 128 + (((c >> 1) ^ xr) << 4) + (c & 1) * 8;
            asm volatile("" : "+f"(gf[0]), "+f"(gf[1]), "+f"(gf[2]), "+f"(gf[3]), "+l"(op), "+r"(xs));
            float outA[64], outB[64];
            STAMPIF(at == 0, 9);
            mbar_wait(bar_order + 8);
            STAMPIF(at == 0, 35);
            sched_fence(lds32(sb + OFF_EPOCH + 8) + TN(GT2));
            run_entries<1, true>(sb, 32, NBIG, 32 % NST, outA, outB);
            uint32_t gp[2], om[2];
            uint2 xa[2][8], xb[2][8];
            auto coef = [&](int r0) {
#pragma unroll
                for (int r = 0; r < 2; r++) {
                    const float gv = gf[r0 + r];
                    const bool routed = (int)__float_as_uint(gv) < 0;
                    gp[r] = routed ? 0u : pack_bf(gv, gv); om[r] = routed ? 0u : pack_bf(1.0f - gv, 1.0f - gv);
                }
            };
            auto load_x = [&](uint2 (&xv)[2][8], int r0, int j) {
#pragma unroll
                for (int r = 0; r < 2; r++) xv[r][j] = lds64((xs ^ ((j & 3) << 5)) + (r0 + (j >> 2)) * TILE + r * 2048);
            };
            auto term = [&](uint2 (&xv)[2][8], int j) {
                const uint2 dk = lds64(sb + OFF_DK + c * 8 + 32 * j);
#pragma unroll
                for (int r = 0; r < 2; r++) {
                    xv[r][j].x = mul_bf2(xv[r][j].x, fma_bf2(gp[r], dk.x, om[r]));
                    xv[r][j].y = mul_bf2(xv[r][j].y, fma_bf2(gp[r], dk.y, om[r]));
                }
            };
            auto store = [&](const float (&acc)[64], const uint2 (&xv)[2][8], int r0, int j, int r) {
                const int o = 8 * j + 2 * r;
                const float gv = fabsf(gf[r0 + r]);
                stg128(op + (r * 32 + r0 * 8) * D_ + 16 * j, __float_as_uint(fmaf(gv, acc[o], bf_lo(xv[r][j].x))), __float_as_uint(fmaf(gv, acc[o + 1], bf_hi(xv[r][j].x))),
                       __float_as_uint(fmaf(gv, acc[o + 4], bf_lo(xv[r][j].y))), __float_as_uint(fmaf(gv, acc[o + 5], bf_hi(xv[r][j].y))));
            };
            uint64_t dh = make_desc_h(sb), dc = make_desc(sb);
#pragma unroll
            for (int n = 0; n < 16; n++) {
                const int j = n & 7;
                asm volatile("mov.b64 %0, %0; mov.b64 %1, %1;" : "+l"(dh), "+l"(dc));
                if (n < 10 || !(n & 1)) mbar_wait(full + 8 * (NBIG + n));
                KSTAMP(NBIG + n);
                const uint64_t da = dh + (uint64_t)(tail_h(n) >> 4), db = dc + (uint64_t)(tail_c(j) >> 4);
                wgmma_fence();
#pragma unroll
                for (int kk = 0; kk < 4; kk++) {
                    wgmma_n128<1>(n < 8 ? outA : outB, da + kk * 128, db + kk * 2);
                    if (n > 8 && (kk & 1)) store(outA, xa, 0, j, kk >> 1);
                    if (n > 11 && !(kk & 1)) load_x(xb, 2, 2 * n - 24 + (kk >> 1));
                }
                wgmma_commit();
                if (n == 3) coef(0);
                if (n == 4 || n == 11) mbar_wait(bar_x + (n & 8));
                if (n >= 4 && n < 8) { load_x(xa, 0, 2 * n - 8); load_x(xa, 0, 2 * n - 7); }
                if (n < 10) {
                    wgmma_wait<1>();
                    if (lane == 0) mbar_arrive(empty + 8 * (NBIG + n - 1));
                }
                if (n >= 4 && n < 8) { term(xa, 2 * n - 8); term(xa, 2 * n - 7); }
                if (n == 8) {
                    pin64(outA);
                    store(outA, xa, 0, 0, 0);
                    store(outA, xa, 0, 0, 1);
                }
            }
            coef(2);
            term(xb, 0);
            wgmma_wait<0>();
            pin64(outB);
            STAMPIF(at == 0, 51);
#pragma unroll
            for (int j = 0; j < 8; j++) {
                if (j) term(xb, j);
                store(outB, xb, 2, j, 0);
                store(outB, xb, 2, j, 1);
            }
            __syncwarp();
            if (lane == 0) mbar_arrive(bar_stored);
            STAMPIF(at == 0, 52);
        }
    } else if (warp < 12) {
        asm volatile("setmaxnreg.dec.sync.aligned.u32 72;");
        init_barriers();
#pragma unroll
        for (int i = 0; i < 2; i++) sts128(sb + OFF_LIST + i * 2048 + at * 16, 0u, 0u, 0u, 0u);
        uint32_t* keys = reinterpret_cast<uint32_t*>(smem + OFF_KEYS);
        keys[4] = 0;
        named_bar(0, 480);
        mbar_wait(bar_epoch);
        const uint32_t t2 = lds32(sb + OFF_EPOCH + 4);
        STAMPIF(at == 0, 20);
        float facc[4];
        const uint64_t dft = make_desc(sb + OFF_FT), dxs = make_desc(sb + OFF_XS);
#pragma unroll 1
        for (int u = 0; u < 4; u++) {
            mbar_wait(ffull + 8 * u);
            STAMPIF(at == 0, 4 + u);
            wgmma_fence();
            small_tile<0>(facc, dft + u * (TILE >> 4), dxs + u * 64, u == 0);
            wgmma_commit();
        }
        wgmma_wait<0>();
        pin4(facc);
        if (lane < 4) mbar_arrive(fempty + 8 * lane);
        auto gate_up = [&](auto rest) {
            uint32_t slot = 4, par = 0;
#pragma unroll 1
            for (int j = 0; j < 16; j++) {
                if (j == 2) rest();
                mbar_wait(ffull + 8 * slot, par);
                mbar_wait(empty + 8 * prm.use[j]);
                wgmma_fence();
                small_tile<1>(facc, dft + slot * (TILE >> 4), dxs + j * 64, j == 0);
                wgmma_commit();
                wgmma_wait<0>();
                if (lane == 0) mbar_arrive(fempty + 8 * slot);
                if (++slot == NFT) { slot = 0; par ^= 1; }
            }
            pin4(facc);
        };
        auto down = [&]() {
            const uint64_t dhid = make_desc(sb + OFF_HID);
#pragma unroll 1
            for (int j = 0; j < 7; j++) {
                mbar_wait(dfull + 8 * j);
                mbar_wait(empty + 8 * prm.use[16 + j]);
                wgmma_fence();
                small_tile<1>(facc, dft + j * (TILE >> 4), dhid + j * 64, j == 0);
                wgmma_commit();
                if (j && !(j & 1)) {
                    wgmma_wait<0>();
                    if (lane == 0) mbar_arrive(bar_dfree + 4 * j - 8);
                }
            }
            wgmma_wait<0>();
            pin4(facc);
        };
        if ((c & 1) == (w >> 1)) {
            float* red = reinterpret_cast<float*>(smem + OFF_RED) + w * 32 + (c >> 1) * 16 + g;
            red[0] = (w & 1) ? facc[1] : facc[0];
            red[8] = (w & 1) ? facc[3] : facc[2];
        }
        named_bar(2, 128);
        STAMPIF(at == 0, 21);
        const uint32_t tpub = clk32();
        if (w < 2) {
            const float* red = reinterpret_cast<const float*>(smem + OFF_RED) + w * 16 + (lane & 15);
            const float v = rbf((red[0] + red[32]) + (red[64] + red[96]));
            if (w == 0) {
                uint32_t k = __float_as_uint(v);
                k = ((k ^ ((uint32_t)((int)k >> 31) | 0x80000000u)) & 0xFFFF0000u) | (t2 << 11) | (2047u - (uint32_t)(rid * 16 + (lane & 15)));
                int rank = 0;
#pragma unroll
                for (int i = 0; i < 8; i++) rank += __shfl_sync(0xffffffffu, k, (lane >> 4) * 8 + i) > k;
                rank += __shfl_xor_sync(0xffffffffu, rank, 16);
                if (rank < 8) st_relaxed(&prm.s->key[cta * 8 + rank], k);
            } else if (lane < 16) st_relaxed(&prm.s->gate[rid * 16 + lane], __float_as_uint(rbf(sigmoidf_(v))) | t2);
            __syncwarp();
        }
        uint32_t it = 0;
        uint4 ka, kb4;
        sleep_until(tpub + TN(G0));
        while (true) {
            ka = ld_relaxed4(&prm.s->key[at * 8]);
            kb4 = ld_relaxed4(&prm.s->key[at * 8 + 4]);
            if (__all_sync(0xffffffffu, (((ka.x ^ (t2 << 11)) | (kb4.x ^ (t2 << 11))) & 0x1800u) == 0)) break;
            if (++it > SPIN_LIMIT) __trap();
        }
        STAMPIF(at == 0, 22);
        STAMPIF(at == 0 && it > 0, 23);
        const uint32_t m1 = __reduce_max_sync(0xffffffffu, ka.x), m2 = __reduce_max_sync(0xffffffffu, ka.x == m1 ? ka.y : ka.x);
        if (lane == 0) keys[w] = m2;
        named_bar(2, 128);
        const uint4 th4 = *reinterpret_cast<const uint4*>(keys);
        const uint32_t th = min(min(th4.x, th4.y), min(th4.z, th4.w));
        {
            const uint32_t k8[8] = {ka.x, ka.y, ka.z, ka.w, kb4.x, kb4.y, kb4.z, kb4.w};
            auto append = [&](int lo, int hi) {
                uint32_t n = 0, pos = 0;
#pragma unroll
                for (int i = lo; i < hi; i++) n += k8[i] >= th;
                asm volatile("{ .reg .pred p; setp.ne.u32 p, %2, 0; @p atom.shared.add.u32 %0, [%1], %2; }" : "+r"(pos) : "r"(sb + OFF_KEYS + 16), "r"(n) : "memory");
#pragma unroll
                for (int i = lo; i < hi; i++)
                    if (k8[i] >= th) reinterpret_cast<uint32_t*>(smem + OFF_LIST)[pos + i - lo] = k8[i];
            };
            append(0, 2);
            if (__any_sync(0xffffffffu, k8[2] >= th)) append(2, 8);
        }
        named_bar(2, 128);
        {
            const uint32_t* list = reinterpret_cast<const uint32_t*>(smem + OFF_LIST);
            const int n = (int)keys[4];
#pragma unroll 1
            for (int i0 = w * 32; i0 < n; i0 += 128) {
                const uint32_t k = list[i0 + lane];
                int rank = 0;
#pragma unroll 2
                for (int o = 0; o < n; o += 4) {
                    const uint4 l4 = *reinterpret_cast<const uint4*>(list + o);
                    rank += (l4.x > k) + (l4.y > k) + (l4.z > k) + (l4.w > k);
                }
                if (rank < 8) reinterpret_cast<uint32_t*>(smem + OFF_SEL)[rank] = k;
            }
        }
        named_bar(2, 128);
        STAMPIF(at == 0, 24);
        const uint32_t* sel = reinterpret_cast<const uint32_t*>(smem + OFF_SEL);
        auto gates = [&]() {
            uint32_t gv;
            it = 0;
            while (true) {
                gv = ld_relaxed(&prm.s->gate[chunk * 128 + at]);
                const uint32_t ar = ld_relaxed(&prm.s->armed[((cta >> 4) * 14 + min(lane, 13)) * 4]);
                if (__all_sync(0xffffffffu, (gv & 3u) == t2 && ar == t2)) break;
                if (++it > SPIN_LIMIT) __trap();
            }
            asm volatile("fence.acquire.gpu;" ::: "memory");
#pragma unroll
            for (int s = 0; s < 8; s++)
                if ((~sel[s] & 2047u) == (uint32_t)(chunk * 128 + at)) gv |= 0x80000000u;
            reinterpret_cast<uint16_t*>(smem + OFF_G)[at] = (uint16_t)(gv >> 16);
            __syncwarp();
            if (lane == 0) mbar_arrive(bar_g);
        };
        if (has_gu) {
            const int tk = (at >> 3) & 7;
            const char* xt = (const char*)prm.x + (~sel[tk] & 2047u) * 2048 + (at >> 6) * 128 + (at & 7) * 16;
#pragma unroll
            for (int i = 0; i < 8; i++) {
                cp_async16(sb + OFF_XS + (2 * i + (at >> 6)) * 1024 + tk * 128 + (((at & 7) ^ tk) << 4), xt + i * 256);
                if (i == 0 || i == 7) asm volatile("cp.async.commit_group;" ::: "memory");
            }
            asm volatile("cp.async.wait_group 1;" ::: "memory");
            fence_async_smem();
            named_bar(2, 128);
            STAMPIF(at == 0, 25);
            gate_up([&]() {
                asm volatile("cp.async.wait_all;" ::: "memory");
                fence_async_smem();
                named_bar(2, 128);
                gates();
            });
            if (!(cta & 1)) {
#pragma unroll
                for (int u = 0; u < 4; u++) {
                    const float v = rbf(facc[u]);
                    facc[u] = __fdividef(v, 1.0f + __expf(-v));
                }
            }
            st_relaxed2(&prm.s->hid[cta * 128 + at], pack_bf(facc[0], facc[1]), pack_bf(facc[2], facc[3]));
        } else gates();
        STAMPIF(at == 0, 26);
        {
            mbar_wait(empty + 8 * max(TN(HG), 31));
            const uint2* hp = &prm.s->hid[(cta >> 4) * 14 * 128 + at];
            uint32_t hv[16];
            it = 0;
            while (true) {
                uint32_t top = 0;
#pragma unroll
                for (int j = 0; j < 7; j++) {
                    const uint2 hg = ld_relaxed2(hp + 256 * j), hu = ld_relaxed2(hp + 256 * j + 128);
                    top = max(top, max(hg.x, hu.x));
                    hv[2 * j] = mul_bf2(hg.x, hu.x); hv[2 * j + 1] = mul_bf2(hg.y, hu.y);
                }
                if (__all_sync(0xffffffffu, top != ~0u)) break;
                do {
                    if (++it > SPIN_LIMIT) __trap();
                } while (!__all_sync(0xffffffffu, ld_relaxed(hp + min(lane, 13) * 128 - lane) != ~0u));
            }
            STAMPIF(at == 0 && it > 0, 61);
            hv[14] = hv[15] = 0;
#pragma unroll
            for (int j = 0; j < 4; j++)
                asm volatile("stmatrix.sync.aligned.m8n8.x4.trans.shared.b16 [%0], {%1, %2, %3, %4};" ::"r"(
                                 sb + OFF_HID + (2 * j + (lane >> 4)) * 1024 + (lane & 7) * 128 + (((2 * w + ((lane >> 3) & 1)) ^ (lane & 7)) << 4)),
                             "r"(hv[4 * j]), "r"(hv[4 * j + 1]), "r"(hv[4 * j + 2]), "r"(hv[4 * j + 3]) : "memory");
        }
        fence_async_smem();
        named_bar(2, 128);
        STAMPIF(at == 0, 27);
        down();
#pragma unroll
        for (int u = 0; u < 4; u++)
            st_relaxed(&prm.s->y[((2 * c + (u & 1)) * 8 + (cta >> 4)) * D_ + (cta & 15) * 64 + w * 16 + g + 8 * (u >> 1)], (__float_as_uint(facc[u]) & ~3u) | t2);
        STAMPIF(at == 0, 28);
        mbar_wait(bar_dfree + 16);
        uint32_t mine = 0;
#pragma unroll 1
        for (int s = 0; s < 8; s++) {
            const uint32_t key = sel[s];
            const int t = 2047 - (int)(key & 2047u);
            if ((t >> 7) != chunk) continue;
            const uint32_t* yp = &prm.s->y[s * 8 * D_ + dt * 128 + at];
            const float xv = __bfloat162float(prm.x[(size_t)t * D_ + dt * 128 + at]);
            float y;
            it = 0;
            while (true) {
                uint32_t bad = 0;
                y = 0.f;
#pragma unroll
                for (int ks = 0; ks < 8; ks++) {
                    const uint32_t v = ld_relaxed(yp + ks * D_);
                    bad |= v ^ t2;
                    y += __uint_as_float(v);
                }
                if (__all_sync(0xffffffffu, (bad & 3u) == 0)) break;
                if (++it > SPIN_LIMIT) __trap();
            }
            mine |= 1u << s;
            const uint32_t kb = key >> 16;
            const float rs = rbf(sigmoidf_(bf_lo((kb & 0x8000u) ? (kb & 0x7FFFu) : (~kb & 0xFFFFu))));
            const float gv = fabsf(__bfloat162float(reinterpret_cast<const __nv_bfloat16*>(smem + OFF_G)[t & 127]));
            const float dk = __bfloat162float(reinterpret_cast<const __nv_bfloat16*>(smem + OFF_DK)[at]);
            reinterpret_cast<float*>(smem + OFF_E)[s * 128 + at] = fmaf(gv, rbf(xv * dk), rbf(rbf(1.0f - gv) * rbf(xv + rbf(rbf(y) * rs))));
        }
        STAMPIF(at == 0, 50);
        if (mine) mbar_wait(bar_stored);
        while (mine) {
            const int s = __ffs(mine) - 1;
            mine &= mine - 1;
            atomicAdd(prm.out + (size_t)(~sel[s] & 2047u) * D_ + dt * 128 + at, reinterpret_cast<const float*>(smem + OFF_E)[s * 128 + at]);
        }
        STAMPIF(at == 0, 29);
    } else {
        asm volatile("setmaxnreg.dec.sync.aligned.u32 40;");
        if (warp == 15) {
            prefetch_map(&mXr);
            named_bar(0, 480);
#pragma unroll 1
            for (int i = 0; i < 4; i++) {
                const int u = i;
                if (lane == 0) mbar_expect_tx(ffull + 8 * u, TILE);
                sleep_until(cstart + (i == 0 ? TN(RT0) : i == 1 ? TN(RT1) : i == 2 ? TN(RT2) : TN(RT3)));
                if (elect_one()) tma3(sb + OFF_FT + u * TILE, &mXr, u * 256, rid * 16, ffull + 8 * u);
                STAMP(53 + u);
            }
            const CUtensorMap* mw = (cta & 1) ? &mWu : &mWg;
            if (sb & 1023) __trap();
            prefetch_map(mw);
            prefetch_map(&mWd);
            uint32_t slot = 4, par = 1;
#pragma unroll 1
            for (int j = 0; j < (has_gu && DBG != 1 ? 16 : 0); j++) {
                mbar_wait(fempty + 8 * slot, par);
                if (lane == 0) mbar_expect_tx(ffull + 8 * slot, TILE);
                mbar_wait(empty + 8 * prm.fetch[j]);
                if (elect_one()) tma2(sb + OFF_FT + slot * TILE, mw, (cta >> 1) * 64, TN(WDBG) ? 0 : j * 64, ffull + 8 * slot);
                if (++slot == NFT) { slot = 0; par ^= 1; }
            }
            if (lane < 9) mbar_expect_tx(lane < 7 ? dfull + 8 * lane : bar_x + 8 * (lane - 7), lane < 7 ? TILE : 2 * TILE);
            mbar_wait(bar_g);
#pragma unroll 1
            for (int j = 0; j < (DBG != 1 ? 7 : 0); j++) {
                if (has_gu) mbar_wait(fempty + 8 * min(j, 4), 1);
                mbar_wait(empty + 8 * prm.fetch[16 + j]);
                if (elect_one()) tma2(sb + OFF_FT + j * TILE, &mWd, (cta & 15) * 64, (cta >> 4) * 448 + (TN(WDBG) ? 0 : j * 64), dfull + 8 * j);
            }
            prefetch_map(&mXe);
#pragma unroll 1
            for (int u = 0; u < 4; u++) {
                mbar_wait(bar_dfree + 8 + 4 * (u & 2));
                mbar_wait(empty + 8 * (TN(DN_E0) + u));
                if (elect_one())
                    asm volatile("cp.async.bulk.tensor.5d.shared::cluster.global.mbarrier::complete_tx::bytes [%0], [%1, {%3, %6, %6, %4, %5}], [%2];"
                                 ::"r"(sb + OFF_FT + (3 + u) * TILE), "l"(&mXe), "r"(bar_x + 4 * (u & 2)), "r"(dt * 128 + (u & 1) * 64), "r"(u & 2), "r"(chunk * 4), "r"(0) : "memory");
            }
        } else if (warp == 13) {
#pragma unroll
            for (int u = 0; u < 8; u++) {
                const int row = (u >> 2) * 4 + (lane >> 3);
                cp_async16(sb + OFF_XS + (u & 3) * 1024 + row * 128 + (((lane & 7) ^ row) << 4), (const char*)(u < 4 ? prm.w_r : prm.gate_w) + (u & 3) * 512 + lane * 16);
            }
            STAMP(57);
            const uint32_t tag = ld_relaxed(&prm.s->epoch[cta]) + 1;
            named_bar(1, 64);
            *reinterpret_cast<uint2*>(smem + OFF_EPOCH) = make_uint2(tag, tag % 3u + 1u);
            STAMPIF(tag, 58);
            asm volatile("cp.async.wait_all;" ::: "memory");
            STAMP(59);
            fence_async_smem();
            __syncwarp();
            if (lane == 0) {
                mbar_arrive(bar_epoch);
                prm.s->epoch[cta] = tag;
            }
            sleep_until(cstart + TN(T_BASE));
            {
                const uint2 st = ld_relaxed2(&prm.s->start[2 * lane]);
                const uint32_t d = st.x - cstart + 512u, age = gtime32() - st.y;
                const uint32_t m = __reduce_max_sync(0xffffffffu, d < 1024u && age < 4096u ? (d << 12) | age : 0u);
                const uint32_t late = (m & 4095u) - __reduce_min_sync(0xffffffffu, age);
                *reinterpret_cast<volatile uint32_t*>(smem + OFF_EPOCH + 8) = cstart + (m ? (m >> 12) - 512u + min(late, 256u) * TN(G_NS) / 4 : 0u);
                __syncwarp();
                if (lane == 0) mbar_arrive(bar_base);
                STAMP(60);
            }
            mbar_wait(bar_const);
            asm volatile("fence.acq_rel.gpu;" ::: "memory");
            if (lane < 4) st_relaxed2(&prm.s->armed[cta * 4 + lane], tag % 3u + 1u, 0u);
            prefetch_map(&mCre);
            prefetch_map(&mCim);
            const uint2* flag = &prm.s->flag[chunk * 256 + lane];
#pragma unroll 1
            for (int e = 0; e < 8; e++) {
                mbar_wait(bar_out + 8 * e);
                if (e == 3) {
                    const char* rb = reinterpret_cast<const char*>(prm.s->h) + (size_t)chunk * 524288 + 3 * 65536 + (dt >> 1) * 16384 + (dt & 1) * 4096 + lane * 128;
                    const uint32_t b = ld_relaxed(rb) ^ ld_relaxed(rb + TILE);
                    if (lane < 4) st_relaxed2(&prm.s->flag[(chunk * 8 + 3) * 32 + dt * 4 + lane], tag, b);
                }
                uint32_t it = 0, f0 = ld_relaxed(flag + 32 * e);
                __nanosleep(100);
                while (true) {
                    const uint32_t f1 = ld_relaxed(flag + 32 * e);
                    if (__all_sync(0xffffffffu, f0 == tag)) break;
                    f0 = ld_relaxed(flag + 32 * e);
                    if (__all_sync(0xffffffffu, f1 == tag)) break;
                    if (++it > SPIN_LIMIT) __trap();
                }
                asm volatile("fence.acquire.gpu;" ::: "memory");
                if (lane < 4) mbar_arrive(bar_ready + 8 * e);
                STAMP(10 + e);
            }
        } else if (warp == 14) {
            prefetch_map(&mPB);
            auto pf_c = [&](int k) { prefetch_slice(&mPC, 4 * (k >> 1), cta * 8 + (k & 1) * 4); };
            named_bar(0, 480);
            asm volatile("bar.arrive 1, 64;" ::: "memory");
            if (lane < 24) st_relaxed(lane < 8 ? &prm.s->key[cta * 8 + lane] : &prm.s->gate[rid * 16 + lane - 8], 0u);
#pragma unroll 1
            for (int k = TN(PF0) ? 0 : 1; k < 4; k++) {
                sleep_until(cstart + (k == 0 ? TN(PF0) : k == 1 ? TN(PF1) : k == 2 ? TN(PF2) : TN(PF3)));
                if (elect_one()) prefetch_slice(&mPB, 4 * k, cta * 4);
            }
#pragma unroll 1
            for (int k = 0; k < 4; k++) {
                mbar_wait(empty + 8 * (TN(PB_E0) + TN(PB_STEP) * k));
                if (elect_one()) prefetch_slice(&mPB, 4 * k, 512 + cta * 4);
            }
#pragma unroll 1
            for (int k = 0; k < TN(PC_N); k++) {
                mbar_wait(empty + 8 * min(TN(PC_E0) + TN(PC_STEP) * k / 2, 26));
                if (elect_one()) pf_c(k);
            }
            int pk = TN(PC_N), pe = TN(PC_E1);
            const char* src = reinterpret_cast<const char*>(prm.s->h) + (size_t)chunk * 524288;
            uint32_t dst = sb + (32 % NST) * SLOT;
#pragma unroll 1
            for (int i = 32; i < NBIG; i++) {
                if (!(i & 3)) {
                    mbar_wait(bar_ready + 2 * (i - 32));
                    asm volatile("fence.proxy.async.global;" ::: "memory");
                }
                mbar_wait(empty + 8 * (i - NST));
                PSTAMP(i);
                if (elect_one()) bulk_load(dst, src, 2 * TILE, full + 8 * i);
                if (i == pe && pk < 8) {
                    if (elect_one()) pf_c(pk);
                    pk++; pe += TN(PC_S1);
                }
                src += (TN(HDBG) & 1) ? 0 : 2 * TILE;
                dst = dst == sb + (NST - 1) * SLOT ? sb : dst + SLOT;
            }
            mbar_wait(bar_dfree);
#pragma unroll
            for (int k = 0; k < 14; k++) {
                if (k == 4) continue;
                if (k == 0 || k == 2) {
                    mbar_wait(bar_ready + 48 + 4 * k);
                    asm volatile("fence.proxy.async.global;" ::: "memory");
                }
                mbar_wait(empty + 8 * (NBIG - NST + k));
                PSTAMP(NBIG + (k < 5 ? 2 * k : k + 2));
                PSTAMP(NBIG + (k < 5 ? 2 * k + 1 : k + 2));
                if (elect_one()) {
#pragma unroll
                    for (int n = k < 5 ? 2 * k : k + 2; n < (k < 3 ? 2 * k + 2 : k == 3 ? 7 : k + 3); n++)
                        bulk_load(sb + tail_h(n), src + (n & 7) * 2 * TILE + (n >> 3) * TILE, TILE, full + 8 * (NBIG + (n < 10 ? n : n & ~1)));
                }
            }
        } else {
            if (elect_one()) {
#pragma unroll
                for (int i = 0; i < NST; i++) mbar_init(full + 8 * i, 1);
                fence_mbar_init();
            }
            __syncwarp();
#pragma unroll 1
            for (int i = 0; i < NST; i++) {
                if (elect_one()) {
                    mbar_expect_tx(full + 8 * i, SLOT);
                    tma5b(sb + i * SLOT, &mB, i * 64, dt * 4, full + 8 * i);
                    tma4(sb + i * SLOT + 2 * TILE, &mX, i * 64, chunk * 64, full + 8 * i);
                }
                STAMPIF(i == 0, 1);
            }
            STAMP(2);
            named_bar(0, 480);
            uint32_t dst = sb;
#pragma unroll 1
            for (int i = NST; i < 32; i++) {
                if (lane == 0) mbar_expect_tx(full + 8 * i, SLOT);
                mbar_wait(empty + 8 * (i - NST));
                PSTAMP(i);
                if (elect_one()) {
                    tma5b(dst, &mB, (i & 15) * 64, ((TN(HDBG) & 8) ? 0 : (i >> 4) * 64) + dt * 4, full + 8 * i);
                    tma4(dst + 2 * TILE, &mX, (i & 15) * 64, chunk * 64, full + 8 * i);
                }
                dst = dst == sb + (NST - 1) * SLOT ? sb : dst + SLOT;
            }
#pragma unroll 1
            for (int i = 32; i < NBIG; i++) {
                if (lane == 0) mbar_expect_tx(full + 8 * i, SLOT);
                mbar_wait(empty + 8 * (i - NST));
                if (elect_one()) tma5(dst + 2 * TILE, (i & 4) ? &mCim : &mCre, (TN(HDBG) & 2) ? 0 : ((i & 3) + ((i >> 1) & 12)) * 64, dt * 8, full + 8 * i);
                dst = dst == sb + (NST - 1) * SLOT ? sb : dst + SLOT;
            }
            if (lane < 16) mbar_expect_tx(full + 8 * (NBIG + lane), lane < 8 ? 3 * TILE : lane < 10 ? TILE : 2 * TILE);
            dst = sb + tail_c(0);
#pragma unroll 1
            for (int j = 0; j < 8; j++) {
                mbar_wait(empty + 8 * (NBIG - NST + 1 + (j >> 1)));
                if (elect_one()) tma5(dst, (j & 4) ? &mCim : &mCre, ((j & 3) + 12) * 64, dt * 8, full + 8 * (NBIG + j));
                dst = j == 5 ? sb : dst + 2 * TILE;
            }
        }
    }
}

typedef CUresult (*EncodeFn)(CUtensorMap*, CUtensorMapDataType, cuuint32_t, void*, const cuuint64_t*, const cuuint64_t*, const cuuint32_t*,
                             const cuuint32_t*, CUtensorMapInterleave, CUtensorMapSwizzle, CUtensorMapL2promotion, CUtensorMapFloatOOBfill);

bool encode(EncodeFn fn, CUtensorMap* m, const void* ptr, int rank, const cuuint64_t* dims, const cuuint64_t* strides, const cuuint32_t* box,
            CUtensorMapL2promotion promo = CU_TENSOR_MAP_L2_PROMOTION_NONE) {
    const cuuint32_t es[5] = {1, 1, 1, 1, 1};
    return fn(m, CU_TENSOR_MAP_DATA_TYPE_BFLOAT16, rank, const_cast<void*>(ptr), dims, strides, box, es, CU_TENSOR_MAP_INTERLEAVE_NONE,
              CU_TENSOR_MAP_SWIZZLE_128B, promo, CU_TENSOR_MAP_FLOAT_OOB_FILL_NONE) == CUDA_SUCCESS;
}

}

extern "C" void kernel_launch(void* const* d_in, const int* in_sizes, int n_in, void* d_out, int out_size) {
    (void)in_sizes; (void)n_in; (void)out_size;
    Params prm;
    prm.x = (const __nv_bfloat16*)d_in[0];
    prm.lam_re = (const __nv_bfloat16*)d_in[1];
    prm.lam_im = (const __nv_bfloat16*)d_in[2];
    prm.b_re = (const __nv_bfloat16*)d_in[3];
    prm.b_im = (const __nv_bfloat16*)d_in[4];
    prm.c_re = (const __nv_bfloat16*)d_in[5];
    prm.c_im = (const __nv_bfloat16*)d_in[6];
    prm.log_dt = (const __nv_bfloat16*)d_in[7];
    prm.dskip = (const __nv_bfloat16*)d_in[8];
    prm.w_r = (const __nv_bfloat16*)d_in[10];
    prm.gate_w = (const __nv_bfloat16*)d_in[14];
    prm.out = (float*)d_out;
    cudaGetSymbolAddress((void**)&prm.s, g_scratch);
    prm.swapped = prm.b_im < prm.b_re;

    void* fnp = nullptr;
    cudaDriverEntryPointQueryResult qr;
    cudaGetDriverEntryPoint("cuTensorMapEncodeTiled", &fnp, cudaEnableDefault, &qr);
    EncodeFn fn = (EncodeFn)fnp;
    cudaFuncSetAttribute(fused_kernel, cudaFuncAttributeMaxDynamicSharedMemorySize, SMEM_BYTES);

    CUtensorMap mX, mB, mCre, mCim, mWg, mWu, mWd, mXr, mPB, mPC, mXe;
    const cuuint64_t row = 2048;
    {
        const cuuint64_t dims[4] = {1024, 2, 4, 976}, st[3] = {row, 32 * row, 2 * row};
        const cuuint32_t box[4] = {64, 2, 4, 16};
        encode(fn, &mX, prm.x, 4, dims, st, box, PROMO);
    }
    {
        const char *lo = (const char*)(prm.swapped ? prm.b_im : prm.b_re), *hi = (const char*)(prm.swapped ? prm.b_re : prm.b_im);
        const cuuint64_t dims[5] = {1024, 8, 2, 96, 2}, st[4] = {row, (cuuint64_t)(hi - lo), 8 * row, 256 * row};
        const cuuint32_t box[5] = {64, 8, 2, 4, 2};
        encode(fn, &mB, lo, 5, dims, st, box, PROMO);
    }
    {
        const cuuint64_t dims[5] = {1024, 2, 4, 2, 64}, st[4] = {row, 4 * row, 2 * row, 16 * row};
        const cuuint32_t box[5] = {64, 2, 4, 2, 8};
        encode(fn, &mCre, prm.c_re, 5, dims, st, box);
        encode(fn, &mCim, prm.c_im, 5, dims, st, box);
    }
    {
        const cuuint64_t dims[2] = {F_, D_}, st[1] = {F_ * 2}, dimsd[2] = {D_, F_}, std_[1] = {row};
        const cuuint32_t box[2] = {64, 64};
        encode(fn, &mWg, d_in[11], 2, dims, st, box);
        encode(fn, &mWu, d_in[12], 2, dims, st, box);
        encode(fn, &mWd, d_in[13], 2, dimsd, std_, box);
    }
    for (int i = 0; i < 2; i++) {
        const char *p = (const char*)(i ? prm.c_re : prm.b_re), *q = (const char*)(i ? prm.c_im : prm.b_im);
        const cuuint64_t dims[4] = {64, 16, 1024, 2}, st[3] = {128, row, (cuuint64_t)(p < q ? q - p : p - q)};
        const cuuint32_t box[4] = {16, 4, 4, 2};
        encode(fn, i ? &mPC : &mPB, p < q ? p : q, 4, dims, st, box, CU_TENSOR_MAP_L2_PROMOTION_L2_128B);
    }
    {
        const cuuint64_t dims[3] = {D_ - 192, S_, 4}, st[2] = {row, 128};
        const cuuint32_t box[3] = {64, 16, 4};
        encode(fn, &mXr, prm.x, 3, dims, st, box);
    }
    {
        const cuuint64_t dims[5] = {1024, 2, 4, 4, S_ / 32}, st[4] = {4 * row, row, 8 * row, 32 * row};
        const cuuint32_t box[5] = {64, 2, 4, 2, 4};
        encode(fn, &mXe, prm.x, 5, dims, st, box);
    }
    for (int j = 0, e4 = 4 * TN(GC0); j < 23; j++) {
        prm.fetch[j] = j < NFT ? TN(GU_E0) + j * TN(W_NUM) / 4 : j < 16 ? 0 : TN(DL0) + (j - 16) * TN(DLS) / 4;
        prm.use[j] = j < 16 ? e4 / 4 : TN(DC0) + (j - 16) * TN(DCS) / 4;
        const int last = j < 19 ? 54 : 58;
        if (prm.fetch[j] > last) prm.fetch[j] = last;
        if (prm.use[j] > last) prm.use[j] = last;
        e4 += j < TN(N1) ? TN(GCS) : j < TN(N2) ? TN(GCS2) : j < 10 ? TN(GCS3) : TN(GCS4);
    }
    fused_kernel<<<NCTA, 512, SMEM_BYTES, cudaStreamPerThread>>>(mX, mB, mCre, mCim, mWg, mWu, mWd, mXr, mPB, mPC, mXe, prm);
}
```

```cpp
#include <cuda_runtime.h>
#include <cuda_bf16.h>
#include <cuda.h>
#include <stdint.h>

namespace {

constexpr int S_ = 2048, D_ = 1024, F_ = 3584;
constexpr int NCTA = 128;
constexpr int NBIG = 56, NENT = 72;
constexpr int NST = 5;
constexpr int NFT = 5;
constexpr uint32_t SLOT = 32768, TILE = 8192;
constexpr uint32_t OFF_FT = NST * SLOT;
constexpr uint32_t OFF_XS = OFF_FT + NFT * TILE;
constexpr uint32_t OFF_LIST = OFF_XS + 8192;
constexpr uint32_t OFF_RED = OFF_XS + 4096;
constexpr uint32_t OFF_CONST = OFF_XS + 16384;
constexpr uint32_t OFF_M = OFF_CONST + 8192, OFF_ONE = OFF_M + 512;
constexpr uint32_t OFF_HID = OFF_CONST;
constexpr uint32_t OFF_G = OFF_ONE + 16;
constexpr uint32_t OFF_DK = OFF_G + 256;
constexpr uint32_t OFF_FULL = OFF_DK + 256;
constexpr uint32_t OFF_EMPTY = OFF_FULL + 102 * 8;
constexpr uint32_t OFF_KEYS = OFF_EMPTY + 86 * 8;
constexpr uint32_t OFF_SEL = OFF_KEYS + 32;
constexpr uint32_t OFF_EPOCH = OFF_SEL + 32;
constexpr uint32_t OFF_PROF = OFF_EPOCH + 16;
constexpr uint32_t SMEM_BYTES = OFF_PROF + 432;
static_assert(SMEM_BYTES <= 232448, "smem");

static_assert(NBIG % NST == 1, "tail layout");
__host__ __device__ constexpr uint32_t tail_c(int j) { return j < 6 ? 2 * SLOT + j * 2 * TILE : (j - 6) * 2 * TILE; }
__host__ __device__ constexpr uint32_t tail_h(int n) { return n % 7 < 3 ? OFF_FT + n % 7 * TILE : SLOT + (n % 7 - 3) * TILE; }

constexpr uint32_t SPIN_LIMIT = 1u << 18;

struct Scratch {
    uint2 carry[16 * 1024];
    uint2 hid[NCTA * 128];
    uint32_t y[8 * 8 * D_];
    uint32_t key[NCTA * 8];
    uint32_t gate[S_];
    uint2 armed[NCTA * 4];
    unsigned int epoch[256];
    uint4 start[32 * 2];
    uint4 h[16 * 32 * 1024];
};
__device__ __align__(1024) Scratch g_scratch;
#define STAMPW(cond, w) do {} while (0)
#define GSTAMP(cond, w) do {} while (0)
#define STAMPIF(cond, i) STAMPW(cond, 96 + (i))
#define STAMP(i) STAMPW(1, 96 + (i))
#define KSTAMP(i) STAMPW((threadIdx.x & 127) == 0, i)
#define PSTAMP(i) STAMPW((i) < 56 && (i) >= 32, 160 + (i))

struct Params {
    const __nv_bfloat16 *x, *lam_re, *lam_im, *b_re, *b_im, *c_re, *c_im, *log_dt, *dskip, *w_r, *gate_w;
    float* out;
    Scratch* s;
    int fetch[23], use[23];
    int swapped;
};

__device__ __forceinline__ uint32_t smem_u32(const void* p) { return (uint32_t)__cvta_generic_to_shared(p); }
__device__ __forceinline__ void mbar_init(uint32_t bar, uint32_t cnt) { asm volatile("mbarrier.init.shared::cta.b64 [%0], %1;" ::"r"(bar), "r"(cnt) : "memory"); }
__device__ __forceinline__ void mbar_expect_tx(uint32_t bar, uint32_t bytes) { asm volatile("mbarrier.arrive.expect_tx.shared::cta.b64 _, [%0], %1;" ::"r"(bar), "r"(bytes) : "memory"); }
__device__ __forceinline__ void mbar_arrive(uint32_t bar) { asm volatile("mbarrier.arrive.shared::cta.b64 _, [%0];" ::"r"(bar) : "memory"); }
__device__ __forceinline__ bool mbar_try(uint32_t bar, uint32_t parity) {
    uint32_t ok;
    asm volatile("{ .reg .pred p; mbarrier.try_wait.parity.shared::cta.b64 p, [%1], %2; selp.u32 %0, 1, 0, p; }" : "=r"(ok) : "r"(bar), "r"(parity) : "memory");
    return ok;
}
__device__ __forceinline__ bool mbar_test(uint32_t bar, uint32_t parity) {
    uint32_t ok;
    asm volatile("{ .reg .pred p; mbarrier.test_wait.parity.shared::cta.b64 p, [%1], %2; selp.u32 %0, 1, 0, p; }" : "=r"(ok) : "r"(bar), "r"(parity) : "memory");
    return __all_sync(0xffffffffu, ok);
}
__device__ __forceinline__ void mbar_wait(uint32_t bar, uint32_t parity = 0) {
    if (mbar_try(bar, parity)) return;
#pragma unroll 1
    for (uint32_t it = 0; it < SPIN_LIMIT; ++it)
        if (mbar_try(bar, parity)) return;
    __trap();
}
__device__ __forceinline__ bool elect_one() {
    uint32_t pred;
    asm volatile("{ .reg .pred P; elect.sync _|P, 0xffffffff; selp.b32 %0, 1, 0, P; }" : "=r"(pred));
    return pred;
}
__device__ __forceinline__ void named_bar(int id, int n) { asm volatile("bar.sync %0, %1;" ::"r"(id), "r"(n) : "memory"); }
__device__ __forceinline__ void fence_mbar_init() { asm volatile("fence.mbarrier_init.release.cluster;" ::: "memory"); }
__device__ __forceinline__ void fence_async_smem() { asm volatile("fence.proxy.async.shared::cta;" ::: "memory"); }

__device__ __forceinline__ void bulk_load(uint32_t dst, const void* src, uint32_t bytes, uint32_t bar) {
    asm volatile("cp.async.bulk.shared::cluster.global.mbarrier::complete_tx::bytes [%0], [%1], %2, [%3];" ::"r"(dst), "l"(src), "r"(bytes), "r"(bar) : "memory");
}
__device__ __forceinline__ void cp_async16(uint32_t dst, const void* src) { asm volatile("cp.async.cg.shared.global [%0], [%1], 16;" ::"r"(dst), "l"(src) : "memory"); }
__device__ __forceinline__ void sts128(uint32_t a, uint32_t x, uint32_t y, uint32_t z, uint32_t w) {
    asm volatile("st.shared.v4.u32 [%0], {%1,%2,%3,%4};" ::"r"(a), "r"(x), "r"(y), "r"(z), "r"(w) : "memory");
}
__device__ __forceinline__ uint2 lds64(uint32_t a) {
    uint2 v;
    asm volatile("ld.shared.v2.u32 {%0,%1}, [%2];" : "=r"(v.x), "=r"(v.y) : "r"(a) : "memory");
    return v;
}
__device__ __forceinline__ uint32_t lds32(uint32_t a) {
    uint32_t v;
    asm volatile("ld.volatile.shared.u32 %0, [%1];" : "=r"(v) : "r"(a) : "memory");
    return v;
}
__device__ __forceinline__ void stg128(void* p, uint32_t x, uint32_t y, uint32_t z, uint32_t w) {
    asm volatile("st.global.v4.u32 [%0], {%1,%2,%3,%4};" ::"l"(p), "r"(x), "r"(y), "r"(z), "r"(w) : "memory");
}
__device__ __forceinline__ void st_relaxed(void* p, uint32_t x) { asm volatile("st.relaxed.gpu.global.b32 [%0], %1;" ::"l"(p), "r"(x) : "memory"); }
__device__ __forceinline__ void st_relaxed2(void* p, uint32_t x, uint32_t y) { asm volatile("st.relaxed.gpu.global.v2.b32 [%0], {%1, %2};" ::"l"(p), "r"(x), "r"(y) : "memory"); }
__device__ __forceinline__ void st_relaxed4(void* p, uint32_t x, uint32_t y, uint32_t z, uint32_t w) {
    asm volatile("st.relaxed.gpu.global.v4.b32 [%0], {%1, %2, %3, %4};" ::"l"(p), "r"(x), "r"(y), "r"(z), "r"(w) : "memory");
}
__device__ __forceinline__ uint32_t ld_relaxed(const void* p) {
    uint32_t v;
    asm volatile("ld.relaxed.gpu.global.b32 %0, [%1];" : "=r"(v) : "l"(p) : "memory");
    return v;
}
__device__ __forceinline__ uint2 ld_relaxed2(const void* p) {
    uint2 v;
    asm volatile("ld.relaxed.gpu.global.v2.b32 {%0, %1}, [%2];" : "=r"(v.x), "=r"(v.y) : "l"(p) : "memory");
    return v;
}
__device__ __forceinline__ uint4 ld_relaxed4(const void* p) {
    uint4 v;
    asm volatile("ld.relaxed.gpu.global.v4.b32 {%0, %1, %2, %3}, [%4];" : "=r"(v.x), "=r"(v.y), "=r"(v.z), "=r"(v.w) : "l"(p) : "memory");
    return v;
}
__device__ __forceinline__ uint32_t clk32() { uint32_t c; asm volatile("mov.u32 %0, %%clock;" : "=r"(c)); return c; }
__device__ __forceinline__ uint32_t gtime32() { uint32_t c; asm volatile("mov.u32 %0, %%globaltimer_lo;" : "=r"(c)); return c; }
__device__ __forceinline__ void sched_fence(uint32_t t) { while ((int)(clk32() - t) < 0) {} }
__device__ __forceinline__ void sleep_until(uint32_t t) { while ((int)(clk32() - t) < 0) __nanosleep(40); }

__device__ __forceinline__ void tma2(uint32_t dst, const CUtensorMap* m, int c0, int c1, uint32_t bar) {
    asm volatile("{ .reg .b64 pol; createpolicy.fractional.L2::evict_first.b64 pol;\n"
                 "cp.async.bulk.tensor.2d.shared::cluster.global.mbarrier::complete_tx::bytes.L2::cache_hint [%0], [%1, {%3, %4}], [%2], pol; }"
                 ::"r"(dst), "l"(m), "r"(bar), "r"(c0), "r"(c1) : "memory");
}
__device__ __forceinline__ void tma3(uint32_t dst, const CUtensorMap* m, int c0, int c1, uint32_t bar) {
    asm volatile("cp.async.bulk.tensor.3d.shared::cluster.global.mbarrier::complete_tx::bytes [%0], [%1, {%3, %4, %5}], [%2];"
                 ::"r"(dst), "l"(m), "r"(bar), "r"(c0), "r"(c1), "r"(0) : "memory");
}
__device__ __forceinline__ void tma4(uint32_t dst, const CUtensorMap* m, int c0, int c3, uint32_t bar) {
    asm volatile("cp.async.bulk.tensor.4d.shared::cluster.global.mbarrier::complete_tx::bytes [%0], [%1, {%3, %5, %5, %4}], [%2];"
                 ::"r"(dst), "l"(m), "r"(bar), "r"(c0), "r"(c3), "r"(0) : "memory");
}
__device__ __forceinline__ void tma5(uint32_t dst, const CUtensorMap* m, int c0, int c4, uint32_t bar) {
    asm volatile("cp.async.bulk.tensor.5d.shared::cluster.global.mbarrier::complete_tx::bytes [%0], [%1, {%3, %5, %5, %5, %4}], [%2];"
                 ::"r"(dst), "l"(m), "r"(bar), "r"(c0), "r"(c4), "r"(0) : "memory");
}
__device__ __forceinline__ void tma5b(uint32_t dst, const CUtensorMap* m, int c0, int c3, uint32_t bar) {
    asm volatile("cp.async.bulk.tensor.5d.shared::cluster.global.mbarrier::complete_tx::bytes [%0], [%1, {%3, %5, %5, %4, %5}], [%2];"
                 ::"r"(dst), "l"(m), "r"(bar), "r"(c0), "r"(c3), "r"(0) : "memory");
}
__device__ __forceinline__ void prefetch_l2(const void* p) { asm volatile("prefetch.global.L2 [%0];" ::"l"(p)); }
__device__ __forceinline__ void prefetch_slice(const CUtensorMap* m, int line, int row) {
    asm volatile("cp.async.bulk.prefetch.tensor.4d.L2.global [%0, {%3, %1, %2, %3}];" ::"l"(m), "r"(line), "r"(row), "r"(0) : "memory");
}
__device__ __forceinline__ void prefetch_map(const CUtensorMap* m) { asm volatile("prefetch.tensormap [%0];" ::"l"(m)); }
__device__ __forceinline__ uint32_t uni(uint32_t v) { return __shfl_sync(0xffffffffu, v, 0); }

__device__ __forceinline__ uint64_t make_desc(uint32_t addr) {
    return (uint64_t)((addr & 0x3FFFF) >> 4) | ((uint64_t)1 << 16) | ((uint64_t)64 << 32) | ((uint64_t)1 << 62);
}
__device__ __forceinline__ uint64_t make_desc_h(uint32_t addr) {
    return (uint64_t)((addr & 0x3FFFF) >> 4) | ((uint64_t)32 << 16) | ((uint64_t)64 << 32) | ((uint64_t)2 << 62);
}
__device__ __forceinline__ void wgmma_fence() { asm volatile("wgmma.fence.sync.aligned;" ::: "memory"); }
__device__ __forceinline__ void wgmma_commit() { asm volatile("wgmma.commit_group.sync.aligned;" ::: "memory"); }
template <int N> __device__ __forceinline__ void wgmma_wait() { asm volatile("wgmma.wait_group.sync.aligned %0;" ::"n"(N) : "memory"); }

#define R8(d, i) "+f"(d[i]), "+f"(d[i + 1]), "+f"(d[i + 2]), "+f"(d[i + 3]), "+f"(d[i + 4]), "+f"(d[i + 5]), "+f"(d[i + 6]), "+f"(d[i + 7])
#define R64(d) R8(d, 0), R8(d, 8), R8(d, 16), R8(d, 24), R8(d, 32), R8(d, 40), R8(d, 48), R8(d, 56)
template <int TA>
__device__ __forceinline__ void wgmma_n128(float (&d)[64], uint64_t da, uint64_t db, int scale_d = 1) {
    asm volatile("{ .reg .pred p; setp.ne.b32 p, %66, 0;\n"
                 "wgmma.mma_async.sync.aligned.m64n128k16.f32.bf16.bf16 "
                 "{%0,%1,%2,%3,%4,%5,%6,%7,%8,%9,%10,%11,%12,%13,%14,%15,%16,%17,%18,%19,%20,%21,%22,%23,%24,%25,%26,%27,%28,%29,%30,%31,"
                 "%32,%33,%34,%35,%36,%37,%38,%39,%40,%41,%42,%43,%44,%45,%46,%47,%48,%49,%50,%51,%52,%53,%54,%55,%56,%57,%58,%59,%60,%61,%62,%63}, "
                 "%64, %65, p, 1, 1, %67, 0; }"
                 : R64(d)
                 : "l"(da), "l"(db), "r"(scale_d), "n"(TA));
}
__device__ __forceinline__ void pin4(float (&d)[4]) { asm volatile("" : "+f"(d[0]), "+f"(d[1]), "+f"(d[2]), "+f"(d[3])::"memory"); }
__device__ __forceinline__ void pin64(float (&d)[64]) { asm volatile("" : R64(d)::"memory"); }

template <int TA>
__device__ __forceinline__ void wgmma_n8(float (&d)[4], uint64_t da, uint64_t db, int scale_d = 1) {
    asm volatile("{ .reg .pred p; setp.ne.b32 p, %7, 0;\n"
                 "wgmma.mma_async.sync.aligned.m64n8k16.f32.bf16.bf16 {%0,%1,%2,%3}, %4, %5, p, 1, 1, %6, 0; }"
                 : "+f"(d[0]), "+f"(d[1]), "+f"(d[2]), "+f"(d[3])
                 : "l"(da), "l"(db), "n"(TA), "r"(scale_d));
}

__device__ __forceinline__ float bf_lo(uint32_t u) { return __uint_as_float(u << 16); }
__device__ __forceinline__ float bf_hi(uint32_t u) { return __uint_as_float(u & 0xFFFF0000u); }
__device__ __forceinline__ float rbf(float v) { return __bfloat162float(__float2bfloat16_rn(v)); }
__device__ __forceinline__ uint32_t pack_bf(float lo, float hi) {
    uint32_t r;
    asm("cvt.rn.bf16x2.f32 %0, %1, %2;" : "=r"(r) : "f"(hi), "f"(lo));
    return r;
}
__device__ __forceinline__ uint32_t mul_bf2(uint32_t a, uint32_t b) {
    uint32_t r;
    asm("mul.rn.bf16x2 %0, %1, %2;" : "=r"(r) : "r"(a), "r"(b));
    return r;
}
__device__ __forceinline__ uint32_t fma_bf2(uint32_t a, uint32_t b, uint32_t c) {
    uint32_t r;
    asm("fma.rn.bf16x2 %0, %1, %2, %3;" : "=r"(r) : "r"(a), "r"(b), "r"(c));
    return r;
}
__device__ __forceinline__ float2 cmul(float2 a, float2 b) { return make_float2(a.x * b.x - a.y * b.y, a.x * b.y + a.y * b.x); }
__device__ __forceinline__ float2 cfma(float2 a, float2 b, float2 c) {
    return make_float2(fmaf(a.x, b.x, fmaf(-a.y, b.y, c.x)), fmaf(a.x, b.y, fmaf(a.y, b.x, c.y)));
}
__device__ __forceinline__ float sigmoidf_(float v) { return __fdividef(1.0f, 1.0f + expf(-v)); }

#define SCHED_NAMES RT0, RT1, RT2, RT3, PF0, PF1, PF2, PF3, T_SMALL, T_INIT, T_X0, T_BASE, G_NS, GT0, GT1, GT2, G0, GAP0, GAP1, RS_E, \
    PB_E0, PB_STEP, PC_E0, PC_STEP, PC_N, PC_E1, PC_S1, GU_E0, W_NUM, GC0, N1, N2, GCS, GCS2, GCS3, GCS4, HG, DL0, DLS, DC0, DCS, DN_E0, WDBG, T_OWN, T_RETRY, NP, T_Y, T_FIL0, T_FILL
enum { SCHED_NAMES, NTUNE };
constexpr int sched_default[NTUNE] = {
    1000, 2500, 3000, 3000,
    0, 1100, 1300, 2800,
    400, 500, 1, 2500, 3,
    6800, 0, 0,
    1500, 50, 50, 4,
    4, 1, 9, 4, 5, 50, 3,
    4, 9, 15, 6, 6, 7, 7, 7, 5, 43, 37, 8, 38, 1, 50,
    0, 1100, 200, 0, 700, 0, 0};
template <int I> struct Sched { static constexpr int v = sched_default[I]; };
#define TN(i) (Sched<i>::v)
#define DBG 0
#define NKK 4
#define NSA 14
#define X0 3
#define CH1 52
#define GE 8
#define DOUBLE 0
#define RAISE_J 1
#define GREEDY 0
#define POLL_S 24
#define REL_KK 1
#define PROMO CU_TENSOR_MAP_L2_PROMOTION_L2_256B

template <int TA, bool FRESH>
__device__ __forceinline__ void run_entries(uint32_t sb, int lo, int hi, int slot, float (&accA)[64], float (&accB)[64]) {
    const uint64_t da0 = TA ? make_desc_h(sb) : make_desc(sb), db0 = make_desc(sb + 2 * TILE);
    const bool leader = (threadIdx.x & 31) == 0;
    uint32_t prev = FRESH ? sb + OFF_FULL + 8 * 80 : sb + OFF_EMPTY + 8 * (lo - 1);
#pragma unroll 1
    for (int i = lo; i < hi; i++) {
        const uint32_t bar = sb + OFF_FULL + 8 * i;
        mbar_wait(bar);
        KSTAMP(i);
        const uint64_t da = da0 + (uint64_t)(slot * (SLOT >> 4)), db = db0 + (uint64_t)(slot * (SLOT >> 4));
        slot = slot == NST - 1 ? 0 : slot + 1;
        wgmma_fence();
#pragma unroll
        for (int kk = 0; kk < 4; kk++) {
            wgmma_n128<TA>(accA, da + kk * (TA ? 128 : 2), db + kk * 2, !FRESH || kk > 0 || i != lo);
            wgmma_n128<TA>(accB, da + 512 + kk * (TA ? 128 : 2), db + kk * 2, !FRESH || kk > 0 || i != lo);
            if (kk == REL_KK) {
                wgmma_commit();
                wgmma_wait<1>();
                if (leader) mbar_arrive(prev);
            }
        }
        if (REL_KK < 3) wgmma_commit();
        prev = bar + (OFF_EMPTY - OFF_FULL);
    }
}

template <int TA>
__device__ __forceinline__ void small_tile(float (&acc)[4], uint64_t da, uint64_t db, bool first) {
#pragma unroll
    for (int kk = 0; kk < 4; kk++) wgmma_n8<TA>(acc, da + kk * (TA ? 128 : 2), db + kk * 2, kk > 0 || !first);
}

template <int N>
__device__ __forceinline__ uint32_t check_tile(uint32_t sb, uint32_t dst, uint32_t probe, const char* src, uint32_t par, uint32_t bar, uint32_t phase, uint32_t pause) {
#pragma unroll 1
    for (uint32_t it = 0; it < SPIN_LIMIT; it++) {
        uint32_t v[N], bad = 0;
#pragma unroll
        for (int u = 0; u < N; u++) v[u] = lds32(probe + (N == 16 ? (u >> 1) * 1024 + (u & 1) * 256 : u * 1024));
#pragma unroll
        for (int u = 0; u < N; u += 4)
            asm("{ .reg .b32 a, b; lop3.b32 a, %1, %2, %5, 0x7E; lop3.b32 b, %3, %4, %5, 0x7E; lop3.b32 %0, %0, a, b, 0xFE; }"
                : "+r"(bad) : "r"(v[u]), "r"(v[u + 1]), "r"(v[u + 2]), "r"(v[u + 3]), "r"(par));
        if (!__any_sync(0xffffffffu, bad & 1u)) return phase;
        STAMP(10);
        __nanosleep(pause);
        if (elect_one()) {
            mbar_expect_tx(bar, N * 1024);
            bulk_load(dst, src, N * 1024, bar);
        }
        mbar_wait(bar, phase);
        phase ^= 1;
    }
    __trap();
    return 0;
}

__global__ void __launch_bounds__(512, 1)
fused_kernel(const __grid_constant__ CUtensorMap mX, const __grid_constant__ CUtensorMap mB, const __grid_constant__ CUtensorMap mCre,
             const __grid_constant__ CUtensorMap mCim, const __grid_constant__ CUtensorMap mWg, const __grid_constant__ CUtensorMap mWu,
             const __grid_constant__ CUtensorMap mWd, const __grid_constant__ CUtensorMap mXr, const __grid_constant__ CUtensorMap mPB,
             const __grid_constant__ CUtensorMap mPC, const __grid_constant__ CUtensorMap mXe, const __grid_constant__ Params prm) {
    extern __shared__ __align__(1024) uint8_t smem[];
    uint32_t sb;
    asm volatile("mov.u32 %0, %1;" : "=r"(sb) : "r"(smem_u32(smem)));
    const int tid = threadIdx.x, warp = __shfl_sync(0xffffffffu, tid >> 5, 0), lane = tid & 31;
    const int cta = blockIdx.x;
    const uint32_t cstart = clk32();
    const int chunk = (cta >> 2) & 15;
    const int dt = (cta >> 6) * 4 + (cta & 3);
    const int rid = chunk * 8 + dt;
    const bool has_gu = cta < 112;
    const uint32_t full = sb + OFF_FULL, empty = sb + OFF_EMPTY;
    const uint32_t ffull = full + 8 * 85, fempty = empty + 8 * 65;
    const uint32_t bar_epoch = full + 8 * 72, dfull = full + 8 * 73, bar_base = full + 8 * 82, bar_x = full + 8 * 83, bar_retry = full + 8 * 81, hfull = full + 8 * 90;
    const uint32_t bar_order = empty + 8 * 70, bar_const = empty + 8 * 85, bar_stored = empty + 8 * 72, bar_dfree = empty + 8 * 73,
                    bar_g = empty + 8 * 84, bar_out = empty + 8 * 76;
    const int w = warp & 3, g = lane >> 2, c = lane & 3, at = tid & 127;

    const uint32_t probe = (lane >> 3) * 32 + (g & 1) * 144 + (c & 1) * 516;

    STAMPIF(tid == 0, 0);
    GSTAMP(tid == 0, 94);
    auto init_barriers = [&]() {
        if (elect_one()) {
            const uint32_t base = warp < 6 ? full + min(8 * NST + 136 * warp, 8 * 85) : empty + min(136 * (warp - 6), 8 * 69), cnt = warp < 6 ? 1 : 4;
#pragma unroll
            for (int i = 0; i < 17; i++) mbar_init(base + 8 * i, cnt);
            fence_mbar_init();
        }
        __syncwarp();
    };
    if (warp != 12) {
        if (warp >= 14) {
            const int r = cta * 8 + g;
            if (warp == 15 && !(cta & 3) && lane < 8) st_relaxed((uint32_t*)&prm.s->start[cta >> 1] + lane, (lane & 1) ? gtime32() : cstart);
            prefetch_l2(warp == 14 ? (const char*)prm.x + (rid * 16 + (lane >> 1)) * 2048 + (c & 1 & TN(T_X0)) * 128
                                   : (const char*)((r & 512) ? prm.b_im : prm.b_re) + (r & 511) * 2048 + (c & TN(T_X0)) * 128);
        }
        sleep_until(cstart + (warp == 13 ? TN(T_SMALL) : TN(T_INIT)));
    }
    if (warp < 8) {
        init_barriers();
        asm volatile("setmaxnreg.inc.sync.aligned.u32 200;");
        named_bar(0, 480);
        STAMPIF(tid == 0 && lds32(sb + OFF_KEYS + 16) == 0, 8);
        const int wg = warp >> 2;
        const int p = wg * 512 + dt * 32 + w * 8 + g;
        uint32_t cp = sb + OFF_CONST + 8 * (wg * 64 + w * 8 + g);
        const int j1 = chunk - 1 - c;
        uint2* cq = &prm.s->carry[j1 * 1024 + p];
        char* hd = reinterpret_cast<char*>(prm.s->h) + (size_t)chunk * 524288 + wg * 262144 + (dt >> 1) * 16384 + ((dt & 1) * 4 + w) * 1024 + g * 64 + ((c ^ (g >> 1)) << 4);
        const bool never = uni(cstart == 0 && sb == 0);
        asm volatile("" : "+l"(cq), "+l"(hd), "+r"(cp));
        float2 a[2], a32[2], a64[2], a512[2], pw32[2], pw128[2];
        uint32_t mm[2], t2, par;
        auto constants = [&]() {
            mbar_wait(bar_const);
            t2 = lds32(sb + OFF_EPOCH + 4); par = lds32(sb + OFF_EPOCH) & 1u;
            auto ldc = [](uint32_t a) { const uint2 v = lds64(a); return make_float2(__uint_as_float(v.x), __uint_as_float(v.y)); };
#pragma unroll
            for (int h = 0; h < 2; h++) {
                a[h] = ldc(cp + 256 * h); a32[h] = ldc(cp + 256 * h + 1024); a64[h] = ldc(cp + 256 * h + 2048); a512[h] = ldc(cp + 256 * h + 7168);
                pw32[h] = ldc(c ? cp + 256 * h + 1024 * c : sb + OFF_ONE);
                pw128[h] = ldc(c ? cp + 256 * h + 3072 + 1024 * c : sb + OFF_ONE);
                mm[h] = lds32(sb + OFF_M + 4 * (wg * 64 + w * 8 + g + 32 * h));
            }
        };
        if (wg == 1) {
            const int pc = w * 256 + dt * 32 + lane;
            const float lr = __bfloat162float(prm.lam_re[pc]), li = __bfloat162float(prm.lam_im[pc]), ld = __bfloat162float(prm.log_dt[pc]);
            const uint32_t dk = __ldg(reinterpret_cast<const uint32_t*>(prm.dskip + dt * 128) + (at & 63));
            reinterpret_cast<uint32_t*>(smem + OFF_DK)[at & 63] = dk;
            const float dtv = rbf(expf(ld));
            const float er = expf(dtv * lr);
            float sn, cs;
            sincosf(dtv * li, &sn, &cs);
            const float ar = er * cs, ai = er * sn;
            const float nr = ar - 1.0f, ni = ai;
            const bool big = fabsf(lr) >= fabsf(li);
            const float t = (big ? li : lr) / (big ? lr : li), dn = big ? lr + li * t : lr * t + li;
            const float cr = (big ? nr + ni * t : nr * t + ni) / dn, ci = (big ? ni - nr * t : ni * t - nr) / dn;
            float2* ct = reinterpret_cast<float2*>(smem + OFF_CONST) + at;
            float2 pw = make_float2(ar, prm.swapped ? -ai : ai);
            ct[0] = pw;
            const float mx = prm.swapped ? -2.f * ci : 2.f * cr, my = prm.swapped ? 2.f * cr : -2.f * ci;
            reinterpret_cast<uint32_t*>(smem + OFF_M)[at] = pack_bf(mx, my);
            *reinterpret_cast<float2*>(smem + OFF_ONE) = make_float2(1.f, 0.f);
#pragma unroll
            for (int i = 0; i < 5; i++) pw = cmul(pw, pw);
#pragma unroll
            for (int i = 0; i < 2; i++) {
                const float2 p2 = cmul(pw, pw);
                ct[128 + 384 * i] = pw; ct[256 + 384 * i] = p2; ct[384 + 384 * i] = cmul(p2, pw);
                pw = cmul(p2, p2);
            }
            ct[896] = pw;
            mbar_wait(bar_epoch);
            __syncwarp();
            mbar_wait(empty + 8 * TN(RS_E));
            st_relaxed2(&prm.s->hid[cta * 128 + at], ~0u, ~0u);
            st_relaxed4(&prm.s->y[((at >> 4) * 8 + (cta >> 4)) * D_ + (cta & 15) * 64 + (at & 15) * 4], 0u, 0u, 0u, 0u);
            st_relaxed2(&prm.s->carry[chunk * 1024 + pc], 0u, 0u);
            __syncwarp();
            if (lane == 0) mbar_arrive(bar_const);

            STAMPIF(at == 0, 3);
            constants();
            mbar_wait(bar_order);
        }

        float accA[64], accB[64];
        run_entries<0, true>(sb, wg * 16, wg * 16 + GE, wg, accA, accB);
        if (wg == 0) constants();
        if (wg == 0 || TN(GT1)) {
            mbar_wait(bar_base);
            sched_fence(lds32(sb + OFF_EPOCH + 8) + (wg ? TN(GT1) : TN(GT0)));
        }
        run_entries<0, false>(sb, wg * 16 + GE, wg * 16 + 16, (wg + GE) % NST, accA, accB);
        if (lane == 0) mbar_arrive(bar_order + 8 * wg);
        uint2 v[2][4];
#pragma unroll
        for (int m = 0; m < 8; m++) v[m >> 2][m & 3] = make_uint2(t2, t2);
        wgmma_wait<0>();
        pin64(accA); pin64(accB);
        if (lane == 0) mbar_arrive(empty + 8 * (wg * 16 + 15));
        STAMPIF(at == 0, 30 + 10 * wg);

        auto cut = [&]() { if (never) sched_fence(cstart); };
        auto poll = [&](uint2 (&u)[4], int h) {
#pragma unroll
            for (int m = 0; m < 4; m++)
                asm volatile("{ .reg .pred p; setp.ge.s32 p, %3, %4; @p ld.relaxed.gpu.global.v2.b32 {%0, %1}, [%2]; }"
                             : "+r"(u[m].x), "+r"(u[m].y) : "l"(cq + 256 * h - 4096 * m), "r"(j1), "r"(4 * m) : "memory");
        };
        auto check = [&](const uint2 (&u)[4]) {
            uint32_t bad = 0;
#pragma unroll
            for (int m = 0; m < 4; m++) bad |= (u[m].x ^ t2) | (u[m].y ^ t2);
            return bad;
        };
        auto valid = [&](const uint2 (&u)[4]) { return __all_sync(0xffffffffu, (check(u) & 3u) == 0); };

        auto horner = [&](const uint2 (&u)[4], int h) {
            float2 r = make_float2(__uint_as_float(u[3].x), __uint_as_float(u[3].y));
#pragma unroll
            for (int m = 2; m >= 0; m--) r = cfma(a512[h], r, make_float2(__uint_as_float(u[m].x), __uint_as_float(u[m].y)));
            return r;
        };
        float2 w0[2];
#pragma unroll
        for (int h = 0; h < 2; h++) {
            float (&acc)[64] = h ? accB : accA;
            float2 e = make_float2(acc[0], acc[2]);
#pragma unroll
            for (int s = 1; s < 32; s++) {
                const int i0 = 4 * (s >> 1) + (s & 1);
                e = cfma(a[h], e, make_float2(acc[i0], acc[i0 + 2]));
                if (!GREEDY && h == 1 && s == POLL_S) { cut(); poll(v[0], 0); }
            }
            float2 y = make_float2(__shfl_up_sync(0xffffffffu, e.x, 1, 4), __shfl_up_sync(0xffffffffu, e.y, 1, 4));
            if (c >= 1) e = cfma(a32[h], y, e);
            y = make_float2(__shfl_up_sync(0xffffffffu, e.x, 2, 4), __shfl_up_sync(0xffffffffu, e.y, 2, 4));
            if (c >= 2) e = cfma(a64[h], y, e);
            if (c == 3) st_relaxed2(cq + 4096 + 256 * h, (__float_as_uint(e.x) & ~3u) | t2, (__float_as_uint(e.y) & ~3u) | t2);
            if (h || !GREEDY) cut();
            w0[h] = make_float2(__shfl_up_sync(0xffffffffu, e.x, 1, 4), __shfl_up_sync(0xffffffffu, e.y, 1, 4));
            if (c == 0) w0[h] = make_float2(0.f, 0.f);
            STAMPIF(at == 0 && (h || !GREEDY), 31 + h + 10 * wg);
        }
        if (GREEDY) { __nanosleep(100); poll(v[0], 0); __nanosleep(100); }
        uint32_t sx[2][16], sy[2][16], mr[2][4], tp;
        const uint32_t gap = wg ? TN(GAP1) : TN(GAP0);
#pragma unroll
        for (int h = 0; h < 2; h++) {
            const uint32_t sg = prm.swapped ? 0x80008000u : 0u;
            mr[h][0] = __byte_perm(mm[h], 0, 0x1010); mr[h][1] = __byte_perm(mm[h], 0, 0x3232);
            mr[h][2] = mr[h][1] ^ sg; mr[h][3] = mr[h][0] ^ sg ^ 0x80008000u;
        }
        auto put = [&](int e, int j) {
            uint32_t d[4];
#pragma unroll
            for (int u = 0; u < 4; u++) d[u] = fma_bf2(mr[e >> 1][2 * (e & 1)], sx[e >> 1][4 * j + u], mul_bf2(mr[e >> 1][2 * (e & 1) + 1], sy[e >> 1][4 * j + u]));
            d[j] = (d[j] & ~1u) | par;
            stg128(hd + e * 65536 + (j >> 1) * 8192 + (j & 1) * 512, d[0], d[1], d[2], d[3]);
            if (j == 3 && lane == 0) mbar_arrive(bar_out + 32 * wg + 8 * e);
        };
#pragma unroll
        for (int h = 0; h < 2; h++) {
            float (&acc)[64] = h ? accB : accA;
            float2 hin;
            uint32_t it = 0;
            if (h == 0 && DOUBLE) {
                while (true) {
                    poll(v[1], 0);
                    if (valid(v[0])) { hin = horner(v[0], 0); break; }
                    poll(v[0], 0);
                    if (valid(v[1])) { hin = horner(v[1], 0); it++; break; }
                    if (++it > SPIN_LIMIT) __trap();
                }
            } else {
                while (!valid(v[0])) {
                    poll(v[0], h);
                    if (++it > SPIN_LIMIT) __trap();
                }
                hin = horner(v[0], h);
            }
            STAMPIF(at == 0 && it > 0 && h == 0, 39 + 10 * wg);
            hin = cmul(pw128[h], hin);
            hin.x += __shfl_xor_sync(0xffffffffu, hin.x, 1); hin.y += __shfl_xor_sync(0xffffffffu, hin.y, 1);
            hin.x += __shfl_xor_sync(0xffffffffu, hin.x, 2); hin.y += __shfl_xor_sync(0xffffffffu, hin.y, 2);
            float2 st = cfma(pw32[h], hin, w0[h]);
            STAMPIF(at == 0, 33 + 3 * h + 10 * wg);
#pragma unroll
            for (int j = 0; j < 4; j++) {
#pragma unroll
                for (int u = 0; u < 4; u++) {
                    const int i0 = 16 * j + 4 * u;
                    const float2 y = cfma(a[h], st, make_float2(acc[i0], acc[i0 + 2]));
                    st = cfma(a[h], y, make_float2(acc[i0 + 1], acc[i0 + 3]));
                    sx[h][4 * j + u] = pack_bf(y.x, st.x); sy[h][4 * j + u] = pack_bf(y.y, st.y);
                }
                if (h) sleep_until(tp += gap);
                if (h == 0 && j == RAISE_J) poll(v[0], 1);
                put(2 * h, j);
                cut();
            }
            STAMPIF(at == 0, 34 + 3 * h + 10 * wg);
            tp = clk32();
#pragma unroll
            for (int j = 0; j < 4; j++) {
                sleep_until(tp += gap);
                put(2 * h + 1, j);
            }
        }
        STAMPIF(at == 0, 38 + 10 * wg);

        if (wg == 1) {
            const char* src = reinterpret_cast<const char*>(prm.s->h) + (size_t)chunk * 524288;
            uint32_t rpar = 1;
#pragma unroll 1
            for (int i = CH1 + w; i < NBIG; i += 4) {
                const uint32_t slot = i % NST;
                mbar_wait(empty + 8 * (i - NST));
                mbar_wait(hfull + 8 * slot, (i - 32) / NST & 1);
                rpar = check_tile<16>(sb, sb + slot * SLOT, sb + slot * SLOT + probe + (c >> 1) * 8200, src + (i - 32) * 2 * TILE, par, full + 8 * w, rpar, TN(T_RETRY));
                if (lane == 0) mbar_expect_tx(full + 8 * i, 2 * TILE);
            }
#pragma unroll 1
            for (int n = w; n < 16; n += 4) {
                mbar_wait(empty + 8 * (NBIG - 7 + n));
                mbar_wait(hfull + 8 * (NST + n % 7), n / 7 & 1);
                const uint32_t dst = sb + tail_h(n);
                rpar = check_tile<8>(sb, dst, dst + probe + (c >> 1) * 256 + (n & 8), src + (24 + (n & 7)) * 2 * TILE + (n >> 3) * TILE, par, full + 8 * w, rpar, TN(T_RETRY));
                if (lane == 0) mbar_expect_tx(full + 8 * (NBIG + n), n < 8 ? 2 * TILE : 0);
            }
        } else {
            const int tl = 64 * (w & 1) + 8 * (w >> 1) + g;
            float gf[4];
            float* op = prm.out + (size_t)(chunk * 128 + tl) * D_ + dt * 128 + 4 * c;
            const int xr = 2 * (g & 3) + (g >> 2);
            uint32_t xs = sb + OFF_FT + 3 * TILE + (32 * (w & 1) + 8 * (w >> 1) + xr) * 128 + (((c >> 1) ^ xr) << 4) + (c & 1) * 8;
            uint32_t gs = sb + OFF_G + 2 * tl;
            asm volatile("" : "+r"(gs), "+l"(op), "+r"(xs));
            float outA[64], outB[64];
            STAMPIF(at == 0, 9);
            mbar_wait(bar_order + 8);
            STAMPIF(at == 0, 35);
            if (TN(GT2)) sched_fence(lds32(sb + OFF_EPOCH + 8) + TN(GT2));
            run_entries<1, true>(sb, 32, NBIG, 32 % NST, outA, outB);
            uint32_t gp[2], om[2];
            uint2 xa[3][8], xb[3][8];
            auto coef = [&](int r0) {
#pragma unroll
                for (int r = 0; r < 2; r++) {
                    const float gv = gf[r0 + r];
                    const bool routed = (int)__float_as_uint(gv) < 0;
                    gp[r] = routed ? 0u : pack_bf(gv, gv); om[r] = routed ? 0u : pack_bf(1.0f - gv, 1.0f - gv);
                }
            };
            auto load_x = [&](uint2 (&xv)[3][8], int r0, int j) {
#pragma unroll
                for (int r = 0; r < 3; r++) xv[r][j] = lds64(r == 2 ? sb + OFF_DK + c * 8 + 32 * j : (xs ^ ((j & 3) << 5)) + (r0 + (j >> 2)) * TILE + r * 2048);
            };
            auto term = [&](uint2 (&xv)[3][8], int j) {
                const uint2 dk = xv[2][j];
#pragma unroll
                for (int r = 0; r < 2; r++) {
                    xv[r][j].x = mul_bf2(xv[r][j].x, fma_bf2(gp[r], dk.x, om[r]));
                    xv[r][j].y = mul_bf2(xv[r][j].y, fma_bf2(gp[r], dk.y, om[r]));
                }
            };
            auto store = [&](const float (&acc)[64], const uint2 (&xv)[3][8], int r0, int j, int r) {
                const int o = 8 * j + 2 * r;
                const float gv = fabsf(gf[r0 + r]);
                stg128(op + (r * 32 + r0 * 8) * D_ + 16 * j, __float_as_uint(fmaf(gv, acc[o], bf_lo(xv[r][j].x))), __float_as_uint(fmaf(gv, acc[o + 1], bf_hi(xv[r][j].x))),
                       __float_as_uint(fmaf(gv, acc[o + 4], bf_lo(xv[r][j].y))), __float_as_uint(fmaf(gv, acc[o + 5], bf_hi(xv[r][j].y))));
            };
            uint64_t dh = make_desc_h(sb), dc = make_desc(sb);
#pragma unroll
            for (int n = 0; n < 16; n++) {
                const int j = n & 7;
                asm volatile("mov.b64 %0, %0; mov.b64 %1, %1;" : "+l"(dh), "+l"(dc));
                mbar_wait(full + 8 * (NBIG + n));
                KSTAMP(NBIG + n);
                const uint64_t da = dh + (uint64_t)(tail_h(n) >> 4), db = dc + (uint64_t)(tail_c(j) >> 4);
                wgmma_fence();
#pragma unroll
                for (int kk = 0; kk < 4; kk++) {
                    wgmma_n128<1>(n < 8 ? outA : outB, da + kk * 128, db + kk * 2);
                    if (n > 8 && (kk & 1) && 2 * j + (kk >> 1) < NSA) store(outA, xa, 0, j, kk >> 1);
                }
                wgmma_commit();
                if (n == X0 - 1) {
                    mbar_wait(bar_g);
#pragma unroll
                    for (int r = 0; r < 4; r++) {
                        uint32_t u;
                        asm volatile("ld.shared.u16 %0, [%1];" : "=r"(u) : "r"(gs + (r & 1) * 64 + (r >> 1) * 32) : "memory");
                        gf[r] = bf_lo(u);
                    }
                }
                if (n == X0) { coef(0); mbar_wait(bar_x); }
                if (n < 10) {
                    wgmma_wait<1>();
                    if (lane == 0) mbar_arrive(empty + 8 * (NBIG + n - 1));
                }
#pragma unroll
                for (int u = 0; u < 8; u++) {
                    if (X0 + 1 + u * (7 - X0) / 8 == n) term(xa, u);
                }
#pragma unroll
                for (int u = 0; u < 8; u++) {
                    if (X0 + u * (7 - X0) / 8 == n) load_x(xa, 0, u);
                }
                if (n == 8) {
                    pin64(outA);
                    store(outA, xa, 0, 0, 0);
                    store(outA, xa, 0, 0, 1);
                }
            }
            mbar_wait(bar_x + 8);
            load_x(xb, 2, 0);
            load_x(xb, 2, 1);
            coef(2);
#pragma unroll
            for (int u = NSA; u < 16; u++) store(outA, xa, 0, u >> 1, u & 1);
            term(xb, 0);
            wgmma_wait<0>();
            pin64(outB);
            STAMPIF(at == 0, 51);
#pragma unroll
            for (int j = 0; j < 8; j++) {
                if (j < 6) load_x(xb, 2, j + 2);
                if (j) term(xb, j);
                store(outB, xb, 2, j, 0);
                store(outB, xb, 2, j, 1);
            }
            __syncwarp();
            if (lane == 0) mbar_arrive(bar_stored);
            STAMPIF(at == 0, 52);
        }
    } else if (warp < 12) {
        asm volatile("setmaxnreg.dec.sync.aligned.u32 72;");
        init_barriers();
#pragma unroll
        for (int i = 0; i < 2; i++) sts128(sb + OFF_LIST + i * 2048 + at * 16, 0u, 0u, 0u, 0u);
        uint32_t* keys = reinterpret_cast<uint32_t*>(smem + OFF_KEYS);
        keys[4] = 0;
        named_bar(0, 480);
        mbar_wait(bar_epoch);
        const uint32_t t2 = lds32(sb + OFF_EPOCH + 4);
        STAMPIF(at == 0, 20);
        float facc[4];
        const uint64_t dft = make_desc(sb + OFF_FT), dxs = make_desc(sb + OFF_XS);
#pragma unroll 1
        for (int u = 0; u < 4; u++) {
            mbar_wait(ffull + 8 * u);
            STAMPIF(at == 0, 4 + u);
            wgmma_fence();
            small_tile<0>(facc, dft + u * (TILE >> 4), dxs + u * 64, u == 0);
            wgmma_commit();
        }
        wgmma_wait<0>();
        pin4(facc);
        if (lane < 4) mbar_arrive(fempty + 8 * lane);
        auto gate_up = [&](auto rest) {
            uint32_t slot = 4, par = 0, prev = full + 8 * 80;
#pragma unroll 1
            for (int j = 0; j < 16; j++) {
                if (j == 2) rest();
                STAMPW(at == 0, 74 + j);
                mbar_wait(ffull + 8 * slot, par);
                STAMPW(at == 0, 160 + j);
                mbar_wait(empty + 8 * prm.use[j]);
                wgmma_fence();
                small_tile<1>(facc, dft + slot * (TILE >> 4), dxs + j * 64, j == 0);
                wgmma_commit();
                if (j < TN(NP)) { wgmma_wait<0>(); prev = fempty + 8 * slot; }
                else wgmma_wait<1>();
                if (lane == 0) mbar_arrive(prev);
                prev = j < TN(NP) ? full + 8 * 80 : fempty + 8 * slot;
                if (++slot == NFT) { slot = 0; par ^= 1; }
            }
            wgmma_wait<0>();
            if (lane == 0) mbar_arrive(prev);
            pin4(facc);
        };
        auto down = [&]() {
            const uint64_t dhid = make_desc(sb + OFF_HID);
#pragma unroll 1
            for (int j = 0; j < 7; j++) {
                mbar_wait(dfull + 8 * j);
                mbar_wait(empty + 8 * prm.use[16 + j]);
                wgmma_fence();
                small_tile<1>(facc, dft + j * (TILE >> 4), dhid + j * 64, j == 0);
                wgmma_commit();
                if (j && !(j & 1)) {
                    wgmma_wait<0>();
                    if (lane == 0) mbar_arrive(bar_dfree + 4 * j - 8);
                }
            }
            wgmma_wait<0>();
            pin4(facc);
        };
        if ((c & 1) == (w >> 1)) {
            float* red = reinterpret_cast<float*>(smem + OFF_RED) + w * 32 + (c >> 1) * 16 + g;
            red[0] = (w & 1) ? facc[1] : facc[0];
            red[8] = (w & 1) ? facc[3] : facc[2];
        }
        named_bar(2, 128);
        STAMPIF(at == 0, 21);
        const uint32_t tpub = clk32();
        if (w < 2) {
            const float* red = reinterpret_cast<const float*>(smem + OFF_RED) + w * 16 + (lane & 15);
            const float v = rbf((red[0] + red[32]) + (red[64] + red[96]));
            if (w == 0) {
                uint32_t k = __float_as_uint(v);
                k = ((k ^ ((uint32_t)((int)k >> 31) | 0x80000000u)) & 0xFFFF0000u) | (t2 << 11) | (2047u - (uint32_t)(rid * 16 + (lane & 15)));
                int rank = 0;
#pragma unroll
                for (int i = 0; i < 8; i++) rank += __shfl_sync(0xffffffffu, k, (lane >> 4) * 8 + i) > k;
                rank += __shfl_xor_sync(0xffffffffu, rank, 16);
                if (rank < 8) st_relaxed(&prm.s->key[cta * 8 + rank], k);
            } else if (lane < 16) st_relaxed(&prm.s->gate[rid * 16 + lane], __float_as_uint(rbf(sigmoidf_(v))) | t2);
            __syncwarp();
        }
        uint32_t it = 0;
        uint4 ka, kb4;
        sleep_until(tpub + TN(G0));
        while (true) {
            ka = ld_relaxed4(&prm.s->key[at * 8]);
            kb4 = ld_relaxed4(&prm.s->key[at * 8 + 4]);
            if (__all_sync(0xffffffffu, (((ka.x ^ (t2 << 11)) | (kb4.x ^ (t2 << 11))) & 0x1800u) == 0)) break;
            if (++it > SPIN_LIMIT) __trap();
        }
        STAMPIF(at == 0, 22);
        STAMPIF(at == 0 && it > 0, 23);
        const uint32_t m1 = __reduce_max_sync(0xffffffffu, ka.x), m2 = __reduce_max_sync(0xffffffffu, ka.x == m1 ? ka.y : ka.x);
        if (lane == 0) keys[w] = m2;
        named_bar(2, 128);
        const uint4 th4 = *reinterpret_cast<const uint4*>(keys);
        const uint32_t th = min(min(th4.x, th4.y), min(th4.z, th4.w));
        {
            const uint32_t k8[8] = {ka.x, ka.y, ka.z, ka.w, kb4.x, kb4.y, kb4.z, kb4.w};
            auto append = [&](int lo, int hi) {
                uint32_t n = 0, pos = 0;
#pragma unroll
                for (int i = lo; i < hi; i++) n += k8[i] >= th;
                asm volatile("{ .reg .pred p; setp.ne.u32 p, %2, 0; @p atom.shared.add.u32 %0, [%1], %2; }" : "+r"(pos) : "r"(sb + OFF_KEYS + 16), "r"(n) : "memory");
#pragma unroll
                for (int i = lo; i < hi; i++)
                    if (k8[i] >= th) reinterpret_cast<uint32_t*>(smem + OFF_LIST)[pos + i - lo] = k8[i];
            };
            append(0, 2);
            if (__any_sync(0xffffffffu, k8[2] >= th)) append(2, 8);
        }
        named_bar(2, 128);
        {
            const uint32_t* list = reinterpret_cast<const uint32_t*>(smem + OFF_LIST);
            const int n = (int)keys[4];
#pragma unroll 1
            for (int i0 = w * 32; i0 < n; i0 += 128) {
                const uint32_t k = list[i0 + lane];
                int rank = 0;
#pragma unroll 2
                for (int o = 0; o < n; o += 4) {
                    const uint4 l4 = *reinterpret_cast<const uint4*>(list + o);
                    rank += (l4.x > k) + (l4.y > k) + (l4.z > k) + (l4.w > k);
                }
                if (rank < 8) reinterpret_cast<uint32_t*>(smem + OFF_SEL)[rank] = k;
            }
        }
        named_bar(2, 128);
        STAMPIF(at == 0, 24);
        const uint32_t* sel = reinterpret_cast<const uint32_t*>(smem + OFF_SEL);
        auto gates = [&]() {
            uint32_t gv;
            it = 0;
            while (true) {
                gv = ld_relaxed(&prm.s->gate[chunk * 128 + at]);
                const uint32_t ar = ld_relaxed(&prm.s->armed[((cta >> 4) * 14 + min(lane, 13)) * 4]);
                if (__all_sync(0xffffffffu, (gv & 3u) == t2 && ar == t2)) break;
                if (++it > SPIN_LIMIT) __trap();
            }
            asm volatile("fence.acquire.gpu;" ::: "memory");
#pragma unroll
            for (int s = 0; s < 8; s++)
                if ((~sel[s] & 2047u) == (uint32_t)(chunk * 128 + at)) gv |= 0x80000000u;
            reinterpret_cast<uint16_t*>(smem + OFF_G)[at] = (uint16_t)(gv >> 16);
            __syncwarp();
            if (lane == 0) mbar_arrive(bar_g);
        };
        if (has_gu) {
            const int tk = (at >> 3) & 7;
            const char* xt = (const char*)prm.x + (~sel[tk] & 2047u) * 2048 + (at >> 6) * 128 + (at & 7) * 16;
#pragma unroll
            for (int i = 0; i < 8; i++) {
                cp_async16(sb + OFF_XS + (2 * i + (at >> 6)) * 1024 + tk * 128 + (((at & 7) ^ tk) << 4), xt + i * 256);
                if (i == 0 || i == 7) asm volatile("cp.async.commit_group;" ::: "memory");
            }
            asm volatile("cp.async.wait_group 1;" ::: "memory");
            fence_async_smem();
            named_bar(2, 128);
            STAMPIF(at == 0, 25);
            gate_up([&]() {
                asm volatile("cp.async.wait_all;" ::: "memory");
                fence_async_smem();
                named_bar(2, 128);
            });
            if (!(cta & 1)) {
#pragma unroll
                for (int u = 0; u < 4; u++) {
                    const float v = rbf(facc[u]);
                    facc[u] = __fdividef(v, 1.0f + __expf(-v));
                }
            }
            st_relaxed2(&prm.s->hid[cta * 128 + at], pack_bf(facc[0], facc[1]), pack_bf(facc[2], facc[3]));
        }
        STAMPIF(at == 0, 26);
        gates();
        {
            mbar_wait(empty + 8 * max(TN(HG), 31));
            const uint2* hp = &prm.s->hid[(cta >> 4) * 14 * 128 + at];
            uint32_t hv[16];
            it = 0;
            while (true) {
                uint32_t top = 0;
#pragma unroll
                for (int j = 0; j < 7; j++) {
                    const uint2 hg = ld_relaxed2(hp + 256 * j), hu = ld_relaxed2(hp + 256 * j + 128);
                    top = max(top, max(hg.x, hu.x));
                    hv[2 * j] = mul_bf2(hg.x, hu.x); hv[2 * j + 1] = mul_bf2(hg.y, hu.y);
                }
                if (__all_sync(0xffffffffu, top != ~0u)) break;
                do {
                    if (++it > SPIN_LIMIT) __trap();
                } while (!__all_sync(0xffffffffu, ld_relaxed(hp + min(lane, 13) * 128 - lane) != ~0u));
            }
            STAMPIF(at == 0 && it > 0, 61);
            hv[14] = hv[15] = 0;
#pragma unroll
            for (int j = 0; j < 4; j++)
                asm volatile("stmatrix.sync.aligned.m8n8.x4.trans.shared.b16 [%0], {%1, %2, %3, %4};" ::"r"(
                                 sb + OFF_HID + (2 * j + (lane >> 4)) * 1024 + (lane & 7) * 128 + (((2 * w + ((lane >> 3) & 1)) ^ (lane & 7)) << 4)),
                             "r"(hv[4 * j]), "r"(hv[4 * j + 1]), "r"(hv[4 * j + 2]), "r"(hv[4 * j + 3]) : "memory");
        }
        fence_async_smem();
        named_bar(2, 128);
        STAMPIF(at == 0, 27);
        uint32_t mine = __ballot_sync(0xffffffffu, lane < 8 && (int)((~sel[lane & 7] & 2047u) >> 7) == chunk), tr;
        uint2 xr, xd;
        float gr, rs;
        auto skip = [&](int n) {
#pragma unroll 1
            for (int i = 0; i < n; i++) mine &= mine - 1;
            if (mine) {
                const uint32_t key = sel[__ffs(mine) - 1], kb = key >> 16;
                tr = ~key & 2047u;
                xr = __ldg(reinterpret_cast<const uint2*>(prm.x + (size_t)tr * D_ + dt * 128) + lane);
                rs = rbf(sigmoidf_(bf_lo((kb & 0x8000u) ? (kb & 0x7FFFu) : (~kb & 0xFFFFu))));
                gr = fabsf(__bfloat162float(reinterpret_cast<const __nv_bfloat16*>(smem + OFF_G)[tr & 127]));
                xd = lds64(sb + OFF_DK + 8 * lane);
            }
        };
        skip(w);
        down();
#pragma unroll
        for (int u = 0; u < 4; u++)
            st_relaxed(&prm.s->y[((2 * c + (u & 1)) * 8 + (cta >> 4)) * D_ + (cta & 15) * 64 + w * 16 + g + 8 * (u >> 1)], (__float_as_uint(facc[u]) & ~3u) | t2);
        STAMPIF(at == 0, 28);
        sleep_until(clk32() + TN(T_Y));
        while (mine) {
            const uint32_t* yp = &prm.s->y[(__ffs(mine) - 1) * 8 * D_ + dt * 128 + 4 * lane];
            float y[4];
            it = 0;
            while (true) {
                uint32_t bad = 0;
                y[0] = y[1] = y[2] = y[3] = 0.f;
#pragma unroll
                for (int ks = 0; ks < 8; ks++) {
                    const uint4 v = ld_relaxed4(yp + ks * D_);
                    bad |= v.x ^ t2;
                    y[0] += __uint_as_float(v.x); y[1] += __uint_as_float(v.y); y[2] += __uint_as_float(v.z); y[3] += __uint_as_float(v.w);
                }
                if (__all_sync(0xffffffffu, (bad & 3u) == 0)) break;
                if (++it > SPIN_LIMIT) __trap();
            }
            STAMPIF(lane == 0 && it, 62);
#pragma unroll
            for (int u = 0; u < 4; u++) {
                const uint32_t x2 = (u & 2) ? xr.y : xr.x, d2 = mul_bf2(x2, (u & 2) ? xd.y : xd.x);
                y[u] = fmaf(gr, (u & 1) ? bf_hi(d2) : bf_lo(d2), rbf(rbf(1.0f - gr) * rbf(((u & 1) ? bf_hi(x2) : bf_lo(x2)) + rbf(rbf(y[u]) * rs))));
            }
            STAMPIF(lane == 0, 50);
            mbar_wait(bar_stored);
            asm volatile("red.global.add.v4.f32 [%0], {%1, %2, %3, %4};" ::"l"(prm.out + (size_t)tr * D_ + dt * 128 + 4 * lane), "f"(y[0]), "f"(y[1]), "f"(y[2]), "f"(y[3]) : "memory");
            skip(4);
        }
        STAMPIF(lane == 0, 29);
    } else {
        asm volatile("setmaxnreg.dec.sync.aligned.u32 40;");
        if (warp == 15) {
            prefetch_map(&mXr);
            named_bar(0, 480);
#pragma unroll 1
            for (int i = 0; i < 4; i++) {
                const int u = i;
                if (lane == 0) mbar_expect_tx(ffull + 8 * u, TILE);
                sleep_until(cstart + (i == 0 ? TN(RT0) : i == 1 ? TN(RT1) : i == 2 ? TN(RT2) : TN(RT3)));
                if (elect_one()) tma3(sb + OFF_FT + u * TILE, &mXr, u * 256, rid * 16, ffull + 8 * u);
                STAMP(53 + u);
            }
            const CUtensorMap* mw = (cta & 1) ? &mWu : &mWg;
            if (sb & 1023) __trap();
            prefetch_map(mw);
            prefetch_map(&mWd);
            uint32_t slot = 4, par = 1;
#pragma unroll 1
            for (int j = 0; j < (has_gu && DBG != 1 ? 16 : 0); j++) {
                mbar_wait(fempty + 8 * slot, par);
                if (lane == 0) mbar_expect_tx(ffull + 8 * slot, TILE);
                mbar_wait(empty + 8 * prm.fetch[j]);
                STAMPW(1, 176 + j);
                if (elect_one()) tma2(sb + OFF_FT + slot * TILE, mw, (cta >> 1) * 64, TN(WDBG) ? 0 : j * 64, ffull + 8 * slot);
                if (++slot == NFT) { slot = 0; par ^= 1; }
            }
            if (lane < 9) mbar_expect_tx(lane < 7 ? dfull + 8 * lane : bar_x + 8 * (lane - 7), lane < 7 ? TILE : 2 * TILE);
            if (!has_gu) mbar_wait(bar_g);
#pragma unroll 1
            for (int j = 0; j < (DBG != 1 ? 7 : 0); j++) {
                if (has_gu) mbar_wait(fempty + 8 * min(j, 4), 1);
                mbar_wait(empty + 8 * prm.fetch[16 + j]);
                if (elect_one()) tma2(sb + OFF_FT + j * TILE, &mWd, (cta & 15) * 64, (cta >> 4) * 448 + (TN(WDBG) ? 0 : j * 64), dfull + 8 * j);
            }
            prefetch_map(&mXe);
#pragma unroll 1
            for (int u = 0; u < 4; u++) {
                mbar_wait(bar_dfree + 8 + 4 * (u & 2));
                mbar_wait(empty + 8 * (TN(DN_E0) + u));
                if (elect_one())
                    asm volatile("cp.async.bulk.tensor.5d.shared::cluster.global.mbarrier::complete_tx::bytes [%0], [%1, {%3, %6, %6, %4, %5}], [%2];"
                                 ::"r"(sb + OFF_FT + (3 + u) * TILE), "l"(&mXe), "r"(bar_x + 4 * (u & 2)), "r"(dt * 128 + (u & 1) * 64), "r"(u & 2), "r"(chunk * 4), "r"(0) : "memory");
            }
        } else if (warp == 13) {
#pragma unroll
            for (int u = 0; u < 8; u++) {
                const int row = (u >> 2) * 4 + (lane >> 3);
                cp_async16(sb + OFF_XS + (u & 3) * 1024 + row * 128 + (((lane & 7) ^ row) << 4), (const char*)(u < 4 ? prm.w_r : prm.gate_w) + (u & 3) * 512 + lane * 16);
            }
            STAMP(57);
            const uint32_t tag = ld_relaxed(&prm.s->epoch[cta]) + 1;
            named_bar(1, 64);
            *reinterpret_cast<uint2*>(smem + OFF_EPOCH) = make_uint2(tag, tag % 3u + 1u);
            STAMPIF(tag, 58);
            asm volatile("cp.async.wait_all;" ::: "memory");
            STAMP(59);
            fence_async_smem();
            __syncwarp();
            if (lane == 0) {
                mbar_arrive(bar_epoch);
                prm.s->epoch[cta] = tag;
            }
            sleep_until(cstart + TN(T_BASE));
            {
                const uint2 st = ld_relaxed2(&prm.s->start[2 * lane]);
                const uint32_t d = st.x - cstart + 512u, age = gtime32() - st.y;
                const uint32_t m = __reduce_max_sync(0xffffffffu, d < 1024u && age < 4096u ? (d << 12) | age : 0u);
                const uint32_t late = (m & 4095u) - __reduce_min_sync(0xffffffffu, age);
                *reinterpret_cast<volatile uint32_t*>(smem + OFF_EPOCH + 8) = cstart + (m ? (m >> 12) - 512u + min(late, 256u) * TN(G_NS) / 4 : 0u);
                __syncwarp();
                if (lane == 0) mbar_arrive(bar_base);
                STAMP(60);
            }
            mbar_wait(bar_const);
            asm volatile("fence.acq_rel.gpu;" ::: "memory");
            if (lane < 4) st_relaxed2(&prm.s->armed[cta * 4 + lane], tag % 3u + 1u, 0u);
            prefetch_map(&mCre);
            prefetch_map(&mCim);
            const char* src = reinterpret_cast<const char*>(prm.s->h) + (size_t)chunk * 524288;
            uint32_t slot = 32 % NST, hpar = 0, rpar = 0;
#pragma unroll 1
            for (int i = 32; i < CH1; i++) {
                mbar_wait(hfull + 8 * slot, hpar);
                rpar = check_tile<16>(sb, sb + slot * SLOT, sb + slot * SLOT + probe + (c >> 1) * 8200, src, tag, bar_retry, rpar, TN(T_RETRY));
                if (lane == 0) mbar_expect_tx(full + 8 * i, 2 * TILE);
                src += 2 * TILE;
                slot = slot == NST - 1 ? 0 : slot + 1;
                hpar ^= slot == 32 % NST;
            }
        } else if (warp == 14) {
            prefetch_map(&mPB);
            auto pf_c = [&](int k) { prefetch_slice(&mPC, 4 * (k >> 1), cta * 8 + (k & 1) * 4); };
            named_bar(0, 480);
            asm volatile("bar.arrive 1, 64;" ::: "memory");
            if (lane < 24) st_relaxed(lane < 8 ? &prm.s->key[cta * 8 + lane] : &prm.s->gate[rid * 16 + lane - 8], 0u);
#pragma unroll 1
            for (int k = TN(PF0) ? 0 : 1; k < 4; k++) {
                sleep_until(cstart + (k == 0 ? TN(PF0) : k == 1 ? TN(PF1) : k == 2 ? TN(PF2) : TN(PF3)));
                if (elect_one()) prefetch_slice(&mPB, 4 * k, cta * 4);
            }
#pragma unroll 1
            for (int k = 0; k < 4; k++) {
                mbar_wait(empty + 8 * (TN(PB_E0) + TN(PB_STEP) * k));
                if (elect_one()) prefetch_slice(&mPB, 4 * k, 512 + cta * 4);
            }
#pragma unroll 1
            for (int k = 0; k < TN(PC_N); k++) {
                mbar_wait(empty + 8 * min(TN(PC_E0) + TN(PC_STEP) * k / 2, 26));
                if (elect_one()) pf_c(k);
            }
            int pk = TN(PC_N), pe = TN(PC_E1);
            auto own_part = [&](int e) {
                if (!mbar_test(bar_out + 8 * e, 0)) {
                    mbar_wait(bar_out + 8 * e);
                    sleep_until(clk32() + TN(T_OWN));
                    STAMP(11);
                }
            };
            const char* src = reinterpret_cast<const char*>(prm.s->h) + (size_t)chunk * 524288;
            uint32_t slot = 32 % NST;
#pragma unroll 1
            for (int i = 32; i < NBIG; i++) {
                if (!(i & 3)) own_part((i - 32) >> 2);
                mbar_wait(empty + 8 * (i - NST));
                PSTAMP(i);
                if (elect_one()) {
                    mbar_expect_tx(hfull + 8 * slot, 2 * TILE);
                    bulk_load(sb + slot * SLOT, src, 2 * TILE, hfull + 8 * slot);
                }
                if (i == pe && pk < 8) {
                    if (elect_one()) pf_c(pk);
                    pk++; pe += TN(PC_S1);
                }
                src += 2 * TILE;
                slot = slot == NST - 1 ? 0 : slot + 1;
            }
            mbar_wait(bar_dfree);
#pragma unroll
            for (int k = 0; k < 14; k++) {
                if (k == 4) continue;
                if (k == 0 || k == 2) own_part(6 + k / 2);
                mbar_wait(empty + 8 * (NBIG - NST + k));
                if (elect_one()) {
#pragma unroll
                    for (int n = k < 5 ? 2 * k : k + 2; n < (k < 3 ? 2 * k + 2 : k == 3 ? 7 : k + 3); n++) {
                        mbar_expect_tx(hfull + 8 * (NST + n % 7), TILE);
                        bulk_load(sb + tail_h(n), src + (n & 7) * 2 * TILE + (n >> 3) * TILE, TILE, hfull + 8 * (NST + n % 7));
                    }
                }
            }
        } else {
            if (elect_one()) {
#pragma unroll
                for (int i = 0; i < NST; i++) mbar_init(full + 8 * i, 1);
                fence_mbar_init();
            }
            __syncwarp();
#pragma unroll 1
            for (int i = 0; i < NST; i++) {
                if (elect_one()) {
                    mbar_expect_tx(full + 8 * i, SLOT);
                    tma5b(sb + i * SLOT, &mB, i * 64, dt * 4, full + 8 * i);
                    tma4(sb + i * SLOT + 2 * TILE, &mX, i * 64, chunk * 64, full + 8 * i);
                }
                STAMPIF(i == 0, 1);
                if (TN(T_FILL)) sleep_until(cstart + TN(T_FIL0) + i * TN(T_FILL));
            }
            STAMP(2);
            named_bar(0, 480);
            uint32_t dst = sb;
#pragma unroll 1
            for (int i = NST; i < 32; i++) {
                if (lane == 0) mbar_expect_tx(full + 8 * i, SLOT);
                mbar_wait(empty + 8 * (i - NST));
                PSTAMP(i);
                if (elect_one()) {
                    tma5b(dst, &mB, (i & 15) * 64, (i >> 4) * 64 + dt * 4, full + 8 * i);
                    tma4(dst + 2 * TILE, &mX, (i & 15) * 64, chunk * 64, full + 8 * i);
                }
                dst = dst == sb + (NST - 1) * SLOT ? sb : dst + SLOT;
            }
#pragma unroll 1
            for (int i = 32; i < NBIG; i++) {
                mbar_wait(empty + 8 * (i - NST));
                if (elect_one()) tma5(dst + 2 * TILE, (i & 4) ? &mCim : &mCre, ((i & 3) + ((i >> 1) & 12)) * 64, dt * 8, full + 8 * i);
                dst = dst == sb + (NST - 1) * SLOT ? sb : dst + SLOT;
            }
            dst = sb + tail_c(0);
#pragma unroll 1
            for (int j = 0; j < 8; j++) {
                mbar_wait(empty + 8 * (NBIG - NST + 1 + (j >> 1)));
                if (elect_one()) tma5(dst, (j & 4) ? &mCim : &mCre, ((j & 3) + 12) * 64, dt * 8, full + 8 * (NBIG + j));
                dst = j == 5 ? sb : dst + 2 * TILE;
            }
        }
    }
}

typedef CUresult (*EncodeFn)(CUtensorMap*, CUtensorMapDataType, cuuint32_t, void*, const cuuint64_t*, const cuuint64_t*, const cuuint32_t*,
                             const cuuint32_t*, CUtensorMapInterleave, CUtensorMapSwizzle, CUtensorMapL2promotion, CUtensorMapFloatOOBfill);

bool encode(EncodeFn fn, CUtensorMap* m, const void* ptr, int rank, const cuuint64_t* dims, const cuuint64_t* strides, const cuuint32_t* box,
            CUtensorMapL2promotion promo = CU_TENSOR_MAP_L2_PROMOTION_NONE) {
    const cuuint32_t es[5] = {1, 1, 1, 1, 1};
    return fn(m, CU_TENSOR_MAP_DATA_TYPE_BFLOAT16, rank, const_cast<void*>(ptr), dims, strides, box, es, CU_TENSOR_MAP_INTERLEAVE_NONE,
              CU_TENSOR_MAP_SWIZZLE_128B, promo, CU_TENSOR_MAP_FLOAT_OOB_FILL_NONE) == CUDA_SUCCESS;
}

}

extern "C" void kernel_launch(void* const* d_in, const int* in_sizes, int n_in, void* d_out, int out_size) {
    (void)in_sizes; (void)n_in; (void)out_size;
    Params prm;
    prm.x = (const __nv_bfloat16*)d_in[0];
    prm.lam_re = (const __nv_bfloat16*)d_in[1];
    prm.lam_im = (const __nv_bfloat16*)d_in[2];
    prm.b_re = (const __nv_bfloat16*)d_in[3];
    prm.b_im = (const __nv_bfloat16*)d_in[4];
    prm.c_re = (const __nv_bfloat16*)d_in[5];
    prm.c_im = (const __nv_bfloat16*)d_in[6];
    prm.log_dt = (const __nv_bfloat16*)d_in[7];
    prm.dskip = (const __nv_bfloat16*)d_in[8];
    prm.w_r = (const __nv_bfloat16*)d_in[10];
    prm.gate_w = (const __nv_bfloat16*)d_in[14];
    prm.out = (float*)d_out;
    cudaGetSymbolAddress((void**)&prm.s, g_scratch);
    prm.swapped = prm.b_im < prm.b_re;

    void* fnp = nullptr;
    cudaDriverEntryPointQueryResult qr;
    cudaGetDriverEntryPoint("cuTensorMapEncodeTiled", &fnp, cudaEnableDefault, &qr);
    EncodeFn fn = (EncodeFn)fnp;
    cudaFuncSetAttribute(fused_kernel, cudaFuncAttributeMaxDynamicSharedMemorySize, SMEM_BYTES);

    CUtensorMap mX, mB, mCre, mCim, mWg, mWu, mWd, mXr, mPB, mPC, mXe;
    const cuuint64_t row = 2048;
    {
        const cuuint64_t dims[4] = {1024, 2, 4, 976}, st[3] = {row, 32 * row, 2 * row};
        const cuuint32_t box[4] = {64, 2, 4, 16};
        encode(fn, &mX, prm.x, 4, dims, st, box, PROMO);
    }
    {
        const char *lo = (const char*)(prm.swapped ? prm.b_im : prm.b_re), *hi = (const char*)(prm.swapped ? prm.b_re : prm.b_im);
        const cuuint64_t dims[5] = {1024, 8, 2, 96, 2}, st[4] = {row, (cuuint64_t)(hi - lo), 8 * row, 256 * row};
        const cuuint32_t box[5] = {64, 8, 2, 4, 2};
        encode(fn, &mB, lo, 5, dims, st, box, PROMO);
    }
    {
        const cuuint64_t dims[5] = {1024, 2, 4, 2, 64}, st[4] = {row, 4 * row, 2 * row, 16 * row};
        const cuuint32_t box[5] = {64, 2, 4, 2, 8};
        encode(fn, &mCre, prm.c_re, 5, dims, st, box);
        encode(fn, &mCim, prm.c_im, 5, dims, st, box);
    }
    {
        const cuuint64_t dims[2] = {F_, D_}, st[1] = {F_ * 2}, dimsd[2] = {D_, F_}, std_[1] = {row};
        const cuuint32_t box[2] = {64, 64};
        encode(fn, &mWg, d_in[11], 2, dims, st, box);
        encode(fn, &mWu, d_in[12], 2, dims, st, box);
        encode(fn, &mWd, d_in[13], 2, dimsd, std_, box);
    }
    for (int i = 0; i < 2; i++) {
        const char *p = (const char*)(i ? prm.c_re : prm.b_re), *q = (const char*)(i ? prm.c_im : prm.b_im);
        const cuuint64_t dims[4] = {64, 16, 1024, 2}, st[3] = {128, row, (cuuint64_t)(p < q ? q - p : p - q)};
        const cuuint32_t box[4] = {16, 4, 4, 2};
        encode(fn, i ? &mPC : &mPB, p < q ? p : q, 4, dims, st, box, CU_TENSOR_MAP_L2_PROMOTION_L2_128B);
    }
    {
        const cuuint64_t dims[3] = {D_ - 192, S_, 4}, st[2] = {row, 128};
        const cuuint32_t box[3] = {64, 16, 4};
        encode(fn, &mXr, prm.x, 3, dims, st, box);
    }
    {
        const cuuint64_t dims[5] = {1024, 2, 4, 4, S_ / 32}, st[4] = {4 * row, row, 8 * row, 32 * row};
        const cuuint32_t box[5] = {64, 2, 4, 2, 4};
        encode(fn, &mXe, prm.x, 5, dims, st, box);
    }
    for (int j = 0, e4 = 4 * TN(GC0); j < 23; j++) {
        prm.fetch[j] = j < NFT ? TN(GU_E0) + j * TN(W_NUM) / 4 : j < 16 ? 0 : TN(DL0) + (j - 16) * TN(DLS) / 4;
        prm.use[j] = j < 16 ? e4 / 4 : TN(DC0) + (j - 16) * TN(DCS) / 4;
        const int last = j < 19 ? 54 : 55;
        if (prm.fetch[j] > last) prm.fetch[j] = last;
        if (prm.use[j] > last) prm.use[j] = last;
        e4 += j < TN(N1) ? TN(GCS) : j < TN(N2) ? TN(GCS2) : j < 10 ? TN(GCS3) : TN(GCS4);
    }
    fused_kernel<<<NCTA, 512, SMEM_BYTES, cudaStreamPerThread>>>(mX, mB, mCre, mCim, mWg, mWu, mWd, mXr, mPB, mPC, mXe, prm);
}
```

```cpp
#include <cuda_runtime.h>
#include <cuda_bf16.h>
#include <cuda.h>
#include <stdint.h>

namespace {

constexpr int S_ = 2048, D_ = 1024, F_ = 3584;
constexpr int NCTA = 128;
constexpr int NBIG = 56, NENT = 72;
constexpr int NST = 5;
constexpr int NFT = 5;
constexpr uint32_t SLOT = 32768, TILE = 8192;
constexpr uint32_t OFF_FT = NST * SLOT;
constexpr uint32_t OFF_XS = OFF_FT + NFT * TILE;
constexpr uint32_t OFF_LIST = OFF_XS + 8192;
constexpr uint32_t OFF_RED = OFF_XS + 4096;
constexpr uint32_t OFF_CONST = OFF_XS + 16384;
constexpr uint32_t OFF_M = OFF_CONST + 8192, OFF_ONE = OFF_M + 512;
constexpr uint32_t OFF_HID = OFF_CONST;
constexpr uint32_t OFF_G = OFF_ONE + 16;
constexpr uint32_t OFF_DK = OFF_G + 256;
constexpr uint32_t OFF_FULL = OFF_DK + 256;
constexpr uint32_t OFF_EMPTY = OFF_FULL + 102 * 8;
constexpr uint32_t OFF_KEYS = OFF_EMPTY + 86 * 8;
constexpr uint32_t OFF_SEL = OFF_KEYS + 32;
constexpr uint32_t OFF_EPOCH = OFF_SEL + 32;
constexpr uint32_t OFF_PROF = OFF_EPOCH + 16;
constexpr uint32_t SMEM_BYTES = OFF_PROF + 432;
static_assert(SMEM_BYTES <= 232448, "smem");

static_assert(NBIG % NST == 1, "tail layout");
__host__ __device__ constexpr uint32_t tail_c(int j) { return j < 6 ? 2 * SLOT + j * 2 * TILE : (j - 6) * 2 * TILE; }
__host__ __device__ constexpr uint32_t tail_h(int n) { return n % 7 < 3 ? OFF_FT + n % 7 * TILE : SLOT + (n % 7 - 3) * TILE; }

constexpr uint32_t SPIN_LIMIT = 1u << 18;

struct Scratch {
    uint2 carry[16 * 1024];
    uint2 hid[NCTA * 128];
    uint32_t y[8 * 8 * D_];
    uint32_t key[NCTA * 8];
    uint32_t gate[S_];
    uint2 armed[NCTA * 4];
    unsigned int epoch[256];
    uint4 start[32 * 2];
    uint4 h[16 * 32 * 1024];
};
__device__ __align__(1024) Scratch g_scratch;
#define STAMPW_(cond, w) do {} while (0)
#define GSTAMP(cond, w) do {} while (0)
#define LSTAMP(cond, w) STAMPW_(cond, w)
#define STAMPW(cond, w) STAMPW_(cond, w)
#define STAMPIF(cond, i) STAMPW(cond, 96 + (i))
#define STAMP(i) STAMPW(1, 96 + (i))
#define KSTAMP(i) STAMPW((threadIdx.x & 127) == 0, i)
#define PSTAMP(i) STAMPW((i) < 56 && (i) >= 32, 160 + (i))

struct Params {
    const __nv_bfloat16 *x, *lam_re, *lam_im, *b_re, *b_im, *c_re, *c_im, *log_dt, *dskip, *w_r, *gate_w;
    float* out;
    Scratch* s;
    int fetch[23], use[23];
    int swapped;
};

__device__ __forceinline__ uint32_t smem_u32(const void* p) { return (uint32_t)__cvta_generic_to_shared(p); }
__device__ __forceinline__ void mbar_init(uint32_t bar, uint32_t cnt) { asm volatile("mbarrier.init.shared::cta.b64 [%0], %1;" ::"r"(bar), "r"(cnt) : "memory"); }
__device__ __forceinline__ void mbar_expect_tx(uint32_t bar, uint32_t bytes) { asm volatile("mbarrier.arrive.expect_tx.shared::cta.b64 _, [%0], %1;" ::"r"(bar), "r"(bytes) : "memory"); }
__device__ __forceinline__ void mbar_arrive(uint32_t bar) { asm volatile("mbarrier.arrive.shared::cta.b64 _, [%0];" ::"r"(bar) : "memory"); }
__device__ __forceinline__ bool mbar_try(uint32_t bar, uint32_t parity) {
    uint32_t ok;
    asm volatile("{ .reg .pred p; mbarrier.try_wait.parity.shared::cta.b64 p, [%1], %2; selp.u32 %0, 1, 0, p; }" : "=r"(ok) : "r"(bar), "r"(parity) : "memory");
    return ok;
}
__device__ __forceinline__ bool mbar_test(uint32_t bar, uint32_t parity) {
    uint32_t ok;
    asm volatile("{ .reg .pred p; mbarrier.test_wait.parity.shared::cta.b64 p, [%1], %2; selp.u32 %0, 1, 0, p; }" : "=r"(ok) : "r"(bar), "r"(parity) : "memory");
    return __all_sync(0xffffffffu, ok);
}
__device__ __forceinline__ void mbar_wait(uint32_t bar, uint32_t parity = 0) {
    if (mbar_try(bar, parity)) return;
#pragma unroll 1
    for (uint32_t it = 0; it < SPIN_LIMIT; ++it)
        if (mbar_try(bar, parity)) return;
    __trap();
}
__device__ __forceinline__ bool elect_one() {
    uint32_t pred;
    asm volatile("{ .reg .pred P; elect.sync _|P, 0xffffffff; selp.b32 %0, 1, 0, P; }" : "=r"(pred));
    return pred;
}
__device__ __forceinline__ void named_bar(int id, int n) { asm volatile("bar.sync %0, %1;" ::"r"(id), "r"(n) : "memory"); }
__device__ __forceinline__ void fence_mbar_init() { asm volatile("fence.mbarrier_init.release.cluster;" ::: "memory"); }
__device__ __forceinline__ void fence_async_smem() { asm volatile("fence.proxy.async.shared::cta;" ::: "memory"); }

__device__ __forceinline__ void bulk_load(uint32_t dst, const void* src, uint32_t bytes, uint32_t bar) {
    asm volatile("cp.async.bulk.shared::cluster.global.mbarrier::complete_tx::bytes [%0], [%1], %2, [%3];" ::"r"(dst), "l"(src), "r"(bytes), "r"(bar) : "memory");
}
__device__ __forceinline__ void cp_async16(uint32_t dst, const void* src) { asm volatile("cp.async.cg.shared.global [%0], [%1], 16;" ::"r"(dst), "l"(src) : "memory"); }
__device__ __forceinline__ void sts128(uint32_t a, uint32_t x, uint32_t y, uint32_t z, uint32_t w) {
    asm volatile("st.shared.v4.u32 [%0], {%1,%2,%3,%4};" ::"r"(a), "r"(x), "r"(y), "r"(z), "r"(w) : "memory");
}
__device__ __forceinline__ uint2 lds64(uint32_t a) {
    uint2 v;
    asm volatile("ld.shared.v2.u32 {%0,%1}, [%2];" : "=r"(v.x), "=r"(v.y) : "r"(a) : "memory");
    return v;
}
__device__ __forceinline__ uint32_t lds32(uint32_t a) {
    uint32_t v;
    asm volatile("ld.volatile.shared.u32 %0, [%1];" : "=r"(v) : "r"(a) : "memory");
    return v;
}
__device__ __forceinline__ void stg128(void* p, uint32_t x, uint32_t y, uint32_t z, uint32_t w) {
    asm volatile("st.global.v4.u32 [%0], {%1,%2,%3,%4};" ::"l"(p), "r"(x), "r"(y), "r"(z), "r"(w) : "memory");
}
__device__ __forceinline__ void st_relaxed(void* p, uint32_t x) { asm volatile("st.relaxed.gpu.global.b32 [%0], %1;" ::"l"(p), "r"(x) : "memory"); }
__device__ __forceinline__ void st_relaxed2(void* p, uint32_t x, uint32_t y) { asm volatile("st.relaxed.gpu.global.v2.b32 [%0], {%1, %2};" ::"l"(p), "r"(x), "r"(y) : "memory"); }
__device__ __forceinline__ void st_relaxed4(void* p, uint32_t x, uint32_t y, uint32_t z, uint32_t w) {
    asm volatile("st.relaxed.gpu.global.v4.b32 [%0], {%1, %2, %3, %4};" ::"l"(p), "r"(x), "r"(y), "r"(z), "r"(w) : "memory");
}
__device__ __forceinline__ uint32_t ld_relaxed(const void* p) {
    uint32_t v;
    asm volatile("ld.relaxed.gpu.global.b32 %0, [%1];" : "=r"(v) : "l"(p) : "memory");
    return v;
}
__device__ __forceinline__ uint2 ld_relaxed2(const void* p) {
    uint2 v;
    asm volatile("ld.relaxed.gpu.global.v2.b32 {%0, %1}, [%2];" : "=r"(v.x), "=r"(v.y) : "l"(p) : "memory");
    return v;
}
__device__ __forceinline__ uint4 ld_relaxed4(const void* p) {
    uint4 v;
    asm volatile("ld.relaxed.gpu.global.v4.b32 {%0, %1, %2, %3}, [%4];" : "=r"(v.x), "=r"(v.y), "=r"(v.z), "=r"(v.w) : "l"(p) : "memory");
    return v;
}
__device__ __forceinline__ uint32_t clk32() { uint32_t c; asm volatile("mov.u32 %0, %%clock;" : "=r"(c)); return c; }
__device__ __forceinline__ uint32_t gtime32() { uint32_t c; asm volatile("mov.u32 %0, %%globaltimer_lo;" : "=r"(c)); return c; }
__device__ __forceinline__ void sched_fence(uint32_t t) { while ((int)(clk32() - t) < 0) {} }
__device__ __forceinline__ void sleep_until(uint32_t t) { while ((int)(clk32() - t) < 0) __nanosleep(40); }

__device__ __forceinline__ void tma2(uint32_t dst, const CUtensorMap* m, int c0, int c1, uint32_t bar) {
    asm volatile("{ .reg .b64 pol; createpolicy.fractional.L2::evict_first.b64 pol;\n"
                 "cp.async.bulk.tensor.2d.shared::cluster.global.mbarrier::complete_tx::bytes.L2::cache_hint [%0], [%1, {%3, %4}], [%2], pol; }"
                 ::"r"(dst), "l"(m), "r"(bar), "r"(c0), "r"(c1) : "memory");
}
__device__ __forceinline__ void tma3(uint32_t dst, const CUtensorMap* m, int c0, int c1, uint32_t bar) {
    asm volatile("cp.async.bulk.tensor.3d.shared::cluster.global.mbarrier::complete_tx::bytes [%0], [%1, {%3, %4, %5}], [%2];"
                 ::"r"(dst), "l"(m), "r"(bar), "r"(c0), "r"(c1), "r"(0) : "memory");
}
__device__ __forceinline__ void tma4(uint32_t dst, const CUtensorMap* m, int c0, int c3, uint32_t bar) {
    asm volatile("cp.async.bulk.tensor.4d.shared::cluster.global.mbarrier::complete_tx::bytes [%0], [%1, {%3, %5, %5, %4}], [%2];"
                 ::"r"(dst), "l"(m), "r"(bar), "r"(c0), "r"(c3), "r"(0) : "memory");
}
__device__ __forceinline__ void tma5(uint32_t dst, const CUtensorMap* m, int c0, int c4, uint32_t bar) {
    asm volatile("cp.async.bulk.tensor.5d.shared::cluster.global.mbarrier::complete_tx::bytes [%0], [%1, {%3, %5, %5, %5, %4}], [%2];"
                 ::"r"(dst), "l"(m), "r"(bar), "r"(c0), "r"(c4), "r"(0) : "memory");
}
__device__ __forceinline__ void tma5b(uint32_t dst, const CUtensorMap* m, int c0, int c3, uint32_t bar) {
    asm volatile("cp.async.bulk.tensor.5d.shared::cluster.global.mbarrier::complete_tx::bytes [%0], [%1, {%3, %5, %5, %4, %5}], [%2];"
                 ::"r"(dst), "l"(m), "r"(bar), "r"(c0), "r"(c3), "r"(0) : "memory");
}
__device__ __forceinline__ void prefetch_l2(const void* p) { asm volatile("prefetch.global.L2 [%0];" ::"l"(p)); }
__device__ __forceinline__ void prefetch_slice(const CUtensorMap* m, int line, int row) {
    asm volatile("cp.async.bulk.prefetch.tensor.4d.L2.global [%0, {%3, %1, %2, %3}];" ::"l"(m), "r"(line), "r"(row), "r"(0) : "memory");
}
__device__ __forceinline__ void prefetch_map(const CUtensorMap* m) { asm volatile("prefetch.tensormap [%0];" ::"l"(m)); }
__device__ __forceinline__ uint32_t uni(uint32_t v) { return __shfl_sync(0xffffffffu, v, 0); }

__device__ __forceinline__ uint32_t make_desc(uint32_t addr) { return ((addr & 0x3FFFF) >> 4) | (1u << 16); }
__device__ __forceinline__ uint32_t make_desc_h(uint32_t addr) { return ((addr & 0x3FFFF) >> 4) | (32u << 16); }
template <int H> __device__ __forceinline__ uint64_t desc64(uint32_t lo) {
    uint64_t d;
    asm volatile("mov.b64 %0, {%1, %2};" : "=l"(d) : "r"(lo), "n"(64u | ((H ? 2u : 1u) << 30)));
    return d;
}
__device__ __forceinline__ void wgmma_fence() { asm volatile("wgmma.fence.sync.aligned;" ::: "memory"); }
__device__ __forceinline__ void wgmma_commit() { asm volatile("wgmma.commit_group.sync.aligned;" ::: "memory"); }
template <int N> __device__ __forceinline__ void wgmma_wait() { asm volatile("wgmma.wait_group.sync.aligned %0;" ::"n"(N) : "memory"); }

#define R8(d, i) "+f"(d[i]), "+f"(d[i + 1]), "+f"(d[i + 2]), "+f"(d[i + 3]), "+f"(d[i + 4]), "+f"(d[i + 5]), "+f"(d[i + 6]), "+f"(d[i + 7])
#define R64(d) R8(d, 0), R8(d, 8), R8(d, 16), R8(d, 24), R8(d, 32), R8(d, 40), R8(d, 48), R8(d, 56)
template <int TA>
__device__ __forceinline__ void wgmma_n128(float (&d)[64], uint64_t da, uint64_t db, int scale_d = 1) {
    asm volatile("{ .reg .pred p; setp.ne.b32 p, %66, 0;\n"
                 "wgmma.mma_async.sync.aligned.m64n128k16.f32.bf16.bf16 "
                 "{%0,%1,%2,%3,%4,%5,%6,%7,%8,%9,%10,%11,%12,%13,%14,%15,%16,%17,%18,%19,%20,%21,%22,%23,%24,%25,%26,%27,%28,%29,%30,%31,"
                 "%32,%33,%34,%35,%36,%37,%38,%39,%40,%41,%42,%43,%44,%45,%46,%47,%48,%49,%50,%51,%52,%53,%54,%55,%56,%57,%58,%59,%60,%61,%62,%63}, "
                 "%64, %65, p, 1, 1, %67, 0; }"
                 : R64(d)
                 : "l"(da), "l"(db), "r"(scale_d), "n"(TA));
}
__device__ __forceinline__ void pin4(float (&d)[4]) { asm volatile("" : "+f"(d[0]), "+f"(d[1]), "+f"(d[2]), "+f"(d[3])::"memory"); }
__device__ __forceinline__ void pin64(float (&d)[64]) { asm volatile("" : R64(d)::"memory"); }

template <int TA>
__device__ __forceinline__ void wgmma_n8(float (&d)[4], uint64_t da, uint64_t db, int scale_d = 1) {
    asm volatile("{ .reg .pred p; setp.ne.b32 p, %7, 0;\n"
                 "wgmma.mma_async.sync.aligned.m64n8k16.f32.bf16.bf16 {%0,%1,%2,%3}, %4, %5, p, 1, 1, %6, 0; }"
                 : "+f"(d[0]), "+f"(d[1]), "+f"(d[2]), "+f"(d[3])
                 : "l"(da), "l"(db), "n"(TA), "r"(scale_d));
}

__device__ __forceinline__ float bf_lo(uint32_t u) { return __uint_as_float(u << 16); }
__device__ __forceinline__ float bf_hi(uint32_t u) { return __uint_as_float(u & 0xFFFF0000u); }
__device__ __forceinline__ float rbf(float v) { return __bfloat162float(__float2bfloat16_rn(v)); }
__device__ __forceinline__ uint32_t pack_bf(float lo, float hi) {
    uint32_t r;
    asm("cvt.rn.bf16x2.f32 %0, %1, %2;" : "=r"(r) : "f"(hi), "f"(lo));
    return r;
}
__device__ __forceinline__ uint32_t mul_bf2(uint32_t a, uint32_t b) {
    uint32_t r;
    asm("mul.rn.bf16x2 %0, %1, %2;" : "=r"(r) : "r"(a), "r"(b));
    return r;
}
__device__ __forceinline__ uint32_t fma_bf2(uint32_t a, uint32_t b, uint32_t c) {
    uint32_t r;
    asm("fma.rn.bf16x2 %0, %1, %2, %3;" : "=r"(r) : "r"(a), "r"(b), "r"(c));
    return r;
}
__device__ __forceinline__ float2 cmul(float2 a, float2 b) { return make_float2(a.x * b.x - a.y * b.y, a.x * b.y + a.y * b.x); }
__device__ __forceinline__ float2 cfma(float2 a, float2 b, float2 c) {
    return make_float2(fmaf(a.x, b.x, fmaf(-a.y, b.y, c.x)), fmaf(a.x, b.y, fmaf(a.y, b.x, c.y)));
}
__device__ __forceinline__ float sigmoidf_(float v) { return __fdividef(1.0f, 1.0f + expf(-v)); }

#define SCHED_NAMES RT0, RT1, RT2, RT3, PF0, PF1, PF2, PF3, T_SMALL, T_INIT, T_X0, T_BASE, G_NS, GT0, GT1, GT2, G0, GAP0, GAP1, RS_E, \
    PB_E0, PB_STEP, PC_E0, PC_STEP, PC_N, PC_E1, PC_S1, GU_E0, W_NUM, GC0, N1, N2, GCS, GCS2, GCS3, GCS4, HG, DL0, DLS, DC0, DCS, DN_E0, WDBG, T_OWN, T_RETRY, NP, T_Y, T_FIL0, T_FILL
enum { SCHED_NAMES, NTUNE };
constexpr int sched_default[NTUNE] = {
    2500, 3000, 3500, 4000,
    0, 1100, 1300, 2800,
    400, 500, 1, 2500, 3,
    6700, 0, 0,
    1500, 50, 50, 4,
    4, 1, 9, 4, 5, 50, 3,
    4, 9, 15, 6, 6, 7, 7, 7, 5, 43, 37, 8, 38, 1, 50,
    0, 1100, 200, 0, 700, 0, 0};
template <int I> struct Sched { static constexpr int v = sched_default[I]; };
#define TN(i) (Sched<i>::v)
#define DBG 0
#define NKK 4
#define TDBG 0
#define X0 2
#define CH1 52
#define GE 8
#define DOUBLE 0
#define RAISE_J 1
#define GREEDY 0
#define POLL_S 24
#define PROMO CU_TENSOR_MAP_L2_PROMOTION_L2_256B

template <int TA, class H>
__device__ __forceinline__ void run_entry(uint32_t lo32, uint32_t prev, int accumulate, float (&accA)[64], float (&accB)[64], H inside) {
    const uint64_t da = desc64<TA>(lo32), db = TA ? desc64<0>(lo32 + (2 * TILE >> 4) - (31u << 16)) : da + (2 * TILE >> 4);
    wgmma_fence();
#pragma unroll
    for (int kk = 0; kk < 4; kk++) {
        wgmma_n128<TA>(accA, da + kk * (TA ? 128 : 2), db + kk * 2, kk > 0 ? 1 : accumulate);
        wgmma_n128<TA>(accB, da + 512 + kk * (TA ? 128 : 2), db + kk * 2, kk > 0 ? 1 : accumulate);
        if (kk == 1) {
            wgmma_commit();
            wgmma_wait<1>();
            if ((threadIdx.x & 31) == 0) mbar_arrive(prev);
            inside();
        }
    }
    wgmma_commit();
}
template <int TA, class H>
__device__ __forceinline__ void run_entries(uint32_t sb, int lo, int hi, int slot, float (&accA)[64], float (&accB)[64], H after) {
    const uint32_t da0 = TA ? make_desc_h(sb) : make_desc(sb), dlast = da0 + (NST - 1) * (SLOT >> 4);
    uint32_t prev = sb + OFF_FULL + 8 * 80, bar = sb + OFF_FULL + 8 * lo, lo32 = da0 + slot * (SLOT >> 4);
    int accumulate = 0;
#pragma unroll 1
    for (int i = lo; i < hi; i++) {
        mbar_wait(bar);
        KSTAMP(i);
        run_entry<TA>(lo32, prev, accumulate, accA, accB, []() {});
        prev = bar + (OFF_EMPTY - OFF_FULL);
        bar += 8;
        lo32 = lo32 == dlast ? da0 : lo32 + (SLOT >> 4);
        accumulate = 1;
        after(i);
    }
}

template <int TA>
__device__ __forceinline__ void small_tile(float (&acc)[4], uint32_t alo, uint32_t blo, bool first) {
    const uint64_t da = desc64<0>(alo), db = desc64<0>(blo);
#pragma unroll
    for (int kk = 0; kk < 4; kk++) wgmma_n8<TA>(acc, da + kk * (TA ? 128 : 2), db + kk * 2, kk > 0 || !first);
}

template <int N>
__device__ __forceinline__ uint32_t check_tile(uint32_t sb, uint32_t dst, uint32_t probe, const char* src, uint32_t par, uint32_t bar, uint32_t phase, uint32_t pause) {
    if ((TDBG & 4) && N == 8) return phase;
#pragma unroll 1
    for (uint32_t it = 0; it < SPIN_LIMIT; it++) {
        uint32_t v[N], bad = 0;
#pragma unroll
        for (int u = 0; u < N; u++) v[u] = lds32(dst + probe + (u >> 1) * 2048 + (u & 1) * 256);
#pragma unroll
        for (int u = 0; u < N; u += 4)
            asm("{ .reg .b32 a, b; lop3.b32 a, %1, %2, %5, 0x7E; lop3.b32 b, %3, %4, %5, 0x7E; lop3.b32 %0, %0, a, b, 0xFE; }"
                : "+r"(bad) : "r"(v[u]), "r"(v[u + 1]), "r"(v[u + 2]), "r"(v[u + 3]), "r"(par));
        if (!__any_sync(0xffffffffu, bad & 1u)) return phase;
        STAMP(10);
        __nanosleep(pause);
        if (elect_one()) {
            mbar_expect_tx(bar, N * 1024);
            bulk_load(dst, src, N * 1024, bar);
        }
        mbar_wait(bar, phase);
        phase ^= 1;
    }
    __trap();
    return 0;
}

__global__ void __launch_bounds__(512, 1)
fused_kernel(const __grid_constant__ CUtensorMap mX, const __grid_constant__ CUtensorMap mB, const __grid_constant__ CUtensorMap mCre,
             const __grid_constant__ CUtensorMap mCim, const __grid_constant__ CUtensorMap mWg, const __grid_constant__ CUtensorMap mWu,
             const __grid_constant__ CUtensorMap mWd, const __grid_constant__ CUtensorMap mXr, const __grid_constant__ CUtensorMap mPB,
             const __grid_constant__ CUtensorMap mPC, const __grid_constant__ CUtensorMap mXe, const __grid_constant__ Params prm) {
    extern __shared__ __align__(1024) uint8_t smem[];
    uint32_t sb;
    asm volatile("mov.u32 %0, %1;" : "=r"(sb) : "r"(smem_u32(smem)));
    const int tid = threadIdx.x, warp = __shfl_sync(0xffffffffu, tid >> 5, 0), lane = tid & 31;
    const int cta = blockIdx.x;
    const uint32_t cstart = clk32();
    const int chunk = (cta >> 2) & 15;
    const int dt = (cta >> 6) * 4 + (cta & 3);
    const int rid = chunk * 8 + dt;
    const bool has_gu = cta < 112;
    const uint32_t full = sb + OFF_FULL, empty = sb + OFF_EMPTY;
    const uint32_t ffull = full + 8 * 85, fempty = empty + 8 * 65;
    const uint32_t bar_epoch = full + 8 * 72, dfull = full + 8 * 73, bar_base = full + 8 * 82, bar_x = full + 8 * 83, bar_retry = full + 8 * 81, hfull = full + 8 * 90;
    const uint32_t bar_order = empty + 8 * 70, bar_const = empty + 8 * 85, bar_stored = empty + 8 * 72, bar_dfree = empty + 8 * 73,
                    bar_g = empty + 8 * 84, bar_out = empty + 8 * 76;
    const int w = warp & 3, g = lane >> 2, c = lane & 3, at = tid & 127;

    const uint32_t probe = (lane >> 3) * 32 + (g & 1) * 144 + (c & 1) * 520 + (c >> 1) * 1028;

    LSTAMP(tid == 0, 96);
    GSTAMP(tid == 0, 94);
    auto init_barriers = [&]() {
        if (elect_one()) {
            const uint32_t base = warp < 6 ? full + min(8 * NST + 136 * warp, 8 * 85) : empty + min(136 * (warp - 6), 8 * 69), cnt = warp < 6 ? 1 : 4;
#pragma unroll
            for (int i = 0; i < 17; i++) mbar_init(base + 8 * i, cnt);
            fence_mbar_init();
        }
        __syncwarp();
    };
    if (warp != 12) {
        if (warp >= 14) {
            const int r = cta * 8 + g;
            if (warp == 15 && !(cta & 3) && lane < 8) st_relaxed((uint32_t*)&prm.s->start[cta >> 1] + lane, (lane & 1) ? gtime32() : cstart);
            prefetch_l2(warp == 14 ? (const char*)prm.x + (rid * 16 + (lane >> 1)) * 2048 + (c & 1 & TN(T_X0)) * 128
                                   : (const char*)((r & 512) ? prm.b_im : prm.b_re) + (r & 511) * 2048 + (c & TN(T_X0)) * 128);
        }
        sleep_until(cstart + (warp == 13 ? TN(T_SMALL) : TN(T_INIT)));
    }
    if (warp < 8) {
        init_barriers();
        asm volatile("setmaxnreg.inc.sync.aligned.u32 192;");
        named_bar(0, 480);
        STAMPIF(tid == 0 && lds32(sb + OFF_KEYS + 16) == 0, 8);
        const int wg = warp >> 2;
        const int p = wg * 512 + dt * 32 + w * 8 + g;
        uint32_t cp = sb + OFF_CONST + 8 * (wg * 64 + w * 8 + g), cw = cp + 1024 * c, cm = sb + OFF_M + 4 * (wg * 64 + w * 8 + g);
        const int j1 = chunk - 1 - c;
        uint2* cq = &prm.s->carry[j1 * 1024 + p];
        char* hd = reinterpret_cast<char*>(prm.s->h) + (size_t)chunk * 524288 + wg * 262144 + (dt >> 1) * 16384 + ((dt & 1) * 4 + w) * 1024 + g * 64 + ((c ^ (g >> 1)) << 4);
        const bool never = uni(cstart == 0 && sb == 0);
        asm volatile("" : "+l"(cq), "+l"(hd), "+r"(cp), "+r"(cw), "+r"(cm));
        float2 a[2], a32[2], a64[2], a512[2], pw32[2], pw128[2];
        uint32_t mm[2], t2, par;
        auto constants = [&](int h) {
            if (h) { t2 = lds32(sb + OFF_EPOCH + 4); par = lds32(sb + OFF_EPOCH); }
            auto ldc = [](uint32_t a) { const uint2 v = lds64(a); return make_float2(__uint_as_float(v.x), __uint_as_float(v.y)); };
            {
                a[h] = ldc(cp + 256 * h); a32[h] = ldc(cp + 256 * h + 1024); a64[h] = ldc(cp + 256 * h + 2048); a512[h] = ldc(cp + 256 * h + 7168);
                pw32[h] = ldc(cw + 256 * h);
                pw128[h] = ldc(cw + 256 * h + 3072);
                mm[h] = lds32(cm + 128 * h);
            }
        };
        if (wg == 1) {
            const int pc = w * 256 + dt * 32 + lane;
            const float lr = __bfloat162float(prm.lam_re[pc]), li = __bfloat162float(prm.lam_im[pc]), ld = __bfloat162float(prm.log_dt[pc]);
            const uint32_t dk = __ldg(reinterpret_cast<const uint32_t*>(prm.dskip + dt * 128) + (at & 63));
            reinterpret_cast<uint32_t*>(smem + OFF_DK)[at & 63] = dk;
            const float dtv = rbf(expf(ld));
            const float er = expf(dtv * lr);
            float sn, cs;
            sincosf(dtv * li, &sn, &cs);
            const float ar = er * cs, ai = er * sn;
            const float nr = ar - 1.0f, ni = ai;
            const bool big = fabsf(lr) >= fabsf(li);
            const float t = (big ? li : lr) / (big ? lr : li), dn = big ? lr + li * t : lr * t + li;
            const float cr = (big ? nr + ni * t : nr * t + ni) / dn, ci = (big ? ni - nr * t : ni * t - nr) / dn;
            float2* ct = reinterpret_cast<float2*>(smem + OFF_CONST) + at;
            float2 pw = make_float2(ar, prm.swapped ? -ai : ai);
            ct[0] = pw;
            const float mx = prm.swapped ? -2.f * ci : 2.f * cr, my = prm.swapped ? 2.f * cr : -2.f * ci;
            reinterpret_cast<uint32_t*>(smem + OFF_M)[at] = pack_bf(mx, my);
#pragma unroll
            for (int i = 0; i < 5; i++) pw = cmul(pw, pw);
#pragma unroll
            for (int i = 0; i < 2; i++) {
                const float2 p2 = cmul(pw, pw);
                ct[128 + 384 * i] = pw; ct[256 + 384 * i] = p2; ct[384 + 384 * i] = cmul(p2, pw);
                pw = cmul(p2, p2);
            }
            ct[896] = pw;
            mbar_wait(bar_epoch);
            __syncwarp();
            mbar_wait(empty + 8 * TN(RS_E));
            st_relaxed2(&prm.s->hid[cta * 128 + at], ~0u, ~0u);
            st_relaxed4(&prm.s->y[((at >> 4) * 8 + (cta >> 4)) * D_ + (cta & 15) * 64 + (at & 15) * 4], 0u, 0u, 0u, 0u);
            st_relaxed2(&prm.s->carry[chunk * 1024 + pc], 0u, 0u);
            __syncwarp();
            if (lane == 0) mbar_arrive(bar_const);

            STAMPIF(at == 0, 3);
            mbar_wait(bar_order);
        }

        float accA[64], accB[64];
        run_entries<0>(sb, wg * 16, wg * 16 + 15, wg, accA, accB, [&](int i) {
            if (i == GE - 1) {
                mbar_wait(bar_base);
                sched_fence(lds32(sb + OFF_EPOCH + 8) + TN(GT0));
            }
        });
        mbar_wait(bar_const);
        mbar_wait(full + 8 * (wg * 16 + 15));
        KSTAMP(wg * 16 + 15);
        run_entry<0>(make_desc(sb + wg * SLOT), empty + 8 * (wg * 16 + 14), 1, accA, accB, [&]() { constants(0); constants(1); });
        if (lane == 0) mbar_arrive(bar_order + 8 * wg);
        uint2 v[2][4];
#pragma unroll
        for (int m = 0; m < 8; m++) v[m >> 2][m & 3] = make_uint2(t2, t2);
        wgmma_wait<0>();
        pin64(accA); pin64(accB);
        if (lane == 0) mbar_arrive(empty + 8 * (wg * 16 + 15));
        LSTAMP(at == 0, 96 + 30 + 10 * wg);

        auto cut = [&]() { if (never) sched_fence(cstart); };
        auto poll = [&](uint2 (&u)[4], int h) {
#pragma unroll
            for (int m = 0; m < 4; m++)
                asm volatile("{ .reg .pred p; setp.ge.s32 p, %3, %4; @p ld.relaxed.gpu.global.v2.b32 {%0, %1}, [%2]; }"
                             : "+r"(u[m].x), "+r"(u[m].y) : "l"(cq + 256 * h - 4096 * m), "r"(j1), "r"(4 * m) : "memory");
        };
        auto check = [&](const uint2 (&u)[4]) {
            uint32_t bad = 0;
#pragma unroll
            for (int m = 0; m < 4; m++) bad |= (u[m].x ^ t2) | (u[m].y ^ t2);
            return bad;
        };
        auto valid = [&](const uint2 (&u)[4]) { return __all_sync(0xffffffffu, (check(u) & 3u) == 0); };

        auto horner = [&](const uint2 (&u)[4], int h) {
            float2 r = make_float2(__uint_as_float(u[3].x), __uint_as_float(u[3].y));
#pragma unroll
            for (int m = 2; m >= 0; m--) r = cfma(a512[h], r, make_float2(__uint_as_float(u[m].x), __uint_as_float(u[m].y)));
            return r;
        };
        float2 w0[2];
#pragma unroll
        for (int h = 0; h < 2; h++) {
            float (&acc)[64] = h ? accB : accA;
            float2 e = make_float2(acc[0], acc[2]);
#pragma unroll
            for (int s = 1; s < 32; s++) {
                const int i0 = 4 * (s >> 1) + (s & 1);
                e = cfma(a[h], e, make_float2(acc[i0], acc[i0 + 2]));
                if (!GREEDY && h == 1 && s == POLL_S) { cut(); poll(v[0], 0); }
            }
            float2 y = make_float2(__shfl_up_sync(0xffffffffu, e.x, 1, 4), __shfl_up_sync(0xffffffffu, e.y, 1, 4));
            if (c >= 1) e = cfma(a32[h], y, e);
            y = make_float2(__shfl_up_sync(0xffffffffu, e.x, 2, 4), __shfl_up_sync(0xffffffffu, e.y, 2, 4));
            if (c >= 2) e = cfma(a64[h], y, e);
            if (c == 3) st_relaxed2(cq + 4096 + 256 * h, (__float_as_uint(e.x) & ~3u) | t2, (__float_as_uint(e.y) & ~3u) | t2);
            if (h || !GREEDY) cut();
            w0[h] = make_float2(__shfl_up_sync(0xffffffffu, e.x, 1, 4), __shfl_up_sync(0xffffffffu, e.y, 1, 4));
            STAMPIF(at == 0 && (h || !GREEDY), 31 + h + 10 * wg);
        }
        if (GREEDY) { __nanosleep(100); poll(v[0], 0); __nanosleep(100); }
        uint32_t sx[2][16], sy[2][16], mr[2][4], tp;
        const uint32_t gap = wg ? TN(GAP1) : TN(GAP0);
#pragma unroll
        for (int h = 0; h < 2; h++) {
            const uint32_t sg = prm.swapped ? 0x80008000u : 0u;
            mr[h][0] = __byte_perm(mm[h], 0, 0x1010); mr[h][1] = __byte_perm(mm[h], 0, 0x3232);
            mr[h][2] = mr[h][1] ^ sg; mr[h][3] = mr[h][0] ^ sg ^ 0x80008000u;
        }
        auto put = [&](int e, int j) {
            uint32_t d[4];
#pragma unroll
            for (int u = 0; u < 4; u++) d[u] = fma_bf2(mr[e >> 1][2 * (e & 1)], sx[e >> 1][4 * j + u], mul_bf2(mr[e >> 1][2 * (e & 1) + 1], sy[e >> 1][4 * j + u]));
            #pragma unroll
            for (int u = 0; u < 2; u++)
                asm("lop3.b32 %0, %0, %1, %2, 0xD8;" : "+r"(d[2 * (j & 1) + u]) : "r"(par), "r"((uint32_t)((w & 1) == u)));
            stg128(hd + e * 65536 + (j >> 1) * 8192 + (j & 1) * 512, d[0], d[1], d[2], d[3]);
            if (j == 3 && lane == 0) mbar_arrive(bar_out + 32 * wg + 8 * e);
        };
#pragma unroll
        for (int h = 0; h < 2; h++) {
            float (&acc)[64] = h ? accB : accA;
            float2 hin;
            uint32_t it = 0;
            if (h == 0 && DOUBLE) {
                while (true) {
                    poll(v[1], 0);
                    if (valid(v[0])) { hin = horner(v[0], 0); break; }
                    poll(v[0], 0);
                    if (valid(v[1])) { hin = horner(v[1], 0); it++; break; }
                    if (++it > SPIN_LIMIT) __trap();
                }
            } else {
                while (!valid(v[0])) {
                    poll(v[0], h);
                    if (++it > SPIN_LIMIT) __trap();
                }
                hin = horner(v[0], h);
            }
            STAMPIF(at == 0 && it > 0 && h == 0, 39 + 10 * wg);
            if (c) hin = cmul(pw128[h], hin);
            hin.x += __shfl_xor_sync(0xffffffffu, hin.x, 1); hin.y += __shfl_xor_sync(0xffffffffu, hin.y, 1);
            hin.x += __shfl_xor_sync(0xffffffffu, hin.x, 2); hin.y += __shfl_xor_sync(0xffffffffu, hin.y, 2);
            float2 st = hin;
            if (c) st = cfma(pw32[h], hin, w0[h]);
            STAMPIF(at == 0, 33 + 3 * h + 10 * wg);
#pragma unroll
            for (int j = 0; j < 4; j++) {
#pragma unroll
                for (int u = 0; u < 4; u++) {
                    const int i0 = 16 * j + 4 * u;
                    const float2 y = cfma(a[h], st, make_float2(acc[i0], acc[i0 + 2]));
                    st = cfma(a[h], y, make_float2(acc[i0 + 1], acc[i0 + 3]));
                    sx[h][4 * j + u] = pack_bf(y.x, st.x); sy[h][4 * j + u] = pack_bf(y.y, st.y);
                }
                if (h) sleep_until(tp += gap);
                if (h == 0 && j == RAISE_J) poll(v[0], 1);
                put(2 * h, j);
                cut();
            }
            STAMPIF(at == 0, 34 + 3 * h + 10 * wg);
            tp = clk32();
#pragma unroll
            for (int j = 0; j < 4; j++) {
                sleep_until(tp += gap);
                put(2 * h + 1, j);
            }
        }
        STAMPIF(at == 0, 38 + 10 * wg);

        if (wg == 1) {
            const char* src = reinterpret_cast<const char*>(prm.s->h) + (size_t)chunk * 524288;
            uint32_t rpar = 1;
#pragma unroll 1
            for (int i = CH1 + w; i < NBIG; i += 4) {
                const uint32_t slot = i % NST;
                mbar_wait(empty + 8 * (i - NST));
                mbar_wait(hfull + 8 * slot, (i - 32) / NST & 1);
                rpar = check_tile<16>(sb, sb + slot * SLOT, probe, src + (i - 32) * 2 * TILE, par, full + 8 * w, rpar, TN(T_RETRY));
                if (lane == 0) mbar_expect_tx(full + 8 * i, 2 * TILE);
            }
#pragma unroll 1
            for (int n = w; n < 16; n += 4) {
                mbar_wait(empty + 8 * (NBIG - 7 + n));
                mbar_wait(hfull + 8 * (NST + n % 7), n / 7 & 1);
                const uint32_t dst = sb + tail_h(n);
                rpar = check_tile<8>(sb, dst, probe, src + (24 + (n & 7)) * 2 * TILE + (n >> 3) * TILE, par, full + 8 * w, rpar, TN(T_RETRY));
                if (lane == 0) mbar_expect_tx(full + 8 * (NBIG + n), n < 8 ? 2 * TILE : 0);
            }
        } else {
            asm volatile("setmaxnreg.inc.sync.aligned.u32 216;");
            const int tl = 64 * (w & 1) + 8 * (w >> 1) + g;
            float gf[4];
            float* op = prm.out + (size_t)(chunk * 128 + tl) * D_ + dt * 128 + 4 * c;
            const int xr = 2 * (g & 3) + (g >> 2);
            uint32_t xs = sb + OFF_FT + 3 * TILE + (32 * (w & 1) + 8 * (w >> 1) + xr) * 128 + (((c >> 1) ^ xr) << 4) + (c & 1) * 8;
            uint32_t gs = sb + OFF_G + 2 * tl;
            asm volatile("" : "+r"(gs), "+l"(op), "+r"(xs));
            float outA[64], outB[64];
            STAMPIF(at == 0, 9);
            mbar_wait(bar_order + 8);
            STAMPIF(at == 0, 35);
            if (TN(GT2)) sched_fence(lds32(sb + OFF_EPOCH + 8) + TN(GT2));
            run_entries<1>(sb, 32, NBIG, 32 % NST, outA, outB, [](int) {});
            uint32_t gp[4], om[4];
            uint2 xt[4][8], dk[8];
            auto load_x = [&](int q, int j) {
#pragma unroll
                for (int r = 0; r < 2; r++) xt[2 * q + r][j] = lds64((xs ^ ((j & 3) << 5)) + (2 * q + (j >> 2)) * TILE + r * 2048);
                if (q == 0) dk[j] = lds64(sb + OFF_DK + c * 8 + 32 * j);
            };
            auto term = [&](int q, int j) {
#pragma unroll
                for (int r = 2 * q; r < 2 * q + 2; r++) {
                    xt[r][j].x = mul_bf2(xt[r][j].x, fma_bf2(gp[r], dk[j].x, om[r]));
                    xt[r][j].y = mul_bf2(xt[r][j].y, fma_bf2(gp[r], dk[j].y, om[r]));
                }
            };
            auto store = [&](int q, int j) {
                const float (&acc)[64] = q ? outB : outA;
#pragma unroll
                for (int r = 0; r < 2; r++) {
                    const int o = 8 * j + 2 * r;
                    const float gv = fabsf(gf[2 * q + r]);
                    const uint2 t = xt[2 * q + r][j];
                    stg128(op + (r * 32 + q * 16) * D_ + 16 * j, __float_as_uint(fmaf(gv, acc[o], bf_lo(t.x))), __float_as_uint(fmaf(gv, acc[o + 1], bf_hi(t.x))),
                           __float_as_uint(fmaf(gv, acc[o + 4], bf_lo(t.y))), __float_as_uint(fmaf(gv, acc[o + 5], bf_hi(t.y))));
                }
            };
            uint64_t dh = desc64<1>(make_desc_h(sb)), dc = desc64<0>(make_desc(sb));
#pragma unroll
            for (int n = 0; n < 16; n++) {
                const int j = n & 7;
                if (n == 0) mbar_wait(bar_g);
                if (n == X0 || n == 15) mbar_wait(bar_x + (n == 15 ? 8 : 0));
                mbar_wait(full + 8 * (NBIG + n));
                KSTAMP(NBIG + n);
                asm volatile("mov.b64 %0, %0; mov.b64 %1, %1;" : "+l"(dh), "+l"(dc));
                const uint64_t da = dh + (tail_h(n) >> 4), db = dc + (tail_c(j) >> 4);
                const int xj = n - X0;
                wgmma_fence();
#pragma unroll
                for (int kk = 0; kk < 4; kk++) {
                    wgmma_n128<1>(n < 8 ? outA : outB, da + kk * 128, db + kk * 2);
                    if (kk == 0 && n == 0) {
#pragma unroll
                        for (int r = 0; r < 4; r++) {
                            uint32_t u;
                            asm volatile("ld.shared.u16 %0, [%1];" : "=r"(u) : "r"(gs + (r & 1) * 64 + (r >> 1) * 32) : "memory");
                            gf[r] = bf_lo(u);
                        }
                    }
                    if (kk == 0 && xj >= 0 && xj < 8) load_x(0, xj);
                    if (kk == 0 && n == 15) load_x(1, 0);
                }
                wgmma_commit();
                if (n < 10) {
                    wgmma_wait<1>();
                    if (lane == 0) mbar_arrive(empty + 8 * (NBIG + n - 1));
                    if (!(n & 7)) LSTAMP(at == 0, 96 + 12 + n / 8);
                } else cut();
                if (n == 0) {
#pragma unroll
                    for (int r = 0; r < 4; r++) {
                        const bool routed = (int)__float_as_uint(gf[r]) < 0;
                        gp[r] = routed ? 0u : pack_bf(gf[r], gf[r]); om[r] = routed ? 0u : pack_bf(1.0f - gf[r], 1.0f - gf[r]);
                    }
                }
                if (xj >= 0 && xj < 8) term(0, xj);
                if (n == 8) pin64(outA);
                if (n >= 8) store(0, j);
            }
            term(1, 0);
            cut();
            wgmma_wait<0>();
            pin64(outB);
            LSTAMP(at == 0, 96 + 51);
#pragma unroll
            for (int j = 1; j < 8; j++) load_x(1, j);
            store(1, 0);
#pragma unroll
            for (int j = 1; j < 8; j++) {
                cut();
                term(1, j);
                store(1, j);
            }
            __syncwarp();
            if (lane == 0) mbar_arrive(bar_stored);
            LSTAMP(at == 0, 96 + 52);
        }
    } else if (warp < 12) {
        asm volatile("setmaxnreg.dec.sync.aligned.u32 64;");
        init_barriers();
#pragma unroll
        for (int i = 0; i < 2; i++) sts128(sb + OFF_LIST + i * 2048 + at * 16, 0u, 0u, 0u, 0u);
        uint32_t* keys = reinterpret_cast<uint32_t*>(smem + OFF_KEYS);
        keys[4] = 0;
        named_bar(0, 480);
        mbar_wait(bar_epoch);
        const uint32_t t2 = lds32(sb + OFF_EPOCH + 4);
        STAMPIF(at == 0, 20);
        float facc[4];
        const uint32_t dft = make_desc(sb + OFF_FT), dxs = make_desc(sb + OFF_XS);
#pragma unroll 1
        for (int u = 0; u < 4; u++) {
            mbar_wait(ffull + 8 * u);
            STAMPIF(at == 0, 4 + u);
            wgmma_fence();
            small_tile<0>(facc, dft + u * (TILE >> 4), dxs + u * 64, u == 0);
            wgmma_commit();
        }
        wgmma_wait<0>();
        pin4(facc);
        if (lane < 4) mbar_arrive(fempty + 8 * lane);
        auto gate_up = [&](auto rest) {
            uint32_t slot = 4, par = 0, prev = full + 8 * 80;
#pragma unroll 1
            for (int j = 0; j < 16; j++) {
                if (j == 2) rest();
                STAMPW(at == 0, 74 + j);
                mbar_wait(ffull + 8 * slot, par);
                STAMPW(at == 0, 160 + j);
                mbar_wait(empty + 8 * prm.use[j]);
                wgmma_fence();
                small_tile<1>(facc, dft + slot * (TILE >> 4), dxs + j * 64, j == 0);
                wgmma_commit();
                if (j < TN(NP)) { wgmma_wait<0>(); prev = fempty + 8 * slot; }
                else wgmma_wait<1>();
                if (lane == 0) mbar_arrive(prev);
                prev = j < TN(NP) ? full + 8 * 80 : fempty + 8 * slot;
                if (++slot == NFT) { slot = 0; par ^= 1; }
            }
            wgmma_wait<0>();
            if (lane == 0) mbar_arrive(prev);
            pin4(facc);
        };
        auto down = [&]() {
            const uint32_t dhid = make_desc(sb + OFF_HID);
#pragma unroll 1
            for (int j = 0; j < 7; j++) {
                mbar_wait(dfull + 8 * j);
                mbar_wait(empty + 8 * prm.use[16 + j]);
                wgmma_fence();
                small_tile<1>(facc, dft + j * (TILE >> 4), dhid + j * 64, j == 0);
                wgmma_commit();
                if (j && !(j & 1)) {
                    wgmma_wait<0>();
                    if (lane == 0) mbar_arrive(bar_dfree + 4 * j - 8);
                }
            }
            wgmma_wait<0>();
            pin4(facc);
        };
        if ((c & 1) == (w >> 1)) {
            float* red = reinterpret_cast<float*>(smem + OFF_RED) + w * 32 + (c >> 1) * 16 + g;
            red[0] = (w & 1) ? facc[1] : facc[0];
            red[8] = (w & 1) ? facc[3] : facc[2];
        }
        named_bar(2, 128);
        STAMPIF(at == 0, 21);
        const uint32_t tpub = clk32();
        if (w < 2) {
            const float* red = reinterpret_cast<const float*>(smem + OFF_RED) + w * 16 + (lane & 15);
            const float v = rbf((red[0] + red[32]) + (red[64] + red[96]));
            if (w == 0) {
                uint32_t k = __float_as_uint(v);
                k = ((k ^ ((uint32_t)((int)k >> 31) | 0x80000000u)) & 0xFFFF0000u) | (t2 << 11) | (2047u - (uint32_t)(rid * 16 + (lane & 15)));
                int rank = 0;
#pragma unroll
                for (int i = 0; i < 8; i++) rank += __shfl_sync(0xffffffffu, k, (lane >> 4) * 8 + i) > k;
                rank += __shfl_xor_sync(0xffffffffu, rank, 16);
                if (rank < 8) st_relaxed(&prm.s->key[cta * 8 + rank], k);
            } else if (lane < 16) st_relaxed(&prm.s->gate[rid * 16 + lane], __float_as_uint(rbf(sigmoidf_(v))) | t2);
            __syncwarp();
        }
        uint32_t it = 0;
        uint4 ka, kb4;
        sleep_until(tpub + TN(G0));
        while (true) {
            ka = ld_relaxed4(&prm.s->key[at * 8]);
            kb4 = ld_relaxed4(&prm.s->key[at * 8 + 4]);
            if (__all_sync(0xffffffffu, (((ka.x ^ (t2 << 11)) | (kb4.x ^ (t2 << 11))) & 0x1800u) == 0)) break;
            if (++it > SPIN_LIMIT) __trap();
        }
        STAMPIF(at == 0, 22);
        STAMPIF(at == 0 && it > 0, 23);
        const uint32_t m1 = __reduce_max_sync(0xffffffffu, ka.x), m2 = __reduce_max_sync(0xffffffffu, ka.x == m1 ? ka.y : ka.x);
        if (lane == 0) keys[w] = m2;
        named_bar(2, 128);
        const uint4 th4 = *reinterpret_cast<const uint4*>(keys);
        const uint32_t th = min(min(th4.x, th4.y), min(th4.z, th4.w));
        {
            const uint32_t k8[8] = {ka.x, ka.y, ka.z, ka.w, kb4.x, kb4.y, kb4.z, kb4.w};
            auto append = [&](int lo, int hi) {
                uint32_t n = 0, pos = 0;
#pragma unroll
                for (int i = lo; i < hi; i++) n += k8[i] >= th;
                asm volatile("{ .reg .pred p; setp.ne.u32 p, %2, 0; @p atom.shared.add.u32 %0, [%1], %2; }" : "+r"(pos) : "r"(sb + OFF_KEYS + 16), "r"(n) : "memory");
#pragma unroll
                for (int i = lo; i < hi; i++)
                    if (k8[i] >= th) reinterpret_cast<uint32_t*>(smem + OFF_LIST)[pos + i - lo] = k8[i];
            };
            append(0, 2);
            if (__any_sync(0xffffffffu, k8[2] >= th)) append(2, 8);
        }
        named_bar(2, 128);
        {
            const uint32_t* list = reinterpret_cast<const uint32_t*>(smem + OFF_LIST);
            const int n = (int)keys[4];
#pragma unroll 1
            for (int i0 = w * 32; i0 < n; i0 += 128) {
                const uint32_t k = list[i0 + lane];
                int rank = 0;
#pragma unroll 2
                for (int o = 0; o < n; o += 4) {
                    const uint4 l4 = *reinterpret_cast<const uint4*>(list + o);
                    rank += (l4.x > k) + (l4.y > k) + (l4.z > k) + (l4.w > k);
                }
                if (rank < 8) reinterpret_cast<uint32_t*>(smem + OFF_SEL)[rank] = k;
            }
        }
        named_bar(2, 128);
        STAMPIF(at == 0, 24);
        const uint32_t* sel = reinterpret_cast<const uint32_t*>(smem + OFF_SEL);
        auto gates = [&]() {
            uint32_t gv;
            it = 0;
            while (true) {
                gv = ld_relaxed(&prm.s->gate[chunk * 128 + at]);
                const uint32_t ar = ld_relaxed(&prm.s->armed[((cta >> 4) * 14 + min(lane, 13)) * 4]);
                if (__all_sync(0xffffffffu, (gv & 3u) == t2 && ar == t2)) break;
                if (++it > SPIN_LIMIT) __trap();
            }
            asm volatile("fence.acquire.gpu;" ::: "memory");
#pragma unroll
            for (int s = 0; s < 8; s++)
                if ((~sel[s] & 2047u) == (uint32_t)(chunk * 128 + at)) gv |= 0x80000000u;
            reinterpret_cast<uint16_t*>(smem + OFF_G)[at] = (uint16_t)(gv >> 16);
            __syncwarp();
            if (lane == 0) mbar_arrive(bar_g);
        };
        if (has_gu) {
            const int tk = (at >> 3) & 7;
            const char* xt = (const char*)prm.x + (~sel[tk] & 2047u) * 2048 + (at >> 6) * 128 + (at & 7) * 16;
#pragma unroll
            for (int i = 0; i < 8; i++) {
                cp_async16(sb + OFF_XS + (2 * i + (at >> 6)) * 1024 + tk * 128 + (((at & 7) ^ tk) << 4), xt + i * 256);
                if (i == 0 || i == 7) asm volatile("cp.async.commit_group;" ::: "memory");
            }
            asm volatile("cp.async.wait_group 1;" ::: "memory");
            fence_async_smem();
            named_bar(2, 128);
            STAMPIF(at == 0, 25);
            gate_up([&]() {
                asm volatile("cp.async.wait_all;" ::: "memory");
                fence_async_smem();
                named_bar(2, 128);
            });
            if (!(cta & 1)) {
#pragma unroll
                for (int u = 0; u < 4; u++) {
                    const float v = rbf(facc[u]);
                    facc[u] = __fdividef(v, 1.0f + __expf(-v));
                }
            }
            st_relaxed2(&prm.s->hid[cta * 128 + at], pack_bf(facc[0], facc[1]), pack_bf(facc[2], facc[3]));
        }
        STAMPIF(at == 0, 26);
        gates();
        {
            mbar_wait(empty + 8 * max(TN(HG), 31));
            const uint2* hp = &prm.s->hid[(cta >> 4) * 14 * 128 + at];
            uint32_t hv[16];
            it = 0;
            while (true) {
                uint32_t top = 0;
#pragma unroll
                for (int j = 0; j < 7; j++) {
                    const uint2 hg = ld_relaxed2(hp + 256 * j), hu = ld_relaxed2(hp + 256 * j + 128);
                    top = max(top, max(hg.x, hu.x));
                    hv[2 * j] = mul_bf2(hg.x, hu.x); hv[2 * j + 1] = mul_bf2(hg.y, hu.y);
                }
                if (__all_sync(0xffffffffu, top != ~0u)) break;
                do {
                    if (++it > SPIN_LIMIT) __trap();
                } while (!__all_sync(0xffffffffu, ld_relaxed(hp + min(lane, 13) * 128 - lane) != ~0u));
            }
            STAMPIF(at == 0 && it > 0, 61);
            hv[14] = hv[15] = 0;
#pragma unroll
            for (int j = 0; j < 4; j++)
                asm volatile("stmatrix.sync.aligned.m8n8.x4.trans.shared.b16 [%0], {%1, %2, %3, %4};" ::"r"(
                                 sb + OFF_HID + (2 * j + (lane >> 4)) * 1024 + (lane & 7) * 128 + (((2 * w + ((lane >> 3) & 1)) ^ (lane & 7)) << 4)),
                             "r"(hv[4 * j]), "r"(hv[4 * j + 1]), "r"(hv[4 * j + 2]), "r"(hv[4 * j + 3]) : "memory");
        }
        fence_async_smem();
        named_bar(2, 128);
        STAMPIF(at == 0, 27);
        uint32_t mine = __ballot_sync(0xffffffffu, lane < 8 && (int)((~sel[lane & 7] & 2047u) >> 7) == chunk), tr;
        uint2 xr, xd;
        float gr, rs;
        auto skip = [&](int n) {
#pragma unroll 1
            for (int i = 0; i < n; i++) mine &= mine - 1;
            if (mine) {
                const uint32_t key = sel[__ffs(mine) - 1], kb = key >> 16;
                tr = ~key & 2047u;
                xr = __ldg(reinterpret_cast<const uint2*>(prm.x + (size_t)tr * D_ + dt * 128) + lane);
                rs = rbf(sigmoidf_(bf_lo((kb & 0x8000u) ? (kb & 0x7FFFu) : (~kb & 0xFFFFu))));
                gr = fabsf(__bfloat162float(reinterpret_cast<const __nv_bfloat16*>(smem + OFF_G)[tr & 127]));
                xd = lds64(sb + OFF_DK + 8 * lane);
            }
        };
        skip(w);
        down();
#pragma unroll
        for (int u = 0; u < 4; u++)
            st_relaxed(&prm.s->y[((2 * c + (u & 1)) * 8 + (cta >> 4)) * D_ + (cta & 15) * 64 + w * 16 + g + 8 * (u >> 1)], (__float_as_uint(facc[u]) & ~3u) | t2);
        STAMPIF(at == 0, 28);
        sleep_until(clk32() + TN(T_Y));
        while (mine) {
            const uint32_t* yp = &prm.s->y[(__ffs(mine) - 1) * 8 * D_ + dt * 128 + 4 * lane];
            float y[4];
            it = 0;
            while (true) {
                uint32_t bad = 0;
                y[0] = y[1] = y[2] = y[3] = 0.f;
#pragma unroll
                for (int ks = 0; ks < 8; ks++) {
                    const uint4 v = ld_relaxed4(yp + ks * D_);
                    bad |= v.x ^ t2;
                    y[0] += __uint_as_float(v.x); y[1] += __uint_as_float(v.y); y[2] += __uint_as_float(v.z); y[3] += __uint_as_float(v.w);
                }
                if (__all_sync(0xffffffffu, (bad & 3u) == 0)) break;
                if (++it > SPIN_LIMIT) __trap();
            }
            STAMPIF(lane == 0 && it, 62);
#pragma unroll
            for (int u = 0; u < 4; u++) {
                const uint32_t x2 = (u & 2) ? xr.y : xr.x, d2 = mul_bf2(x2, (u & 2) ? xd.y : xd.x);
                y[u] = fmaf(gr, (u & 1) ? bf_hi(d2) : bf_lo(d2), rbf(rbf(1.0f - gr) * rbf(((u & 1) ? bf_hi(x2) : bf_lo(x2)) + rbf(rbf(y[u]) * rs))));
            }
            STAMPIF(lane == 0, 50);
            mbar_wait(bar_stored);
            asm volatile("red.global.add.v4.f32 [%0], {%1, %2, %3, %4};" ::"l"(prm.out + (size_t)tr * D_ + dt * 128 + 4 * lane), "f"(y[0]), "f"(y[1]), "f"(y[2]), "f"(y[3]) : "memory");
            skip(4);
        }
        LSTAMP(lane == 0, 96 + 29);
    } else {
        asm volatile("setmaxnreg.dec.sync.aligned.u32 40;");
        if (warp == 15) {
            prefetch_map(&mXr);
            named_bar(0, 480);
#pragma unroll 1
            for (int i = 0; i < 4; i++) {
                const int u = i;
                if (lane == 0) mbar_expect_tx(ffull + 8 * u, TILE);
                sleep_until(cstart + (i == 0 ? TN(RT0) : i == 1 ? TN(RT1) : i == 2 ? TN(RT2) : TN(RT3)));
                if (elect_one()) tma3(sb + OFF_FT + u * TILE, &mXr, u * 256, rid * 16, ffull + 8 * u);
                STAMP(53 + u);
            }
            const CUtensorMap* mw = (cta & 1) ? &mWu : &mWg;
            if (sb & 1023) __trap();
            prefetch_map(mw);
            prefetch_map(&mWd);
            uint32_t slot = 4, par = 1;
#pragma unroll 1
            for (int j = 0; j < (has_gu && DBG != 1 ? 16 : 0); j++) {
                mbar_wait(fempty + 8 * slot, par);
                if (lane == 0) mbar_expect_tx(ffull + 8 * slot, TILE);
                mbar_wait(empty + 8 * prm.fetch[j]);
                STAMPW(1, 176 + j);
                if (elect_one()) tma2(sb + OFF_FT + slot * TILE, mw, (cta >> 1) * 64, TN(WDBG) ? 0 : j * 64, ffull + 8 * slot);
                if (++slot == NFT) { slot = 0; par ^= 1; }
            }
            if (lane < 9) mbar_expect_tx(lane < 7 ? dfull + 8 * lane : bar_x + 8 * (lane - 7), lane < 7 ? TILE : 2 * TILE);
            if (!has_gu) mbar_wait(bar_g);
#pragma unroll 1
            for (int j = 0; j < (DBG != 1 ? 7 : 0); j++) {
                if (has_gu) mbar_wait(fempty + 8 * min(j, 4), 1);
                mbar_wait(empty + 8 * prm.fetch[16 + j]);
                if (elect_one()) tma2(sb + OFF_FT + j * TILE, &mWd, (cta & 15) * 64, (cta >> 4) * 448 + (TN(WDBG) ? 0 : j * 64), dfull + 8 * j);
            }
            prefetch_map(&mXe);
#pragma unroll 1
            for (int u = 0; u < 4; u++) {
                mbar_wait(bar_dfree + 8 + 4 * (u & 2));
                mbar_wait(empty + 8 * (TN(DN_E0) + u));
                if (elect_one())
                    asm volatile("cp.async.bulk.tensor.5d.shared::cluster.global.mbarrier::complete_tx::bytes [%0], [%1, {%3, %6, %6, %4, %5}], [%2];"
                                 ::"r"(sb + OFF_FT + (3 + u) * TILE), "l"(&mXe), "r"(bar_x + 4 * (u & 2)), "r"(dt * 128 + (u & 1) * 64), "r"(u & 2), "r"(chunk * 4), "r"(0) : "memory");
            }
        } else if (warp == 13) {
#pragma unroll
            for (int u = 0; u < 8; u++) {
                const int row = (u >> 2) * 4 + (lane >> 3);
                cp_async16(sb + OFF_XS + (u & 3) * 1024 + row * 128 + (((lane & 7) ^ row) << 4), (const char*)(u < 4 ? prm.w_r : prm.gate_w) + (u & 3) * 512 + lane * 16);
            }
            STAMP(57);
            const uint32_t tag = ld_relaxed(&prm.s->epoch[cta]) + 1;
            named_bar(1, 64);
            *reinterpret_cast<uint2*>(smem + OFF_EPOCH) = make_uint2(tag, tag % 3u + 1u);
            STAMPIF(tag, 58);
            asm volatile("cp.async.wait_all;" ::: "memory");
            STAMP(59);
            fence_async_smem();
            __syncwarp();
            if (lane == 0) {
                mbar_arrive(bar_epoch);
                prm.s->epoch[cta] = tag;
            }
            sleep_until(cstart + TN(T_BASE));
            {
                const uint2 st = ld_relaxed2(&prm.s->start[2 * lane]);
                const uint32_t d = st.x - cstart + 512u, age = gtime32() - st.y;
                const uint32_t m = __reduce_max_sync(0xffffffffu, d < 1024u && age < 4096u ? (d << 12) | age : 0u);
                const uint32_t late = (m & 4095u) - __reduce_min_sync(0xffffffffu, age);
                *reinterpret_cast<volatile uint32_t*>(smem + OFF_EPOCH + 8) = cstart + (m ? (m >> 12) - 512u + min(late, 256u) * TN(G_NS) / 4 : 0u);
                __syncwarp();
                if (lane == 0) mbar_arrive(bar_base);
                STAMP(60);
            }
            mbar_wait(bar_const);
            asm volatile("fence.acq_rel.gpu;" ::: "memory");
            if (lane < 4) st_relaxed2(&prm.s->armed[cta * 4 + lane], tag % 3u + 1u, 0u);
            prefetch_map(&mCre);
            prefetch_map(&mCim);
            const char* src = reinterpret_cast<const char*>(prm.s->h) + (size_t)chunk * 524288;
            uint32_t slot = 32 % NST, hpar = 0, rpar = 0;
#pragma unroll 1
            for (int i = 32; i < CH1; i++) {
                mbar_wait(hfull + 8 * slot, hpar);
                rpar = check_tile<16>(sb, sb + slot * SLOT, probe, src, tag, bar_retry, rpar, TN(T_RETRY));
                if (lane == 0) mbar_expect_tx(full + 8 * i, 2 * TILE);
                src += 2 * TILE;
                slot = slot == NST - 1 ? 0 : slot + 1;
                hpar ^= slot == 32 % NST;
            }
        } else if (warp == 14) {
            prefetch_map(&mPB);
            auto pf_c = [&](int k) { prefetch_slice(&mPC, 4 * (k >> 1), cta * 8 + (k & 1) * 4); };
            named_bar(0, 480);
            asm volatile("bar.arrive 1, 64;" ::: "memory");
            if (lane < 24) st_relaxed(lane < 8 ? &prm.s->key[cta * 8 + lane] : &prm.s->gate[rid * 16 + lane - 8], 0u);
#pragma unroll 1
            for (int k = TN(PF0) ? 0 : 1; k < 4; k++) {
                sleep_until(cstart + (k == 0 ? TN(PF0) : k == 1 ? TN(PF1) : k == 2 ? TN(PF2) : TN(PF3)));
                if (elect_one()) prefetch_slice(&mPB, 4 * k, cta * 4);
            }
#pragma unroll 1
            for (int k = 0; k < 4; k++) {
                mbar_wait(empty + 8 * (TN(PB_E0) + TN(PB_STEP) * k));
                if (elect_one()) prefetch_slice(&mPB, 4 * k, 512 + cta * 4);
            }
#pragma unroll 1
            for (int k = 0; k < TN(PC_N); k++) {
                mbar_wait(empty + 8 * min(TN(PC_E0) + TN(PC_STEP) * k / 2, 26));
                if (elect_one()) pf_c(k);
            }
            int pk = TN(PC_N), pe = TN(PC_E1);
            auto own_part = [&](int e) {
                if (!mbar_test(bar_out + 8 * e, 0)) {
                    mbar_wait(bar_out + 8 * e);
                    sleep_until(clk32() + TN(T_OWN));
                    STAMP(11);
                }
            };
            const char* src = reinterpret_cast<const char*>(prm.s->h) + (size_t)chunk * 524288;
            uint32_t slot = 32 % NST;
#pragma unroll 1
            for (int i = 32; i < NBIG; i++) {
                if (!(i & 3)) own_part((i - 32) >> 2);
                mbar_wait(empty + 8 * (i - NST));
                PSTAMP(i);
                if (elect_one()) {
                    mbar_expect_tx(hfull + 8 * slot, 2 * TILE);
                    bulk_load(sb + slot * SLOT, src, 2 * TILE, hfull + 8 * slot);
                }
                if (i == pe && pk < 8) {
                    if (elect_one()) pf_c(pk);
                    pk++; pe += TN(PC_S1);
                }
                src += 2 * TILE;
                slot = slot == NST - 1 ? 0 : slot + 1;
            }
            mbar_wait(bar_dfree);
#pragma unroll
            for (int k = 0; k < 14; k++) {
                if (k == 4) continue;
                if (k == 0 || k == 2) own_part(6 + k / 2);
                mbar_wait(empty + 8 * (NBIG - NST + k));
                if (elect_one()) {
#pragma unroll
                    for (int n = k < 5 ? 2 * k : k + 2; n < (k < 3 ? 2 * k + 2 : k == 3 ? 7 : k + 3); n++) {
                        mbar_expect_tx(hfull + 8 * (NST + n % 7), TILE);
                        bulk_load(sb + tail_h(n), src + (n & 7) * 2 * TILE + (n >> 3) * TILE, TILE, hfull + 8 * (NST + n % 7));
                    }
                }
            }
        } else {
            if (elect_one()) {
#pragma unroll
                for (int i = 0; i < NST; i++) mbar_init(full + 8 * i, 1);
                fence_mbar_init();
            }
            __syncwarp();
#pragma unroll 1
            for (int i = 0; i < NST; i++) {
                if (elect_one()) {
                    mbar_expect_tx(full + 8 * i, SLOT);
                    tma5b(sb + i * SLOT, &mB, i * 64, dt * 4, full + 8 * i);
                    tma4(sb + i * SLOT + 2 * TILE, &mX, i * 64, chunk * 64, full + 8 * i);
                }
                STAMPIF(i == 0, 1);
                if (TN(T_FILL)) sleep_until(cstart + TN(T_FIL0) + i * TN(T_FILL));
            }
            STAMP(2);
            named_bar(0, 480);
            uint32_t dst = sb;
#pragma unroll 1
            for (int i = NST; i < 32; i++) {
                if (lane == 0) mbar_expect_tx(full + 8 * i, SLOT);
                mbar_wait(empty + 8 * (i - NST));
                PSTAMP(i);
                if (elect_one()) {
                    tma5b(dst, &mB, (i & 15) * 64, (i >> 4) * 64 + dt * 4, full + 8 * i);
                    tma4(dst + 2 * TILE, &mX, (i & 15) * 64, chunk * 64, full + 8 * i);
                }
                dst = dst == sb + (NST - 1) * SLOT ? sb : dst + SLOT;
            }
#pragma unroll 1
            for (int i = 32; i < NBIG; i++) {
                mbar_wait(empty + 8 * (i - NST));
                if (elect_one()) tma5(dst + 2 * TILE, (i & 4) ? &mCim : &mCre, ((i & 3) + ((i >> 1) & 12)) * 64, dt * 8, full + 8 * i);
                dst = dst == sb + (NST - 1) * SLOT ? sb : dst + SLOT;
            }
            dst = sb + tail_c(0);
#pragma unroll 1
            for (int j = 0; j < 8; j++) {
                mbar_wait(empty + 8 * (NBIG - NST + 1 + (j >> 1)));
                if (elect_one()) tma5(dst, (j & 4) ? &mCim : &mCre, ((j & 3) + 12) * 64, dt * 8, full + 8 * (NBIG + j));
                dst = j == 5 ? sb : dst + 2 * TILE;
            }
        }
    }
}

typedef CUresult (*EncodeFn)(CUtensorMap*, CUtensorMapDataType, cuuint32_t, void*, const cuuint64_t*, const cuuint64_t*, const cuuint32_t*,
                             const cuuint32_t*, CUtensorMapInterleave, CUtensorMapSwizzle, CUtensorMapL2promotion, CUtensorMapFloatOOBfill);

bool encode(EncodeFn fn, CUtensorMap* m, const void* ptr, int rank, const cuuint64_t* dims, const cuuint64_t* strides, const cuuint32_t* box,
            CUtensorMapL2promotion promo = CU_TENSOR_MAP_L2_PROMOTION_NONE) {
    const cuuint32_t es[5] = {1, 1, 1, 1, 1};
    return fn(m, CU_TENSOR_MAP_DATA_TYPE_BFLOAT16, rank, const_cast<void*>(ptr), dims, strides, box, es, CU_TENSOR_MAP_INTERLEAVE_NONE,
              CU_TENSOR_MAP_SWIZZLE_128B, promo, CU_TENSOR_MAP_FLOAT_OOB_FILL_NONE) == CUDA_SUCCESS;
}

}

extern "C" void kernel_launch(void* const* d_in, const int* in_sizes, int n_in, void* d_out, int out_size) {
    (void)in_sizes; (void)n_in; (void)out_size;
    Params prm;
    prm.x = (const __nv_bfloat16*)d_in[0];
    prm.lam_re = (const __nv_bfloat16*)d_in[1];
    prm.lam_im = (const __nv_bfloat16*)d_in[2];
    prm.b_re = (const __nv_bfloat16*)d_in[3];
    prm.b_im = (const __nv_bfloat16*)d_in[4];
    prm.c_re = (const __nv_bfloat16*)d_in[5];
    prm.c_im = (const __nv_bfloat16*)d_in[6];
    prm.log_dt = (const __nv_bfloat16*)d_in[7];
    prm.dskip = (const __nv_bfloat16*)d_in[8];
    prm.w_r = (const __nv_bfloat16*)d_in[10];
    prm.gate_w = (const __nv_bfloat16*)d_in[14];
    prm.out = (float*)d_out;
    cudaGetSymbolAddress((void**)&prm.s, g_scratch);
    prm.swapped = prm.b_im < prm.b_re;

    void* fnp = nullptr;
    cudaDriverEntryPointQueryResult qr;
    cudaGetDriverEntryPoint("cuTensorMapEncodeTiled", &fnp, cudaEnableDefault, &qr);
    EncodeFn fn = (EncodeFn)fnp;
    cudaFuncSetAttribute(fused_kernel, cudaFuncAttributeMaxDynamicSharedMemorySize, SMEM_BYTES);

    CUtensorMap mX, mB, mCre, mCim, mWg, mWu, mWd, mXr, mPB, mPC, mXe;
    const cuuint64_t row = 2048;
    {
        const cuuint64_t dims[4] = {1024, 2, 4, 976}, st[3] = {row, 32 * row, 2 * row};
        const cuuint32_t box[4] = {64, 2, 4, 16};
        encode(fn, &mX, prm.x, 4, dims, st, box, PROMO);
    }
    {
        const char *lo = (const char*)(prm.swapped ? prm.b_im : prm.b_re), *hi = (const char*)(prm.swapped ? prm.b_re : prm.b_im);
        const cuuint64_t dims[5] = {1024, 8, 2, 96, 2}, st[4] = {row, (cuuint64_t)(hi - lo), 8 * row, 256 * row};
        const cuuint32_t box[5] = {64, 8, 2, 4, 2};
        encode(fn, &mB, lo, 5, dims, st, box, PROMO);
    }
    {
        const cuuint64_t dims[5] = {1024, 2, 4, 2, 64}, st[4] = {row, 4 * row, 2 * row, 16 * row};
        const cuuint32_t box[5] = {64, 2, 4, 2, 8};
        encode(fn, &mCre, prm.c_re, 5, dims, st, box);
        encode(fn, &mCim, prm.c_im, 5, dims, st, box);
    }
    {
        const cuuint64_t dims[2] = {F_, D_}, st[1] = {F_ * 2}, dimsd[2] = {D_, F_}, std_[1] = {row};
        const cuuint32_t box[2] = {64, 64};
        encode(fn, &mWg, d_in[11], 2, dims, st, box);
        encode(fn, &mWu, d_in[12], 2, dims, st, box);
        encode(fn, &mWd, d_in[13], 2, dimsd, std_, box);
    }
    for (int i = 0; i < 2; i++) {
        const char *p = (const char*)(i ? prm.c_re : prm.b_re), *q = (const char*)(i ? prm.c_im : prm.b_im);
        const cuuint64_t dims[4] = {64, 16, 1024, 2}, st[3] = {128, row, (cuuint64_t)(p < q ? q - p : p - q)};
        const cuuint32_t box[4] = {16, 4, 4, 2};
        encode(fn, i ? &mPC : &mPB, p < q ? p : q, 4, dims, st, box, CU_TENSOR_MAP_L2_PROMOTION_L2_128B);
    }
    {
        const cuuint64_t dims[3] = {D_ - 192, S_, 4}, st[2] = {row, 128};
        const cuuint32_t box[3] = {64, 16, 4};
        encode(fn, &mXr, prm.x, 3, dims, st, box);
    }
    {
        const cuuint64_t dims[5] = {1024, 2, 4, 4, S_ / 32}, st[4] = {4 * row, row, 8 * row, 32 * row};
        const cuuint32_t box[5] = {64, 2, 4, 2, 4};
        encode(fn, &mXe, prm.x, 5, dims, st, box);
    }
    for (int j = 0, e4 = 4 * TN(GC0); j < 23; j++) {
        prm.fetch[j] = j < NFT ? TN(GU_E0) + j * TN(W_NUM) / 4 : j < 16 ? 0 : TN(DL0) + (j - 16) * TN(DLS) / 4;
        prm.use[j] = j < 16 ? e4 / 4 : TN(DC0) + (j - 16) * TN(DCS) / 4;
        const int last = 54;
        if (prm.fetch[j] > last) prm.fetch[j] = last;
        if (prm.use[j] > last) prm.use[j] = last;
        e4 += j < TN(N1) ? TN(GCS) : j < TN(N2) ? TN(GCS2) : j < 10 ? TN(GCS3) : TN(GCS4);
    }
    fused_kernel<<<NCTA, 512, SMEM_BYTES, cudaStreamPerThread>>>(mX, mB, mCre, mCim, mWg, mWu, mWd, mXr, mPB, mPC, mXe, prm);
}
```

```cpp
#include <cuda_runtime.h>
#include <cuda_bf16.h>
#include <cuda.h>
#include <stdint.h>

namespace {

constexpr int S_ = 2048, D_ = 1024, F_ = 3584;
constexpr int NCTA = 128;
constexpr int NBIG = 56, NENT = 72;
constexpr int NST = 5;
constexpr int NFT = 5;
constexpr uint32_t SLOT = 32768, TILE = 8192;
constexpr uint32_t OFF_FT = NST * SLOT;
constexpr uint32_t OFF_XS = OFF_FT + NFT * TILE;
constexpr uint32_t OFF_LIST = OFF_XS + 8192;
constexpr uint32_t OFF_RED = OFF_XS + 4096;
constexpr uint32_t OFF_CONST = OFF_XS + 16384;
constexpr uint32_t OFF_M = OFF_CONST + 8192, OFF_ONE = OFF_M + 512;
constexpr uint32_t OFF_HID = OFF_CONST;
constexpr uint32_t OFF_G = OFF_ONE + 16;
constexpr uint32_t OFF_DK = OFF_G + 256;
constexpr uint32_t OFF_FULL = OFF_DK + 256;
constexpr uint32_t OFF_EMPTY = OFF_FULL + 102 * 8;
constexpr uint32_t OFF_KEYS = OFF_EMPTY + 86 * 8;
constexpr uint32_t OFF_SEL = OFF_KEYS + 32;
constexpr uint32_t OFF_EPOCH = OFF_SEL + 32;
constexpr uint32_t OFF_PROF = OFF_EPOCH + 16;
constexpr uint32_t SMEM_BYTES = OFF_PROF + 432;
static_assert(SMEM_BYTES <= 232448, "smem");

static_assert(NBIG % NST == 1, "tail layout");
__host__ __device__ constexpr uint32_t tail_c(int j) { return j < 6 ? 2 * SLOT + j * 2 * TILE : (j - 6) * 2 * TILE; }
__host__ __device__ constexpr uint32_t tail_h(int n) { return n % 7 < 4 ? SLOT + n % 7 * TILE : OFF_FT + (n % 7 - 2) * TILE; }

constexpr uint32_t SPIN_LIMIT = 1u << 18;

struct Scratch {
    uint2 carry[16 * 1024];
    uint2 hid[NCTA * 128];
    uint32_t y[8 * 8 * D_];
    uint32_t key[NCTA * 8];
    uint32_t gate[S_];
    uint2 armed[NCTA * 4];
    unsigned int epoch[256];
    uint4 start[32 * 2];
    uint4 h[16 * 32 * 1024];
};
__device__ __align__(1024) Scratch g_scratch;
#define STAMPW_(cond, w) do {} while (0)
#define GSTAMP(cond, w) do {} while (0)
#define LSTAMP(cond, w) STAMPW_(cond, w)
#define LT 0
#define STAMPW(cond, w) STAMPW_(cond, w)
#define STAMPIF(cond, i) STAMPW(cond, 96 + (i))
#define STAMP(i) STAMPW(1, 96 + (i))
#define KSTAMP(i) STAMPW((threadIdx.x & 127) == 0, i)
#define PSTAMP(i) STAMPW((i) < 56 && (i) >= 32, 160 + (i))

struct Params {
    const __nv_bfloat16 *x, *b_re, *b_im, *lam_re, *lam_im, *c_re, *c_im, *log_dt, *dskip, *w_r, *gate_w;
    float* out;
    Scratch* s;
    int fetch[23], use[23];
    int swapped;
};

__device__ __forceinline__ uint32_t smem_u32(const void* p) { return (uint32_t)__cvta_generic_to_shared(p); }
__device__ __forceinline__ void mbar_init(uint32_t bar, uint32_t cnt) { asm volatile("mbarrier.init.shared::cta.b64 [%0], %1;" ::"r"(bar), "r"(cnt) : "memory"); }
__device__ __forceinline__ void mbar_expect_tx(uint32_t bar, uint32_t bytes) { asm volatile("mbarrier.arrive.expect_tx.shared::cta.b64 _, [%0], %1;" ::"r"(bar), "r"(bytes) : "memory"); }
__device__ __forceinline__ void mbar_arrive(uint32_t bar) { asm volatile("mbarrier.arrive.shared::cta.b64 _, [%0];" ::"r"(bar) : "memory"); }
__device__ __forceinline__ bool mbar_try(uint32_t bar, uint32_t parity) {
    uint32_t ok;
    asm volatile("{ .reg .pred p; mbarrier.try_wait.parity.shared::cta.b64 p, [%1], %2; selp.u32 %0, 1, 0, p; }" : "=r"(ok) : "r"(bar), "r"(parity) : "memory");
    return ok;
}
__device__ __forceinline__ bool mbar_test(uint32_t bar, uint32_t parity) {
    uint32_t ok;
    asm volatile("{ .reg .pred p; mbarrier.test_wait.parity.shared::cta.b64 p, [%1], %2; selp.u32 %0, 1, 0, p; }" : "=r"(ok) : "r"(bar), "r"(parity) : "memory");
    return __all_sync(0xffffffffu, ok);
}
__device__ __forceinline__ void mbar_wait(uint32_t bar, uint32_t parity = 0) {
    if (mbar_try(bar, parity)) return;
#pragma unroll 1
    for (uint32_t it = 0; it < SPIN_LIMIT; ++it)
        if (mbar_try(bar, parity)) return;
    __trap();
}
__device__ __forceinline__ bool elect_one() {
    uint32_t pred;
    asm volatile("{ .reg .pred P; elect.sync _|P, 0xffffffff; selp.b32 %0, 1, 0, P; }" : "=r"(pred));
    return pred;
}
__device__ __forceinline__ void named_bar(int id, int n) { asm volatile("bar.sync %0, %1;" ::"r"(id), "r"(n) : "memory"); }
__device__ __forceinline__ void fence_mbar_init() { asm volatile("fence.mbarrier_init.release.cluster;" ::: "memory"); }
__device__ __forceinline__ void fence_async_smem() { asm volatile("fence.proxy.async.shared::cta;" ::: "memory"); }

__device__ __forceinline__ void bulk_load(uint32_t dst, const void* src, uint32_t bytes, uint32_t bar) {
    asm volatile("cp.async.bulk.shared::cluster.global.mbarrier::complete_tx::bytes [%0], [%1], %2, [%3];" ::"r"(dst), "l"(src), "r"(bytes), "r"(bar) : "memory");
}
__device__ __forceinline__ void cp_async16(uint32_t dst, const void* src) { asm volatile("cp.async.cg.shared.global [%0], [%1], 16;" ::"r"(dst), "l"(src) : "memory"); }
__device__ __forceinline__ void sts128(uint32_t a, uint32_t x, uint32_t y, uint32_t z, uint32_t w) {
    asm volatile("st.shared.v4.u32 [%0], {%1,%2,%3,%4};" ::"r"(a), "r"(x), "r"(y), "r"(z), "r"(w) : "memory");
}
__device__ __forceinline__ uint2 lds64(uint32_t a) {
    uint2 v;
    asm volatile("ld.shared.v2.u32 {%0,%1}, [%2];" : "=r"(v.x), "=r"(v.y) : "r"(a) : "memory");
    return v;
}
__device__ __forceinline__ uint32_t lds32(uint32_t a) {
    uint32_t v;
    asm volatile("ld.volatile.shared.u32 %0, [%1];" : "=r"(v) : "r"(a) : "memory");
    return v;
}
__device__ __forceinline__ void stg128(void* p, uint32_t x, uint32_t y, uint32_t z, uint32_t w) {
    asm volatile("st.global.v4.u32 [%0], {%1,%2,%3,%4};" ::"l"(p), "r"(x), "r"(y), "r"(z), "r"(w) : "memory");
}
__device__ __forceinline__ void st_relaxed(void* p, uint32_t x) { asm volatile("st.relaxed.gpu.global.b32 [%0], %1;" ::"l"(p), "r"(x) : "memory"); }
__device__ __forceinline__ void st_relaxed2(void* p, uint32_t x, uint32_t y) { asm volatile("st.relaxed.gpu.global.v2.b32 [%0], {%1, %2};" ::"l"(p), "r"(x), "r"(y) : "memory"); }
__device__ __forceinline__ void st_relaxed4(void* p, uint32_t x, uint32_t y, uint32_t z, uint32_t w) {
    asm volatile("st.relaxed.gpu.global.v4.b32 [%0], {%1, %2, %3, %4};" ::"l"(p), "r"(x), "r"(y), "r"(z), "r"(w) : "memory");
}
__device__ __forceinline__ uint32_t ld_relaxed(const void* p) {
    uint32_t v;
    asm volatile("ld.relaxed.gpu.global.b32 %0, [%1];" : "=r"(v) : "l"(p) : "memory");
    return v;
}
__device__ __forceinline__ uint2 ld_relaxed2(const void* p) {
    uint2 v;
    asm volatile("ld.relaxed.gpu.global.v2.b32 {%0, %1}, [%2];" : "=r"(v.x), "=r"(v.y) : "l"(p) : "memory");
    return v;
}
__device__ __forceinline__ uint4 ld_relaxed4(const void* p) {
    uint4 v;
    asm volatile("ld.relaxed.gpu.global.v4.b32 {%0, %1, %2, %3}, [%4];" : "=r"(v.x), "=r"(v.y), "=r"(v.z), "=r"(v.w) : "l"(p) : "memory");
    return v;
}
__device__ __forceinline__ uint32_t clk32() { uint32_t c; asm volatile("mov.u32 %0, %%clock;" : "=r"(c)); return c; }
__device__ __forceinline__ uint32_t gtime32() { uint32_t c; asm volatile("mov.u32 %0, %%globaltimer_lo;" : "=r"(c)); return c; }
__device__ __forceinline__ void sched_fence(uint32_t t) { while ((int)(clk32() - t) < 0) {} }
__device__ __forceinline__ void sleep_until(uint32_t t) { while ((int)(clk32() - t) < 0) __nanosleep(40); }

__device__ __forceinline__ void tma2(uint32_t dst, const CUtensorMap* m, int c0, int c1, uint32_t bar) {
    asm volatile("{ .reg .b64 pol; createpolicy.fractional.L2::evict_first.b64 pol;\n"
                 "cp.async.bulk.tensor.2d.shared::cluster.global.mbarrier::complete_tx::bytes.L2::cache_hint [%0], [%1, {%3, %4}], [%2], pol; }"
                 ::"r"(dst), "l"(m), "r"(bar), "r"(c0), "r"(c1) : "memory");
}
__device__ __forceinline__ void tma3(uint32_t dst, const CUtensorMap* m, int c0, int c1, uint32_t bar) {
    asm volatile("cp.async.bulk.tensor.3d.shared::cluster.global.mbarrier::complete_tx::bytes [%0], [%1, {%3, %4, %5}], [%2];"
                 ::"r"(dst), "l"(m), "r"(bar), "r"(c0), "r"(c1), "r"(0) : "memory");
}
__device__ __forceinline__ void tma4(uint32_t dst, const CUtensorMap* m, int c0, int c3, uint32_t bar) {
    asm volatile("cp.async.bulk.tensor.4d.shared::cluster.global.mbarrier::complete_tx::bytes [%0], [%1, {%3, %5, %5, %4}], [%2];"
                 ::"r"(dst), "l"(m), "r"(bar), "r"(c0), "r"(c3), "r"(0) : "memory");
}
__device__ __forceinline__ void tma5(uint32_t dst, const CUtensorMap* m, int c0, int c4, uint32_t bar) {
    asm volatile("cp.async.bulk.tensor.5d.shared::cluster.global.mbarrier::complete_tx::bytes [%0], [%1, {%3, %5, %5, %5, %4}], [%2];"
                 ::"r"(dst), "l"(m), "r"(bar), "r"(c0), "r"(c4), "r"(0) : "memory");
}
__device__ __forceinline__ void tma5b(uint32_t dst, const CUtensorMap* m, int c0, int c3, uint32_t bar) {
    asm volatile("cp.async.bulk.tensor.5d.shared::cluster.global.mbarrier::complete_tx::bytes [%0], [%1, {%3, %5, %5, %4, %5}], [%2];"
                 ::"r"(dst), "l"(m), "r"(bar), "r"(c0), "r"(c3), "r"(0) : "memory");
}
__device__ __forceinline__ void prefetch_l2(const void* p) { asm volatile("prefetch.global.L2 [%0];" ::"l"(p)); }
__device__ __forceinline__ void prefetch_slice(const CUtensorMap* m, int line, int row) {
    asm volatile("cp.async.bulk.prefetch.tensor.4d.L2.global [%0, {%3, %1, %2, %3}];" ::"l"(m), "r"(line), "r"(row), "r"(0) : "memory");
}
__device__ __forceinline__ void prefetch_map(const CUtensorMap* m) { asm volatile("prefetch.tensormap [%0];" ::"l"(m)); }
__device__ __forceinline__ uint32_t uni(uint32_t v) { return __shfl_sync(0xffffffffu, v, 0); }

__device__ __forceinline__ uint32_t make_desc(uint32_t addr) { return ((addr & 0x3FFFF) >> 4) | (1u << 16); }
__device__ __forceinline__ uint32_t make_desc_h(uint32_t addr) { return ((addr & 0x3FFFF) >> 4) | (32u << 16); }
template <int H> __device__ __forceinline__ uint64_t desc64(uint32_t lo) {
    uint64_t d;
    asm volatile("mov.b64 %0, {%1, %2};" : "=l"(d) : "r"(lo), "n"(64u | ((H ? 2u : 1u) << 30)));
    return d;
}
__device__ __forceinline__ void wgmma_fence() { asm volatile("wgmma.fence.sync.aligned;" ::: "memory"); }
__device__ __forceinline__ void wgmma_commit() { asm volatile("wgmma.commit_group.sync.aligned;" ::: "memory"); }
template <int N> __device__ __forceinline__ void wgmma_wait() { asm volatile("wgmma.wait_group.sync.aligned %0;" ::"n"(N) : "memory"); }

#define R8(d, i) "+f"(d[i]), "+f"(d[i + 1]), "+f"(d[i + 2]), "+f"(d[i + 3]), "+f"(d[i + 4]), "+f"(d[i + 5]), "+f"(d[i + 6]), "+f"(d[i + 7])
#define R64(d) R8(d, 0), R8(d, 8), R8(d, 16), R8(d, 24), R8(d, 32), R8(d, 40), R8(d, 48), R8(d, 56)
template <int TA>
__device__ __forceinline__ void wgmma_n128(float (&d)[64], uint64_t da, uint64_t db, int scale_d = 1) {
    asm volatile("{ .reg .pred p; setp.ne.b32 p, %66, 0;\n"
                 "wgmma.mma_async.sync.aligned.m64n128k16.f32.bf16.bf16 "
                 "{%0,%1,%2,%3,%4,%5,%6,%7,%8,%9,%10,%11,%12,%13,%14,%15,%16,%17,%18,%19,%20,%21,%22,%23,%24,%25,%26,%27,%28,%29,%30,%31,"
                 "%32,%33,%34,%35,%36,%37,%38,%39,%40,%41,%42,%43,%44,%45,%46,%47,%48,%49,%50,%51,%52,%53,%54,%55,%56,%57,%58,%59,%60,%61,%62,%63}, "
                 "%64, %65, p, 1, 1, %67, 0; }"
                 : R64(d)
                 : "l"(da), "l"(db), "r"(scale_d), "n"(TA));
}
__device__ __forceinline__ void pin4(float (&d)[4]) { asm volatile("" : "+f"(d[0]), "+f"(d[1]), "+f"(d[2]), "+f"(d[3])::"memory"); }
__device__ __forceinline__ void pin64(float (&d)[64]) { asm volatile("" : R64(d)::"memory"); }

template <int TA>
__device__ __forceinline__ void wgmma_n8(float (&d)[4], uint64_t da, uint64_t db, int scale_d = 1) {
    asm volatile("{ .reg .pred p; setp.ne.b32 p, %7, 0;\n"
                 "wgmma.mma_async.sync.aligned.m64n8k16.f32.bf16.bf16 {%0,%1,%2,%3}, %4, %5, p, 1, 1, %6, 0; }"
                 : "+f"(d[0]), "+f"(d[1]), "+f"(d[2]), "+f"(d[3])
                 : "l"(da), "l"(db), "n"(TA), "r"(scale_d));
}

__device__ __forceinline__ float bf_lo(uint32_t u) { return __uint_as_float(u << 16); }
__device__ __forceinline__ float bf_hi(uint32_t u) { return __uint_as_float(u & 0xFFFF0000u); }
__device__ __forceinline__ float rbf(float v) { return __bfloat162float(__float2bfloat16_rn(v)); }
__device__ __forceinline__ uint32_t pack_bf(float lo, float hi) {
    uint32_t r;
    asm("cvt.rn.bf16x2.f32 %0, %1, %2;" : "=r"(r) : "f"(hi), "f"(lo));
    return r;
}
__device__ __forceinline__ uint32_t mul_bf2(uint32_t a, uint32_t b) {
    uint32_t r;
    asm("mul.rn.bf16x2 %0, %1, %2;" : "=r"(r) : "r"(a), "r"(b));
    return r;
}
__device__ __forceinline__ uint32_t fma_bf2(uint32_t a, uint32_t b, uint32_t c) {
    uint32_t r;
    asm("fma.rn.bf16x2 %0, %1, %2, %3;" : "=r"(r) : "r"(a), "r"(b), "r"(c));
    return r;
}
__device__ __forceinline__ float2 cmul(float2 a, float2 b) { return make_float2(a.x * b.x - a.y * b.y, a.x * b.y + a.y * b.x); }
__device__ __forceinline__ float2 cfma(float2 a, float2 b, float2 c) {
    return make_float2(fmaf(a.x, b.x, fmaf(-a.y, b.y, c.x)), fmaf(a.x, b.y, fmaf(a.y, b.x, c.y)));
}
__device__ __forceinline__ float sigmoidf_(float v) { return __fdividef(1.0f, 1.0f + expf(-v)); }

#define SCHED_NAMES RT0, RT1, RT2, RT3, PF0, PF1, PF2, PF3, T_SMALL, T_INIT, T_X0, T_BASE, G_NS, GT0, GT1, GT2, G0, GAP0, GAP1, RS_E, \
    PB_E0, PB_STEP, PC_E0, PC_STEP, PC_N, PC_E1, PC_S1, GU_E0, W_NUM, GC0, N1, N2, GCS, GCS2, GCS3, GCS4, HG, DL0, DLS, DC0, DCS, DN_E0, WDBG, T_OWN, T_RETRY, NP, T_Y, T_FIL0, T_FILL
enum { SCHED_NAMES, NTUNE };
constexpr int sched_default[NTUNE] = {
    2500, 3000, 3500, 4000,
    0, 1100, 1300, 2800,
    400, 500, 1, 2500, 3,
    6700, 0, 0,
    1500, 50, 50, 4,
    4, 1, 9, 4, 5, 50, 3,
    4, 9, 15, 6, 6, 7, 7, 7, 5, 43, 37, 8, 38, 1, 50,
    0, 1100, 200, 0, 700, 0, 0};
template <int I> struct Sched { static constexpr int v = sched_default[I]; };
#define TN(i) (Sched<i>::v)
#define DBG 0
#define NKK 4
#define EARLY 1
#define TDBG 0
#define X0 2
#define CH1 52
#define GE 8
#define DOUBLE 0
#define RAISE_J 1
#define GREEDY 0
#define POLL_S 24
#define PROMO CU_TENSOR_MAP_L2_PROMOTION_L2_256B

template <int TA, class H>
__device__ __forceinline__ void run_entry(uint32_t lo32, uint32_t prev, int accumulate, float (&accA)[64], float (&accB)[64], H inside) {
    const uint64_t da = desc64<TA>(lo32), db = TA ? desc64<0>(lo32 + (2 * TILE >> 4) - (31u << 16)) : da + (2 * TILE >> 4);
    wgmma_fence();
#pragma unroll
    for (int kk = 0; kk < 4; kk++) {
        wgmma_n128<TA>(accA, da + kk * (TA ? 128 : 2), db + kk * 2, kk > 0 ? 1 : accumulate);
        wgmma_n128<TA>(accB, da + 512 + kk * (TA ? 128 : 2), db + kk * 2, kk > 0 ? 1 : accumulate);
        if (kk == 1) {
            wgmma_commit();
            wgmma_wait<1>();
            if ((threadIdx.x & 31) == 0) mbar_arrive(prev);
            inside();
        }
    }
    wgmma_commit();
}
template <int TA, class H>
__device__ __forceinline__ void run_entries(uint32_t sb, int lo, int hi, int slot, float (&accA)[64], float (&accB)[64], H after) {
    const uint32_t da0 = TA ? make_desc_h(sb) : make_desc(sb), dlast = da0 + (NST - 1) * (SLOT >> 4);
    uint32_t prev = sb + OFF_FULL + 8 * 80, bar = sb + OFF_FULL + 8 * lo, lo32 = da0 + slot * (SLOT >> 4);
    int accumulate = 0;
#pragma unroll 1
    for (int i = lo; i < hi; i++) {
        mbar_wait(bar);
        KSTAMP(i);
        run_entry<TA>(lo32, prev, accumulate, accA, accB, []() {});
        prev = bar + (OFF_EMPTY - OFF_FULL);
        bar += 8;
        lo32 = lo32 == dlast ? da0 : lo32 + (SLOT >> 4);
        accumulate = 1;
        after(i);
    }
}

template <int TA>
__device__ __forceinline__ void small_tile(float (&acc)[4], uint32_t alo, uint32_t blo, bool first) {
    const uint64_t da = desc64<0>(alo), db = desc64<0>(blo);
#pragma unroll
    for (int kk = 0; kk < 4; kk++) wgmma_n8<TA>(acc, da + kk * (TA ? 128 : 2), db + kk * 2, kk > 0 || !first);
}

template <int N>
__device__ __forceinline__ uint32_t check_tile(uint32_t sb, uint32_t dst, uint32_t probe, const char* src, uint32_t par, uint32_t bar, uint32_t phase, uint32_t pause) {
    if ((TDBG & 4) && N == 8) return phase;
#pragma unroll 1
    for (uint32_t it = 0; it < SPIN_LIMIT; it++) {
        uint32_t v[N], bad = 0;
#pragma unroll
        for (int u = 0; u < N; u++) v[u] = lds32(dst + probe + (u >> 1) * 2048 + (u & 1) * 256);
#pragma unroll
        for (int u = 0; u < N; u += 4)
            asm("{ .reg .b32 a, b; lop3.b32 a, %1, %2, %5, 0x7E; lop3.b32 b, %3, %4, %5, 0x7E; lop3.b32 %0, %0, a, b, 0xFE; }"
                : "+r"(bad) : "r"(v[u]), "r"(v[u + 1]), "r"(v[u + 2]), "r"(v[u + 3]), "r"(par));
        if (!__any_sync(0xffffffffu, bad & 1u)) return phase;
        STAMP(10);
        __nanosleep(pause);
        if (elect_one()) {
            mbar_expect_tx(bar, N * 1024);
            bulk_load(dst, src, N * 1024, bar);
        }
        mbar_wait(bar, phase);
        phase ^= 1;
    }
    __trap();
    return 0;
}

__global__ void __launch_bounds__(512, 1)
fused_kernel(const __grid_constant__ Params prm, const __grid_constant__ CUtensorMap mX, const __grid_constant__ CUtensorMap mB, const __grid_constant__ CUtensorMap mCre,
             const __grid_constant__ CUtensorMap mCim, const __grid_constant__ CUtensorMap mWg, const __grid_constant__ CUtensorMap mWu,
             const __grid_constant__ CUtensorMap mWd, const __grid_constant__ CUtensorMap mXr, const __grid_constant__ CUtensorMap mPB,
             const __grid_constant__ CUtensorMap mPC, const __grid_constant__ CUtensorMap mXe) {
    extern __shared__ __align__(1024) uint8_t smem[];
    uint32_t sb;
    asm volatile("mov.u32 %0, %1;" : "=r"(sb) : "r"(smem_u32(smem)));
    const int tid = threadIdx.x, warp = __shfl_sync(0xffffffffu, tid >> 5, 0), lane = tid & 31;
    const int cta = blockIdx.x;
    const uint32_t cstart = clk32();
    const int chunk = (cta >> 2) & 15;
    const int dt = (cta >> 6) * 4 + (cta & 3);
    const int rid = chunk * 8 + dt;
    const bool has_gu = cta < 112;
    const uint32_t full = sb + OFF_FULL, empty = sb + OFF_EMPTY;
    const uint32_t ffull = full + 8 * 85, fempty = empty + 8 * 65;
    const uint32_t bar_epoch = full + 8 * 72, dfull = full + 8 * 73, bar_base = full + 8 * 82, bar_x = full + 8 * 83, bar_retry = full + 8 * 81, hfull = full + 8 * 90;
    const uint32_t bar_order = empty + 8 * 70, bar_const = empty + 8 * 85, bar_stored = empty + 8 * 72, bar_dfree = empty + 8 * 73,
                    bar_g = empty + 8 * 84, bar_out = empty + 8 * 76;
    const int w = warp & 3, g = lane >> 2, c = lane & 3, at = tid & 127;

    const uint32_t probe = (lane >> 3) * 32 + (g & 1) * 144 + (c & 1) * 520 + (c >> 1) * 1028;

    LSTAMP(tid == 0, 96);
    GSTAMP(tid == 0, 94);
    auto init_barriers = [&]() {
        if (elect_one()) {
            const uint32_t base = warp < 6 ? full + min(8 * NST + 136 * warp, 8 * 85) : empty + min(136 * (warp - 6), 8 * 69), cnt = warp < 6 ? 1 : 4;
#pragma unroll
            for (int i = 0; i < 17; i++) mbar_init(base + 8 * i, cnt);
            fence_mbar_init();
        }
        __syncwarp();
    };
    if (warp != 12) {
        if (warp >= 14) {
            const int r = cta * 8 + g;
            if (warp == 15 && !(cta & 3) && lane < 8) st_relaxed((uint32_t*)&prm.s->start[cta >> 1] + lane, (lane & 1) ? gtime32() : cstart);
            prefetch_l2(warp == 14 ? (const char*)prm.x + (rid * 16 + (lane >> 1)) * 2048 + (c & 1 & TN(T_X0)) * 128
                                   : (const char*)((r & 512) ? prm.b_im : prm.b_re) + (r & 511) * 2048 + (c & TN(T_X0)) * 128);
        }
        sleep_until(cstart + (warp == 13 ? TN(T_SMALL) : TN(T_INIT)));
    }
    if (warp < 8) {
        init_barriers();
        asm volatile("setmaxnreg.inc.sync.aligned.u32 192;");
        named_bar(0, 480);
        STAMPIF(tid == 0 && lds32(sb + OFF_KEYS + 16) == 0, 8);
        const int wg = warp >> 2;
        const int p = wg * 512 + dt * 32 + w * 8 + g;
        uint32_t cp = sb + OFF_CONST + 8 * (wg * 64 + w * 8 + g), cw = cp + 1024 * c, cm = sb + OFF_M + 4 * (wg * 64 + w * 8 + g);
        const int j1 = chunk - 1 - c;
        uint2* cq = &prm.s->carry[j1 * 1024 + p];
        char* hd = reinterpret_cast<char*>(prm.s->h) + (size_t)chunk * 524288 + wg * 262144 + (dt >> 1) * 16384 + ((dt & 1) * 4 + w) * 1024 + g * 64 + ((c ^ (g >> 1)) << 4);
        const bool never = uni(cstart == 0 && sb == 0);
        asm volatile("" : "+l"(cq), "+l"(hd), "+r"(cp), "+r"(cw), "+r"(cm));
        float2 a[2], a32[2], a64[2], a512[2], pw32[2], pw128[2];
        uint32_t mm[2], t2, par;
        auto constants = [&](int h) {
            if (h) { t2 = lds32(sb + OFF_EPOCH + 4); par = lds32(sb + OFF_EPOCH); }
            auto ldc = [](uint32_t a) { const uint2 v = lds64(a); return make_float2(__uint_as_float(v.x), __uint_as_float(v.y)); };
            {
                a[h] = ldc(cp + 256 * h); a32[h] = ldc(cp + 256 * h + 1024); a64[h] = ldc(cp + 256 * h + 2048); a512[h] = ldc(cp + 256 * h + 7168);
                pw32[h] = ldc(cw + 256 * h);
                pw128[h] = ldc(cw + 256 * h + 3072);
                mm[h] = lds32(cm + 128 * h);
            }
        };
        if (wg == 1) {
            const int pc = w * 256 + dt * 32 + lane;
            const float lr = __bfloat162float(prm.lam_re[pc]), li = __bfloat162float(prm.lam_im[pc]), ld = __bfloat162float(prm.log_dt[pc]);
            const uint32_t dk = __ldg(reinterpret_cast<const uint32_t*>(prm.dskip + dt * 128) + (at & 63));
            reinterpret_cast<uint32_t*>(smem + OFF_DK)[at & 63] = dk;
            const float dtv = rbf(expf(ld));
            const float er = expf(dtv * lr);
            float sn, cs;
            sincosf(dtv * li, &sn, &cs);
            const float ar = er * cs, ai = er * sn;
            const float nr = ar - 1.0f, ni = ai;
            const bool big = fabsf(lr) >= fabsf(li);
            const float t = (big ? li : lr) / (big ? lr : li), dn = big ? lr + li * t : lr * t + li;
            const float cr = (big ? nr + ni * t : nr * t + ni) / dn, ci = (big ? ni - nr * t : ni * t - nr) / dn;
            float2* ct = reinterpret_cast<float2*>(smem + OFF_CONST) + at;
            float2 pw = make_float2(ar, prm.swapped ? -ai : ai);
            ct[0] = pw;
            const float mx = prm.swapped ? -2.f * ci : 2.f * cr, my = prm.swapped ? 2.f * cr : -2.f * ci;
            reinterpret_cast<uint32_t*>(smem + OFF_M)[at] = pack_bf(mx, my);
#pragma unroll
            for (int i = 0; i < 5; i++) pw = cmul(pw, pw);
#pragma unroll
            for (int i = 0; i < 2; i++) {
                const float2 p2 = cmul(pw, pw);
                ct[128 + 384 * i] = pw; ct[256 + 384 * i] = p2; ct[384 + 384 * i] = cmul(p2, pw);
                pw = cmul(p2, p2);
            }
            ct[896] = pw;
            mbar_wait(bar_epoch);
            __syncwarp();
            mbar_wait(empty + 8 * TN(RS_E));
            st_relaxed2(&prm.s->hid[cta * 128 + at], ~0u, ~0u);
            st_relaxed4(&prm.s->y[((at >> 4) * 8 + (cta >> 4)) * D_ + (cta & 15) * 64 + (at & 15) * 4], 0u, 0u, 0u, 0u);
            st_relaxed2(&prm.s->carry[chunk * 1024 + pc], 0u, 0u);
            __syncwarp();
            if (lane == 0) mbar_arrive(bar_const);

            STAMPIF(at == 0, 3);
            mbar_wait(bar_const);
            constants(0);
            constants(1);
            mbar_wait(bar_order);
        }

        float accA[64], accB[64];
        run_entries<0>(sb, wg * 16, wg * 16 + 15, wg, accA, accB, [&](int i) {
            if (i == GE - 1) {
                mbar_wait(bar_base);
                sched_fence(lds32(sb + OFF_EPOCH + 8) + TN(GT0));
            }
        });
        mbar_wait(full + 8 * (wg * 16 + 15));
        KSTAMP(wg * 16 + 15);
        if (wg == 0) {
            mbar_wait(bar_const);
            run_entry<0>(make_desc(sb), empty + 8 * 14, 1, accA, accB, [&]() { constants(0); constants(1); if (EARLY && lane == 0) mbar_arrive(bar_order); });
        } else run_entry<0>(make_desc(sb + SLOT), empty + 8 * 30, 1, accA, accB, [&]() { if (EARLY && lane == 0) mbar_arrive(bar_order + 8); });
        if (!EARLY && lane == 0) mbar_arrive(bar_order + 8 * wg);
        uint2 v[2][4];
#pragma unroll
        for (int m = 0; m < 8; m++) v[m >> 2][m & 3] = make_uint2(t2, t2);
        wgmma_wait<0>();
        pin64(accA); pin64(accB);
        if (lane == 0) mbar_arrive(empty + 8 * (wg * 16 + 15));
        LSTAMP(at == 0, 96 + 30 + 10 * wg); GSTAMP(LT && at == 0, 193 + wg);

        auto cut = [&]() { if (never) sched_fence(cstart); };
        auto poll = [&](uint2 (&u)[4], int h) {
#pragma unroll
            for (int m = 0; m < 4; m++)
                asm volatile("{ .reg .pred p; setp.ge.s32 p, %3, %4; @p ld.relaxed.gpu.global.v2.b32 {%0, %1}, [%2]; }"
                             : "+r"(u[m].x), "+r"(u[m].y) : "l"(cq + 256 * h - 4096 * m), "r"(j1), "r"(4 * m) : "memory");
        };
        auto check = [&](const uint2 (&u)[4]) {
            uint32_t bad = 0;
#pragma unroll
            for (int m = 0; m < 4; m++) bad |= (u[m].x ^ t2) | (u[m].y ^ t2);
            return bad;
        };
        auto valid = [&](const uint2 (&u)[4]) { return __all_sync(0xffffffffu, (check(u) & 3u) == 0); };

        auto horner = [&](const uint2 (&u)[4], int h) {
            float2 r = make_float2(__uint_as_float(u[3].x), __uint_as_float(u[3].y));
#pragma unroll
            for (int m = 2; m >= 0; m--) r = cfma(a512[h], r, make_float2(__uint_as_float(u[m].x), __uint_as_float(u[m].y)));
            return r;
        };
        float2 w0[2];
#pragma unroll
        for (int h = 0; h < 2; h++) {
            float (&acc)[64] = h ? accB : accA;
            float2 e = make_float2(acc[0], acc[2]);
#pragma unroll
            for (int s = 1; s < 32; s++) {
                const int i0 = 4 * (s >> 1) + (s & 1);
                e = cfma(a[h], e, make_float2(acc[i0], acc[i0 + 2]));
                if (!GREEDY && h == 1 && s == POLL_S) { cut(); poll(v[0], 0); }
            }
            float2 y = make_float2(__shfl_up_sync(0xffffffffu, e.x, 1, 4), __shfl_up_sync(0xffffffffu, e.y, 1, 4));
            if (c >= 1) e = cfma(a32[h], y, e);
            y = make_float2(__shfl_up_sync(0xffffffffu, e.x, 2, 4), __shfl_up_sync(0xffffffffu, e.y, 2, 4));
            if (c >= 2) e = cfma(a64[h], y, e);
            if (c == 3) st_relaxed2(cq + 4096 + 256 * h, (__float_as_uint(e.x) & ~3u) | t2, (__float_as_uint(e.y) & ~3u) | t2);
            if (h || !GREEDY) cut();
            w0[h] = make_float2(__shfl_up_sync(0xffffffffu, e.x, 1, 4), __shfl_up_sync(0xffffffffu, e.y, 1, 4));
            STAMPIF(at == 0 && (h || !GREEDY), 31 + h + 10 * wg);
        }
        if (GREEDY) { __nanosleep(100); poll(v[0], 0); __nanosleep(100); }
        uint32_t sx[2][16], sy[2][16], mr[2][4], tp;
        const uint32_t gap = wg ? TN(GAP1) : TN(GAP0);
#pragma unroll
        for (int h = 0; h < 2; h++) {
            const uint32_t sg = prm.swapped ? 0x80008000u : 0u;
            mr[h][0] = __byte_perm(mm[h], 0, 0x1010); mr[h][1] = __byte_perm(mm[h], 0, 0x3232);
            mr[h][2] = mr[h][1] ^ sg; mr[h][3] = mr[h][0] ^ sg ^ 0x80008000u;
        }
        auto put = [&](int e, int j) {
            uint32_t d[4];
#pragma unroll
            for (int u = 0; u < 4; u++) d[u] = fma_bf2(mr[e >> 1][2 * (e & 1)], sx[e >> 1][4 * j + u], mul_bf2(mr[e >> 1][2 * (e & 1) + 1], sy[e >> 1][4 * j + u]));
            #pragma unroll
            for (int u = 0; u < 2; u++)
                asm("lop3.b32 %0, %0, %1, %2, 0xD8;" : "+r"(d[2 * (j & 1) + u]) : "r"(par), "r"((uint32_t)((w & 1) == u)));
            stg128(hd + e * 65536 + (j >> 1) * 8192 + (j & 1) * 512, d[0], d[1], d[2], d[3]);
            if (j == 3 && lane == 0) mbar_arrive(bar_out + 32 * wg + 8 * e);
        };
#pragma unroll
        for (int h = 0; h < 2; h++) {
            float (&acc)[64] = h ? accB : accA;
            float2 hin;
            uint32_t it = 0;
            if (h == 0 && DOUBLE) {
                while (true) {
                    poll(v[1], 0);
                    if (valid(v[0])) { hin = horner(v[0], 0); break; }
                    poll(v[0], 0);
                    if (valid(v[1])) { hin = horner(v[1], 0); it++; break; }
                    if (++it > SPIN_LIMIT) __trap();
                }
            } else {
                while (!valid(v[0])) {
                    poll(v[0], h);
                    if (++it > SPIN_LIMIT) __trap();
                }
                hin = horner(v[0], h);
            }
            STAMPIF(at == 0 && it > 0 && h == 0, 39 + 10 * wg);
            if (c) hin = cmul(pw128[h], hin);
            hin.x += __shfl_xor_sync(0xffffffffu, hin.x, 1); hin.y += __shfl_xor_sync(0xffffffffu, hin.y, 1);
            hin.x += __shfl_xor_sync(0xffffffffu, hin.x, 2); hin.y += __shfl_xor_sync(0xffffffffu, hin.y, 2);
            float2 st = hin;
            if (c) st = cfma(pw32[h], hin, w0[h]);
            STAMPIF(at == 0, 33 + 3 * h + 10 * wg);
#pragma unroll
            for (int j = 0; j < 4; j++) {
#pragma unroll
                for (int u = 0; u < 4; u++) {
                    const int i0 = 16 * j + 4 * u;
                    const float2 y = cfma(a[h], st, make_float2(acc[i0], acc[i0 + 2]));
                    st = cfma(a[h], y, make_float2(acc[i0 + 1], acc[i0 + 3]));
                    sx[h][4 * j + u] = pack_bf(y.x, st.x); sy[h][4 * j + u] = pack_bf(y.y, st.y);
                }
                if (h) sleep_until(tp += gap);
                if (h == 0 && j == RAISE_J) poll(v[0], 1);
                put(2 * h, j);
                cut();
            }
            STAMPIF(at == 0, 34 + 3 * h + 10 * wg);
            tp = clk32();
#pragma unroll
            for (int j = 0; j < 4; j++) {
                sleep_until(tp += gap);
                put(2 * h + 1, j);
            }
        }
        STAMPIF(at == 0, 38 + 10 * wg);

        if (wg == 1) {
            const char* src = reinterpret_cast<const char*>(prm.s->h) + (size_t)chunk * 524288;
            uint32_t rpar = 1;
#pragma unroll 1
            for (int i = CH1 + w; i < NBIG; i += 4) {
                const uint32_t slot = i % NST;
                mbar_wait(empty + 8 * (i - NST));
                mbar_wait(hfull + 8 * slot, (i - 32) / NST & 1);
                rpar = check_tile<16>(sb, sb + slot * SLOT, probe, src + (i - 32) * 2 * TILE, par, full + 8 * w, rpar, TN(T_RETRY));
                if (lane == 0) mbar_expect_tx(full + 8 * i, 2 * TILE);
            }
#pragma unroll 1
            for (int n = w; n < 16; n += 4) {
                mbar_wait(empty + 8 * (NBIG - 7 + n));
                mbar_wait(hfull + 8 * (NST + n % 7), n / 7 & 1);
                const uint32_t dst = sb + tail_h(n);
                rpar = check_tile<8>(sb, dst, probe, src + (24 + (n & 7)) * 2 * TILE + (n >> 3) * TILE, par, full + 8 * w, rpar, TN(T_RETRY));
                if (lane == 0) mbar_expect_tx(full + 8 * (NBIG + n), n < 8 ? 2 * TILE : 0);
            }
        } else {
            asm volatile("setmaxnreg.inc.sync.aligned.u32 216;");
            const int tl = 64 * (w & 1) + 8 * (w >> 1) + g;
            float gf[4];
            float* op = prm.out + (size_t)(chunk * 128 + tl) * D_ + dt * 128 + 4 * c;
            const int xr = 2 * (g & 3) + (g >> 2);
            uint32_t xs = sb + OFF_FT + (32 * (w & 1) + 8 * (w >> 1) + xr) * 128 + (((c >> 1) ^ xr) << 4) + (c & 1) * 8;
            uint32_t gs = sb + OFF_G + 2 * tl;
            asm volatile("" : "+r"(gs), "+l"(op), "+r"(xs));
            float outA[64], outB[64];
            STAMPIF(at == 0, 9);
            mbar_wait(bar_order + 8);
            STAMPIF(at == 0, 35);
            if (TN(GT2)) sched_fence(lds32(sb + OFF_EPOCH + 8) + TN(GT2));
            run_entries<1>(sb, 32, NBIG, 32 % NST, outA, outB, [](int) {});
            uint32_t gp[4], om[4];
            uint2 xt[4][8], dk[8];
            auto load_x = [&](int q, int j) {
#pragma unroll
                for (int r = 0; r < 2; r++) xt[2 * q + r][j] = lds64((xs ^ ((j & 3) << 5)) + (5 * q + (j >> 2)) * TILE + r * 2048);
                if (q == 0) dk[j] = lds64(sb + OFF_DK + c * 8 + 32 * j);
            };
            auto term = [&](int q, int j) {
#pragma unroll
                for (int r = 2 * q; r < 2 * q + 2; r++) {
                    xt[r][j].x = mul_bf2(xt[r][j].x, fma_bf2(gp[r], dk[j].x, om[r]));
                    xt[r][j].y = mul_bf2(xt[r][j].y, fma_bf2(gp[r], dk[j].y, om[r]));
                }
            };
            auto store = [&](int q, int j) {
                const float (&acc)[64] = q ? outB : outA;
#pragma unroll
                for (int r = 0; r < 2; r++) {
                    const int o = 8 * j + 2 * r;
                    const float gv = fabsf(gf[2 * q + r]);
                    const uint2 t = xt[2 * q + r][j];
                    stg128(op + (r * 32 + q * 16) * D_ + 16 * j, __float_as_uint(fmaf(gv, acc[o], bf_lo(t.x))), __float_as_uint(fmaf(gv, acc[o + 1], bf_hi(t.x))),
                           __float_as_uint(fmaf(gv, acc[o + 4], bf_lo(t.y))), __float_as_uint(fmaf(gv, acc[o + 5], bf_hi(t.y))));
                }
            };
            uint64_t dh = desc64<1>(make_desc_h(sb)), dc = desc64<0>(make_desc(sb));
#pragma unroll
            for (int n = 0; n < 16; n++) {
                const int j = n & 7;
                if (n == 0) mbar_wait(bar_g);
                if (n == X0 || n == 15) mbar_wait(bar_x + (n == 15 ? 8 : 0));
                mbar_wait(full + 8 * (NBIG + n));
                KSTAMP(NBIG + n);
                asm volatile("mov.b64 %0, %0; mov.b64 %1, %1;" : "+l"(dh), "+l"(dc));
                const uint64_t da = dh + (tail_h(n) >> 4), db = dc + (tail_c(j) >> 4);
                const int xj = n - X0;
                wgmma_fence();
#pragma unroll
                for (int kk = 0; kk < 4; kk++) {
                    wgmma_n128<1>(n < 8 ? outA : outB, da + kk * 128, db + kk * 2);
                    if (kk == 0 && n == 0) {
#pragma unroll
                        for (int r = 0; r < 4; r++) {
                            uint32_t u;
                            asm volatile("ld.shared.u16 %0, [%1];" : "=r"(u) : "r"(gs + (r & 1) * 64 + (r >> 1) * 32) : "memory");
                            gf[r] = bf_lo(u);
                        }
                    }
                    if (kk == 0 && xj >= 0 && xj < 8) load_x(0, xj);
                    if (kk == 0 && n == 15) load_x(1, 0);
                }
                wgmma_commit();
                if (n < 10) {
                    wgmma_wait<1>();
                    if (lane == 0) mbar_arrive(empty + 8 * (NBIG + n - 1));
                    if (!(n & 7)) { LSTAMP(at == 0, 96 + 12 + n / 8); GSTAMP(LT && at == 0, 195 + n / 8); }
                } else cut();
                if (n == 0) {
#pragma unroll
                    for (int r = 0; r < 4; r++) {
                        const bool routed = (int)__float_as_uint(gf[r]) < 0;
                        gp[r] = routed ? 0u : pack_bf(gf[r], gf[r]); om[r] = routed ? 0u : pack_bf(1.0f - gf[r], 1.0f - gf[r]);
                    }
                }
                if (xj >= 0 && xj < 8) term(0, xj);
                if (n == 8) pin64(outA);
                if (n >= 8) store(0, j);
            }
            term(1, 0);
            cut();
            wgmma_wait<0>();
            pin64(outB);
            LSTAMP(at == 0, 96 + 51); GSTAMP(LT && at == 0, 197);
#pragma unroll
            for (int j = 1; j < 8; j++) load_x(1, j);
            store(1, 0);
#pragma unroll
            for (int j = 1; j < 8; j++) {
                cut();
                term(1, j);
                store(1, j);
            }
            __syncwarp();
            if (lane == 0) mbar_arrive(bar_stored);
            LSTAMP(at == 0, 96 + 52);
        }
    } else if (warp < 12) {
        asm volatile("setmaxnreg.dec.sync.aligned.u32 64;");
        init_barriers();
#pragma unroll
        for (int i = 0; i < 2; i++) sts128(sb + OFF_LIST + i * 2048 + at * 16, 0u, 0u, 0u, 0u);
        uint32_t* keys = reinterpret_cast<uint32_t*>(smem + OFF_KEYS);
        keys[4] = 0;
        named_bar(0, 480);
        mbar_wait(bar_epoch);
        const uint32_t t2 = lds32(sb + OFF_EPOCH + 4);
        STAMPIF(at == 0, 20);
        float facc[4];
        const uint32_t dft = make_desc(sb + OFF_FT), dxs = make_desc(sb + OFF_XS);
#pragma unroll 1
        for (int u = 0; u < 4; u++) {
            mbar_wait(ffull + 8 * u);
            STAMPIF(at == 0, 4 + u);
            wgmma_fence();
            small_tile<0>(facc, dft + u * (TILE >> 4), dxs + u * 64, u == 0);
            wgmma_commit();
        }
        wgmma_wait<0>();
        pin4(facc);
        if (lane < 4) mbar_arrive(fempty + 8 * lane);
        auto gate_up = [&](auto rest) {
            uint32_t slot = 4, par = 0, prev = full + 8 * 80;
#pragma unroll 1
            for (int j = 0; j < 16; j++) {
                if (j == 2) rest();
                STAMPW(at == 0, 74 + j);
                mbar_wait(ffull + 8 * slot, par);
                STAMPW(at == 0, 160 + j);
                mbar_wait(empty + 8 * prm.use[j]);
                wgmma_fence();
                small_tile<1>(facc, dft + slot * (TILE >> 4), dxs + j * 64, j == 0);
                wgmma_commit();
                if (j < TN(NP)) { wgmma_wait<0>(); prev = fempty + 8 * slot; }
                else wgmma_wait<1>();
                if (lane == 0) mbar_arrive(prev);
                prev = j < TN(NP) ? full + 8 * 80 : fempty + 8 * slot;
                if (++slot == NFT) { slot = 0; par ^= 1; }
            }
            wgmma_wait<0>();
            if (lane == 0) mbar_arrive(prev);
            pin4(facc);
        };
        auto down = [&]() {
            const uint32_t dhid = make_desc(sb + OFF_HID);
#pragma unroll 1
            for (int j = 0; j < 7; j++) {
                mbar_wait(dfull + 8 * j);
                mbar_wait(empty + 8 * prm.use[16 + j]);
                wgmma_fence();
                small_tile<1>(facc, dft + j * (TILE >> 4), dhid + j * 64, j == 0);
                wgmma_commit();
                if ((0x52 >> j) & 1) {
                    wgmma_wait<0>();
                    if (lane == 0) mbar_arrive(bar_dfree + 8 * (j / 3));
                }
            }
            wgmma_wait<0>();
            pin4(facc);
        };
        if ((c & 1) == (w >> 1)) {
            float* red = reinterpret_cast<float*>(smem + OFF_RED) + w * 32 + (c >> 1) * 16 + g;
            red[0] = (w & 1) ? facc[1] : facc[0];
            red[8] = (w & 1) ? facc[3] : facc[2];
        }
        named_bar(2, 128);
        STAMPIF(at == 0, 21);
        const uint32_t tpub = clk32();
        if (w < 2) {
            const float* red = reinterpret_cast<const float*>(smem + OFF_RED) + w * 16 + (lane & 15);
            const float v = rbf((red[0] + red[32]) + (red[64] + red[96]));
            if (w == 0) {
                uint32_t k = __float_as_uint(v);
                k = ((k ^ ((uint32_t)((int)k >> 31) | 0x80000000u)) & 0xFFFF0000u) | (t2 << 11) | (2047u - (uint32_t)(rid * 16 + (lane & 15)));
                int rank = 0;
#pragma unroll
                for (int i = 0; i < 8; i++) rank += __shfl_sync(0xffffffffu, k, (lane >> 4) * 8 + i) > k;
                rank += __shfl_xor_sync(0xffffffffu, rank, 16);
                if (rank < 8) st_relaxed(&prm.s->key[cta * 8 + rank], k);
            } else if (lane < 16) st_relaxed(&prm.s->gate[rid * 16 + lane], __float_as_uint(rbf(sigmoidf_(v))) | t2);
            __syncwarp();
        }
        uint32_t it = 0;
        uint4 ka, kb4;
        sleep_until(tpub + TN(G0));
        while (true) {
            ka = ld_relaxed4(&prm.s->key[at * 8]);
            kb4 = ld_relaxed4(&prm.s->key[at * 8 + 4]);
            if (__all_sync(0xffffffffu, (((ka.x ^ (t2 << 11)) | (kb4.x ^ (t2 << 11))) & 0x1800u) == 0)) break;
            if (++it > SPIN_LIMIT) __trap();
        }
        STAMPIF(at == 0, 22);
        STAMPIF(at == 0 && it > 0, 23);
        const uint32_t m1 = __reduce_max_sync(0xffffffffu, ka.x), m2 = __reduce_max_sync(0xffffffffu, ka.x == m1 ? ka.y : ka.x);
        if (lane == 0) keys[w] = m2;
        named_bar(2, 128);
        const uint4 th4 = *reinterpret_cast<const uint4*>(keys);
        const uint32_t th = min(min(th4.x, th4.y), min(th4.z, th4.w));
        {
            const uint32_t k8[8] = {ka.x, ka.y, ka.z, ka.w, kb4.x, kb4.y, kb4.z, kb4.w};
            auto append = [&](int lo, int hi) {
                uint32_t n = 0, pos = 0;
#pragma unroll
                for (int i = lo; i < hi; i++) n += k8[i] >= th;
                asm volatile("{ .reg .pred p; setp.ne.u32 p, %2, 0; @p atom.shared.add.u32 %0, [%1], %2; }" : "+r"(pos) : "r"(sb + OFF_KEYS + 16), "r"(n) : "memory");
#pragma unroll
                for (int i = lo; i < hi; i++)
                    if (k8[i] >= th) reinterpret_cast<uint32_t*>(smem + OFF_LIST)[pos + i - lo] = k8[i];
            };
            append(0, 2);
            if (__any_sync(0xffffffffu, k8[2] >= th)) append(2, 8);
        }
        named_bar(2, 128);
        {
            const uint32_t* list = reinterpret_cast<const uint32_t*>(smem + OFF_LIST);
            const int n = (int)keys[4];
#pragma unroll 1
            for (int i0 = w * 32; i0 < n; i0 += 128) {
                const uint32_t k = list[i0 + lane];
                int rank = 0;
#pragma unroll 2
                for (int o = 0; o < n; o += 4) {
                    const uint4 l4 = *reinterpret_cast<const uint4*>(list + o);
                    rank += (l4.x > k) + (l4.y > k) + (l4.z > k) + (l4.w > k);
                }
                if (rank < 8) reinterpret_cast<uint32_t*>(smem + OFF_SEL)[rank] = k;
            }
        }
        named_bar(2, 128);
        STAMPIF(at == 0, 24);
        const uint32_t* sel = reinterpret_cast<const uint32_t*>(smem + OFF_SEL);
        auto gates = [&]() {
            uint32_t gv;
            it = 0;
            while (true) {
                gv = ld_relaxed(&prm.s->gate[chunk * 128 + at]);
                const uint32_t ar = ld_relaxed(&prm.s->armed[((cta >> 4) * 14 + min(lane, 13)) * 4]);
                if (__all_sync(0xffffffffu, (gv & 3u) == t2 && ar == t2)) break;
                if (++it > SPIN_LIMIT) __trap();
            }
            asm volatile("fence.acquire.gpu;" ::: "memory");
#pragma unroll
            for (int s = 0; s < 8; s++)
                if ((~sel[s] & 2047u) == (uint32_t)(chunk * 128 + at)) gv |= 0x80000000u;
            reinterpret_cast<uint16_t*>(smem + OFF_G)[at] = (uint16_t)(gv >> 16);
            __syncwarp();
            if (lane == 0) mbar_arrive(bar_g);
        };
        if (has_gu) {
            const int tk = (at >> 3) & 7;
            const char* xt = (const char*)prm.x + (~sel[tk] & 2047u) * 2048 + (at >> 6) * 128 + (at & 7) * 16;
#pragma unroll
            for (int i = 0; i < 8; i++) {
                cp_async16(sb + OFF_XS + (2 * i + (at >> 6)) * 1024 + tk * 128 + (((at & 7) ^ tk) << 4), xt + i * 256);
                if (i == 0 || i == 7) asm volatile("cp.async.commit_group;" ::: "memory");
            }
            asm volatile("cp.async.wait_group 1;" ::: "memory");
            fence_async_smem();
            named_bar(2, 128);
            STAMPIF(at == 0, 25);
            gate_up([&]() {
                asm volatile("cp.async.wait_all;" ::: "memory");
                fence_async_smem();
                named_bar(2, 128);
            });
            if (!(cta & 1)) {
#pragma unroll
                for (int u = 0; u < 4; u++) {
                    const float v = rbf(facc[u]);
                    facc[u] = __fdividef(v, 1.0f + __expf(-v));
                }
            }
            st_relaxed2(&prm.s->hid[cta * 128 + at], pack_bf(facc[0], facc[1]), pack_bf(facc[2], facc[3]));
        }
        STAMPIF(at == 0, 26);
        gates();
        {
            mbar_wait(empty + 8 * max(TN(HG), 31));
            const uint2* hp = &prm.s->hid[(cta >> 4) * 14 * 128 + at];
            uint32_t hv[16];
            it = 0;
            while (true) {
                uint32_t top = 0;
#pragma unroll
                for (int j = 0; j < 7; j++) {
                    const uint2 hg = ld_relaxed2(hp + 256 * j), hu = ld_relaxed2(hp + 256 * j + 128);
                    top = max(top, max(hg.x, hu.x));
                    hv[2 * j] = mul_bf2(hg.x, hu.x); hv[2 * j + 1] = mul_bf2(hg.y, hu.y);
                }
                if (__all_sync(0xffffffffu, top != ~0u)) break;
                do {
                    if (++it > SPIN_LIMIT) __trap();
                } while (!__all_sync(0xffffffffu, ld_relaxed(hp + min(lane, 13) * 128 - lane) != ~0u));
            }
            STAMPIF(at == 0 && it > 0, 61);
            hv[14] = hv[15] = 0;
#pragma unroll
            for (int j = 0; j < 4; j++)
                asm volatile("stmatrix.sync.aligned.m8n8.x4.trans.shared.b16 [%0], {%1, %2, %3, %4};" ::"r"(
                                 sb + OFF_HID + (2 * j + (lane >> 4)) * 1024 + (lane & 7) * 128 + (((2 * w + ((lane >> 3) & 1)) ^ (lane & 7)) << 4)),
                             "r"(hv[4 * j]), "r"(hv[4 * j + 1]), "r"(hv[4 * j + 2]), "r"(hv[4 * j + 3]) : "memory");
        }
        fence_async_smem();
        named_bar(2, 128);
        STAMPIF(at == 0, 27);
        uint32_t mine = __ballot_sync(0xffffffffu, lane < 8 && (int)((~sel[lane & 7] & 2047u) >> 7) == chunk), tr;
        uint2 xr, xd;
        float gr, rs;
        auto skip = [&](int n) {
#pragma unroll 1
            for (int i = 0; i < n; i++) mine &= mine - 1;
            if (mine) {
                const uint32_t key = sel[__ffs(mine) - 1], kb = key >> 16;
                tr = ~key & 2047u;
                xr = __ldg(reinterpret_cast<const uint2*>(prm.x + (size_t)tr * D_ + dt * 128) + lane);
                rs = rbf(sigmoidf_(bf_lo((kb & 0x8000u) ? (kb & 0x7FFFu) : (~kb & 0xFFFFu))));
                gr = fabsf(__bfloat162float(reinterpret_cast<const __nv_bfloat16*>(smem + OFF_G)[tr & 127]));
                xd = lds64(sb + OFF_DK + 8 * lane);
            }
        };
        skip(w);
        down();
#pragma unroll
        for (int u = 0; u < 4; u++)
            st_relaxed(&prm.s->y[((2 * c + (u & 1)) * 8 + (cta >> 4)) * D_ + (cta & 15) * 64 + w * 16 + g + 8 * (u >> 1)], (__float_as_uint(facc[u]) & ~3u) | t2);
        STAMPIF(at == 0, 28);
        sleep_until(clk32() + TN(T_Y));
        while (mine) {
            const uint32_t* yp = &prm.s->y[(__ffs(mine) - 1) * 8 * D_ + dt * 128 + 4 * lane];
            float y[4];
            it = 0;
            while (true) {
                uint32_t bad = 0;
                y[0] = y[1] = y[2] = y[3] = 0.f;
#pragma unroll
                for (int ks = 0; ks < 8; ks++) {
                    const uint4 v = ld_relaxed4(yp + ks * D_);
                    bad |= v.x ^ t2;
                    y[0] += __uint_as_float(v.x); y[1] += __uint_as_float(v.y); y[2] += __uint_as_float(v.z); y[3] += __uint_as_float(v.w);
                }
                if (__all_sync(0xffffffffu, (bad & 3u) == 0)) break;
                if (++it > SPIN_LIMIT) __trap();
            }
            STAMPIF(lane == 0 && it, 62);
#pragma unroll
            for (int u = 0; u < 4; u++) {
                const uint32_t x2 = (u & 2) ? xr.y : xr.x, d2 = mul_bf2(x2, (u & 2) ? xd.y : xd.x);
                y[u] = fmaf(gr, (u & 1) ? bf_hi(d2) : bf_lo(d2), rbf(rbf(1.0f - gr) * rbf(((u & 1) ? bf_hi(x2) : bf_lo(x2)) + rbf(rbf(y[u]) * rs))));
            }
            STAMPIF(lane == 0, 50);
            mbar_wait(bar_stored);
            asm volatile("red.global.add.v4.f32 [%0], {%1, %2, %3, %4};" ::"l"(prm.out + (size_t)tr * D_ + dt * 128 + 4 * lane), "f"(y[0]), "f"(y[1]), "f"(y[2]), "f"(y[3]) : "memory");
            skip(4);
        }
        LSTAMP(lane == 0, 96 + 29);
    } else {
        asm volatile("setmaxnreg.dec.sync.aligned.u32 40;");
        if (warp == 15) {
            prefetch_map(&mXr);
            named_bar(0, 480);
#pragma unroll 1
            for (int i = 0; i < 4; i++) {
                const int u = i;
                if (lane == 0) mbar_expect_tx(ffull + 8 * u, TILE);
                sleep_until(cstart + (i == 0 ? TN(RT0) : i == 1 ? TN(RT1) : i == 2 ? TN(RT2) : TN(RT3)));
                if (elect_one()) tma3(sb + OFF_FT + u * TILE, &mXr, u * 256, rid * 16, ffull + 8 * u);
                STAMP(53 + u);
            }
            const CUtensorMap* mw = (cta & 1) ? &mWu : &mWg;
            if (sb & 1023) __trap();
            prefetch_map(mw);
            prefetch_map(&mWd);
            uint32_t slot = 4, par = 1;
#pragma unroll 1
            for (int j = 0; j < (has_gu && DBG != 1 ? 16 : 0); j++) {
                mbar_wait(fempty + 8 * slot, par);
                if (lane == 0) mbar_expect_tx(ffull + 8 * slot, TILE);
                mbar_wait(empty + 8 * prm.fetch[j]);
                STAMPW(1, 176 + j);
                if (elect_one()) tma2(sb + OFF_FT + slot * TILE, mw, (cta >> 1) * 64, TN(WDBG) ? 0 : j * 64, ffull + 8 * slot);
                if (++slot == NFT) { slot = 0; par ^= 1; }
            }
            if (lane < 9) mbar_expect_tx(lane < 7 ? dfull + 8 * lane : bar_x + 8 * (lane - 7), lane < 7 ? TILE : 2 * TILE);
            if (!has_gu) mbar_wait(bar_g);
#pragma unroll 1
            for (int j = 0; j < (DBG != 1 ? 7 : 0); j++) {
                if (has_gu) mbar_wait(fempty + 8 * min(j, 4), 1);
                mbar_wait(empty + 8 * prm.fetch[16 + j]);
                if (elect_one()) tma2(sb + OFF_FT + j * TILE, &mWd, (cta & 15) * 64, (cta >> 4) * 448 + (TN(WDBG) ? 0 : j * 64), dfull + 8 * j);
            }
            prefetch_map(&mXe);
#pragma unroll 1
            for (int u = 0; u < 4; u++) {
                mbar_wait(bar_dfree + 8 * (u & 2));
                mbar_wait(empty + 8 * (TN(DN_E0) + u));
                if (elect_one())
                    asm volatile("cp.async.bulk.tensor.5d.shared::cluster.global.mbarrier::complete_tx::bytes [%0], [%1, {%3, %6, %6, %4, %5}], [%2];"
                                 ::"r"(sb + OFF_FT + (u < 2 ? u : u + 3) * TILE), "l"(&mXe), "r"(bar_x + 4 * (u & 2)), "r"(dt * 128 + (u & 1) * 64), "r"(u & 2), "r"(chunk * 4), "r"(0) : "memory");
            }
        } else if (warp == 13) {
#pragma unroll
            for (int u = 0; u < 8; u++) {
                const int row = (u >> 2) * 4 + (lane >> 3);
                cp_async16(sb + OFF_XS + (u & 3) * 1024 + row * 128 + (((lane & 7) ^ row) << 4), (const char*)(u < 4 ? prm.w_r : prm.gate_w) + (u & 3) * 512 + lane * 16);
            }
            STAMP(57);
            const uint32_t tag = ld_relaxed(&prm.s->epoch[cta]) + 1;
            named_bar(1, 64);
            *reinterpret_cast<uint2*>(smem + OFF_EPOCH) = make_uint2(tag, tag % 3u + 1u);
            STAMPIF(tag, 58);
            asm volatile("cp.async.wait_all;" ::: "memory");
            STAMP(59);
            fence_async_smem();
            __syncwarp();
            if (lane == 0) {
                mbar_arrive(bar_epoch);
                prm.s->epoch[cta] = tag;
            }
            sleep_until(cstart + TN(T_BASE));
            {
                const uint2 st = ld_relaxed2(&prm.s->start[2 * lane]);
                const uint32_t d = st.x - cstart + 512u, age = gtime32() - st.y;
                const uint32_t m = __reduce_max_sync(0xffffffffu, d < 1024u && age < 4096u ? (d << 12) | age : 0u);
                const uint32_t late = (m & 4095u) - __reduce_min_sync(0xffffffffu, age);
                *reinterpret_cast<volatile uint32_t*>(smem + OFF_EPOCH + 8) = cstart + (m ? (m >> 12) - 512u + min(late, 256u) * TN(G_NS) / 4 : 0u);
                __syncwarp();
                if (lane == 0) mbar_arrive(bar_base);
                STAMP(60);
            }
            mbar_wait(bar_const);
            asm volatile("fence.acq_rel.gpu;" ::: "memory");
            if (lane < 4) st_relaxed2(&prm.s->armed[cta * 4 + lane], tag % 3u + 1u, 0u);
            prefetch_map(&mCre);
            prefetch_map(&mCim);
            const char* src = reinterpret_cast<const char*>(prm.s->h) + (size_t)chunk * 524288;
            uint32_t slot = 32 % NST, hpar = 0, rpar = 0;
#pragma unroll 1
            for (int i = 32; i < CH1; i++) {
                mbar_wait(hfull + 8 * slot, hpar);
                STAMPIF(i == 32 || i == 33, 14 + (i & 1));
                rpar = check_tile<16>(sb, sb + slot * SLOT, probe, src, tag, bar_retry, rpar, TN(T_RETRY));
                if (lane == 0) mbar_expect_tx(full + 8 * i, 2 * TILE);
                STAMPIF(i == 32 || i == 33, 16 + (i & 1));
                src += 2 * TILE;
                slot = slot == NST - 1 ? 0 : slot + 1;
                hpar ^= slot == 32 % NST;
            }
        } else if (warp == 14) {
            prefetch_map(&mPB);
            auto pf_c = [&](int k) { prefetch_slice(&mPC, 4 * (k >> 1), cta * 8 + (k & 1) * 4); };
            named_bar(0, 480);
            asm volatile("bar.arrive 1, 64;" ::: "memory");
            if (lane < 24) st_relaxed(lane < 8 ? &prm.s->key[cta * 8 + lane] : &prm.s->gate[rid * 16 + lane - 8], 0u);
#pragma unroll 1
            for (int k = TN(PF0) ? 0 : 1; k < 4; k++) {
                sleep_until(cstart + (k == 0 ? TN(PF0) : k == 1 ? TN(PF1) : k == 2 ? TN(PF2) : TN(PF3)));
                if (elect_one()) prefetch_slice(&mPB, 4 * k, cta * 4);
            }
#pragma unroll 1
            for (int k = 0; k < 4; k++) {
                mbar_wait(empty + 8 * (TN(PB_E0) + TN(PB_STEP) * k));
                if (elect_one()) prefetch_slice(&mPB, 4 * k, 512 + cta * 4);
            }
#pragma unroll 1
            for (int k = 0; k < TN(PC_N); k++) {
                mbar_wait(empty + 8 * min(TN(PC_E0) + TN(PC_STEP) * k / 2, 26));
                if (elect_one()) pf_c(k);
            }
            int pk = TN(PC_N), pe = TN(PC_E1);
            auto own_part = [&](int e) {
                if (!mbar_test(bar_out + 8 * e, 0)) {
                    mbar_wait(bar_out + 8 * e);
                    sleep_until(clk32() + TN(T_OWN));
                    STAMP(11);
                }
            };
            const char* src = reinterpret_cast<const char*>(prm.s->h) + (size_t)chunk * 524288;
            uint32_t slot = 32 % NST;
#pragma unroll 1
            for (int i = 32; i < NBIG; i++) {
                if (!(i & 3)) own_part((i - 32) >> 2);
                mbar_wait(empty + 8 * (i - NST));
                PSTAMP(i);
                if (elect_one()) {
                    mbar_expect_tx(hfull + 8 * slot, 2 * TILE);
                    bulk_load(sb + slot * SLOT, src, 2 * TILE, hfull + 8 * slot);
                }
                if (i == pe && pk < 8) {
                    if (elect_one()) pf_c(pk);
                    pk++; pe += TN(PC_S1);
                }
                src += 2 * TILE;
                slot = slot == NST - 1 ? 0 : slot + 1;
            }
#pragma unroll
            for (int k = 0; k < 14; k++) {
                if (k == 4) continue;
                if (k == 0 || k == 2) own_part(6 + k / 2);
                if (k == 2) mbar_wait(bar_dfree + 8);
                mbar_wait(empty + 8 * (NBIG - NST + k));
                if (elect_one()) {
#pragma unroll
                    for (int n = k < 5 ? 2 * k : k + 2; n < (k < 3 ? 2 * k + 2 : k == 3 ? 7 : k + 3); n++) {
                        mbar_expect_tx(hfull + 8 * (NST + n % 7), TILE);
                        bulk_load(sb + tail_h(n), src + (n & 7) * 2 * TILE + (n >> 3) * TILE, TILE, hfull + 8 * (NST + n % 7));
                    }
                }
            }
        } else {
            if (elect_one()) {
#pragma unroll
                for (int i = 0; i < NST; i++) mbar_init(full + 8 * i, 1);
                fence_mbar_init();
            }
            __syncwarp();
#pragma unroll 1
            for (int i = 0; i < NST; i++) {
                if (elect_one()) {
                    mbar_expect_tx(full + 8 * i, SLOT);
                    tma5b(sb + i * SLOT, &mB, i * 64, dt * 4, full + 8 * i);
                    tma4(sb + i * SLOT + 2 * TILE, &mX, i * 64, chunk * 64, full + 8 * i);
                }
                STAMPIF(i == 0, 1);
            }
            STAMP(2);
            named_bar(0, 480);
            uint32_t dst = sb;
#pragma unroll 1
            for (int i = NST; i < 32; i++) {
                if (lane == 0) mbar_expect_tx(full + 8 * i, SLOT);
                mbar_wait(empty + 8 * (i - NST));
                PSTAMP(i);
                if (elect_one()) {
                    tma5b(dst, &mB, (i & 15) * 64, (i >> 4) * 64 + dt * 4, full + 8 * i);
                    tma4(dst + 2 * TILE, &mX, (i & 15) * 64, chunk * 64, full + 8 * i);
                }
                dst = dst == sb + (NST - 1) * SLOT ? sb : dst + SLOT;
            }
#pragma unroll 1
            for (int i = 32; i < NBIG; i++) {
                mbar_wait(empty + 8 * (i - NST));
                if (elect_one()) tma5(dst + 2 * TILE, (i & 4) ? &mCim : &mCre, ((i & 3) + ((i >> 1) & 12)) * 64, dt * 8, full + 8 * i);
                dst = dst == sb + (NST - 1) * SLOT ? sb : dst + SLOT;
            }
            dst = sb + tail_c(0);
#pragma unroll 1
            for (int j = 0; j < 8; j++) {
                mbar_wait(empty + 8 * (NBIG - NST + 1 + (j >> 1)));
                if (elect_one()) tma5(dst, (j & 4) ? &mCim : &mCre, ((j & 3) + 12) * 64, dt * 8, full + 8 * (NBIG + j));
                dst = j == 5 ? sb : dst + 2 * TILE;
            }
        }
    }
}

typedef CUresult (*EncodeFn)(CUtensorMap*, CUtensorMapDataType, cuuint32_t, void*, const cuuint64_t*, const cuuint64_t*, const cuuint32_t*,
                             const cuuint32_t*, CUtensorMapInterleave, CUtensorMapSwizzle, CUtensorMapL2promotion, CUtensorMapFloatOOBfill);

bool encode(EncodeFn fn, CUtensorMap* m, const void* ptr, int rank, const cuuint64_t* dims, const cuuint64_t* strides, const cuuint32_t* box,
            CUtensorMapL2promotion promo = CU_TENSOR_MAP_L2_PROMOTION_NONE) {
    const cuuint32_t es[5] = {1, 1, 1, 1, 1};
    return fn(m, CU_TENSOR_MAP_DATA_TYPE_BFLOAT16, rank, const_cast<void*>(ptr), dims, strides, box, es, CU_TENSOR_MAP_INTERLEAVE_NONE,
              CU_TENSOR_MAP_SWIZZLE_128B, promo, CU_TENSOR_MAP_FLOAT_OOB_FILL_NONE) == CUDA_SUCCESS;
}

}

extern "C" void kernel_launch(void* const* d_in, const int* in_sizes, int n_in, void* d_out, int out_size) {
    (void)in_sizes; (void)n_in; (void)out_size;
    Params prm;
    prm.x = (const __nv_bfloat16*)d_in[0];
    prm.lam_re = (const __nv_bfloat16*)d_in[1];
    prm.lam_im = (const __nv_bfloat16*)d_in[2];
    prm.b_re = (const __nv_bfloat16*)d_in[3];
    prm.b_im = (const __nv_bfloat16*)d_in[4];
    prm.c_re = (const __nv_bfloat16*)d_in[5];
    prm.c_im = (const __nv_bfloat16*)d_in[6];
    prm.log_dt = (const __nv_bfloat16*)d_in[7];
    prm.dskip = (const __nv_bfloat16*)d_in[8];
    prm.w_r = (const __nv_bfloat16*)d_in[10];
    prm.gate_w = (const __nv_bfloat16*)d_in[14];
    prm.out = (float*)d_out;
    cudaGetSymbolAddress((void**)&prm.s, g_scratch);
    prm.swapped = prm.b_im < prm.b_re;

    void* fnp = nullptr;
    cudaDriverEntryPointQueryResult qr;
    cudaGetDriverEntryPoint("cuTensorMapEncodeTiled", &fnp, cudaEnableDefault, &qr);
    EncodeFn fn = (EncodeFn)fnp;
    cudaFuncSetAttribute(fused_kernel, cudaFuncAttributeMaxDynamicSharedMemorySize, SMEM_BYTES);

    CUtensorMap mX, mB, mCre, mCim, mWg, mWu, mWd, mXr, mPB, mPC, mXe;
    const cuuint64_t row = 2048;
    {
        const cuuint64_t dims[4] = {1024, 2, 4, 976}, st[3] = {row, 32 * row, 2 * row};
        const cuuint32_t box[4] = {64, 2, 4, 16};
        encode(fn, &mX, prm.x, 4, dims, st, box, PROMO);
    }
    {
        const char *lo = (const char*)(prm.swapped ? prm.b_im : prm.b_re), *hi = (const char*)(prm.swapped ? prm.b_re : prm.b_im);
        const cuuint64_t dims[5] = {1024, 8, 2, 96, 2}, st[4] = {row, (cuuint64_t)(hi - lo), 8 * row, 256 * row};
        const cuuint32_t box[5] = {64, 8, 2, 4, 2};
        encode(fn, &mB, lo, 5, dims, st, box, PROMO);
    }
    {
        const cuuint64_t dims[5] = {1024, 2, 4, 2, 64}, st[4] = {row, 4 * row, 2 * row, 16 * row};
        const cuuint32_t box[5] = {64, 2, 4, 2, 8};
        encode(fn, &mCre, prm.c_re, 5, dims, st, box);
        encode(fn, &mCim, prm.c_im, 5, dims, st, box);
    }
    {
        const cuuint64_t dims[2] = {F_, D_}, st[1] = {F_ * 2}, dimsd[2] = {D_, F_}, std_[1] = {row};
        const cuuint32_t box[2] = {64, 64};
        encode(fn, &mWg, d_in[11], 2, dims, st, box);
        encode(fn, &mWu, d_in[12], 2, dims, st, box);
        encode(fn, &mWd, d_in[13], 2, dimsd, std_, box);
    }
    for (int i = 0; i < 2; i++) {
        const char *p = (const char*)(i ? prm.c_re : prm.b_re), *q = (const char*)(i ? prm.c_im : prm.b_im);
        const cuuint64_t dims[4] = {64, 16, 1024, 2}, st[3] = {128, row, (cuuint64_t)(p < q ? q - p : p - q)};
        const cuuint32_t box[4] = {16, 4, 4, 2};
        encode(fn, i ? &mPC : &mPB, p < q ? p : q, 4, dims, st, box, CU_TENSOR_MAP_L2_PROMOTION_L2_128B);
    }
    {
        const cuuint64_t dims[3] = {D_ - 192, S_, 4}, st[2] = {row, 128};
        const cuuint32_t box[3] = {64, 16, 4};
        encode(fn, &mXr, prm.x, 3, dims, st, box);
    }
    {
        const cuuint64_t dims[5] = {1024, 2, 4, 4, S_ / 32}, st[4] = {4 * row, row, 8 * row, 32 * row};
        const cuuint32_t box[5] = {64, 2, 4, 2, 4};
        encode(fn, &mXe, prm.x, 5, dims, st, box);
    }
    for (int j = 0, e4 = 4 * TN(GC0); j < 23; j++) {
        prm.fetch[j] = j < NFT ? TN(GU_E0) + j * TN(W_NUM) / 4 : j < 16 ? 0 : TN(DL0) + (j - 16) * TN(DLS) / 4;
        prm.use[j] = j < 16 ? e4 / 4 : TN(DC0) + (j - 16) * TN(DCS) / 4;
        const int last = 54;
        if (prm.fetch[j] > last) prm.fetch[j] = last;
        if (prm.use[j] > last) prm.use[j] = last;
        e4 += j < TN(N1) ? TN(GCS) : j < TN(N2) ? TN(GCS2) : j < 10 ? TN(GCS3) : TN(GCS4);
    }
    fused_kernel<<<NCTA, 512, SMEM_BYTES, cudaStreamPerThread>>>(prm, mX, mB, mCre, mCim, mWg, mWu, mWd, mXr, mPB, mPC, mXe);
}
```

```cpp
#include <cuda_runtime.h>
#include <cuda_bf16.h>
#include <cuda.h>
#include <stdint.h>

namespace {

constexpr int S_ = 2048, D_ = 1024, F_ = 3584;
constexpr int NCTA = 128;
constexpr int NBIG = 56, NENT = 72;
constexpr int NST = 5;
constexpr int NFT = 5;
constexpr uint32_t SLOT = 32768, TILE = 8192;
constexpr uint32_t OFF_FT = NST * SLOT;
constexpr uint32_t OFF_XS = OFF_FT + NFT * TILE;
constexpr uint32_t OFF_LIST = OFF_XS + 8192;
constexpr uint32_t OFF_RED = OFF_XS + 4096;
constexpr uint32_t OFF_CONST = OFF_XS + 16384;
constexpr uint32_t OFF_M = OFF_CONST + 8192, OFF_ONE = OFF_M + 512;
constexpr uint32_t OFF_HID = OFF_CONST;
constexpr uint32_t OFF_G = OFF_ONE + 16;
constexpr uint32_t OFF_DK = OFF_G + 256;
constexpr uint32_t OFF_FULL = OFF_DK + 256;
constexpr uint32_t OFF_EMPTY = OFF_FULL + 102 * 8;
constexpr uint32_t OFF_KEYS = OFF_EMPTY + 86 * 8;
constexpr uint32_t OFF_SEL = OFF_KEYS + 32;
constexpr uint32_t OFF_EPOCH = OFF_SEL + 32;
constexpr uint32_t OFF_PROF = OFF_EPOCH + 16;
constexpr uint32_t SMEM_BYTES = OFF_PROF + 432;
static_assert(SMEM_BYTES <= 232448, "smem");

static_assert(NBIG % NST == 1, "tail layout");
__host__ __device__ constexpr uint32_t tail_c(int j) { return j < 6 ? 2 * SLOT + j * 2 * TILE : (j - 6) * 2 * TILE; }
__host__ __device__ constexpr uint32_t tail_h(int n) { return n % 7 < 4 ? SLOT + n % 7 * TILE : OFF_FT + (n % 7 - 2) * TILE; }

constexpr uint32_t SPIN_LIMIT = 1u << 18;

struct Scratch {
    uint2 carry[16 * 1024];
    uint2 hid[NCTA * 128];
    uint32_t y[8 * 8 * D_];
    uint32_t key[NCTA * 8];
    uint32_t gate[S_];
    uint2 armed[NCTA * 4];
    unsigned int epoch[256];
    uint4 start[32 * 2];
    uint4 h[16 * 32 * 1024];
};
__device__ __align__(1024) Scratch g_scratch;
#define STAMPW_(cond, w) do {} while (0)
#define GSTAMP(cond, w) do {} while (0)
#define LSTAMP(cond, w) STAMPW_(cond, w)
#define LT 0
#define STAMPW(cond, w) STAMPW_(cond, w)
#define STAMPIF(cond, i) STAMPW(cond, 96 + (i))
#define STAMP(i) STAMPW(1, 96 + (i))
#define KSTAMP(i) STAMPW((threadIdx.x & 127) == 0, i)
#define PSTAMP(i) STAMPW((i) < 56 && (i) >= 32, 160 + (i))

struct Params {
    const __nv_bfloat16 *x, *b_re, *b_im, *lam_re, *lam_im, *c_re, *c_im, *log_dt, *dskip, *w_r, *gate_w;
    float* out;
    Scratch* s;
    int fetch[23], use[23];
    int swapped;
};

__device__ __forceinline__ uint32_t smem_u32(const void* p) { return (uint32_t)__cvta_generic_to_shared(p); }
__device__ __forceinline__ void mbar_init(uint32_t bar, uint32_t cnt) { asm volatile("mbarrier.init.shared::cta.b64 [%0], %1;" ::"r"(bar), "r"(cnt) : "memory"); }
__device__ __forceinline__ void mbar_expect_tx(uint32_t bar, uint32_t bytes) { asm volatile("mbarrier.arrive.expect_tx.shared::cta.b64 _, [%0], %1;" ::"r"(bar), "r"(bytes) : "memory"); }
__device__ __forceinline__ void mbar_arrive(uint32_t bar) { asm volatile("mbarrier.arrive.shared::cta.b64 _, [%0];" ::"r"(bar) : "memory"); }
__device__ __forceinline__ bool mbar_try(uint32_t bar, uint32_t parity) {
    uint32_t ok;
    asm volatile("{ .reg .pred p; mbarrier.try_wait.parity.shared::cta.b64 p, [%1], %2; selp.u32 %0, 1, 0, p; }" : "=r"(ok) : "r"(bar), "r"(parity) : "memory");
    return ok;
}
__device__ __forceinline__ bool mbar_test(uint32_t bar, uint32_t parity) {
    uint32_t ok;
    asm volatile("{ .reg .pred p; mbarrier.test_wait.parity.shared::cta.b64 p, [%1], %2; selp.u32 %0, 1, 0, p; }" : "=r"(ok) : "r"(bar), "r"(parity) : "memory");
    return __all_sync(0xffffffffu, ok);
}
__device__ __forceinline__ void mbar_wait(uint32_t bar, uint32_t parity = 0) {
    if (mbar_try(bar, parity)) return;
#pragma unroll 1
    for (uint32_t it = 0; it < SPIN_LIMIT; ++it)
        if (mbar_try(bar, parity)) return;
    __trap();
}
__device__ __forceinline__ bool elect_one() {
    uint32_t pred;
    asm volatile("{ .reg .pred P; elect.sync _|P, 0xffffffff; selp.b32 %0, 1, 0, P; }" : "=r"(pred));
    return pred;
}
__device__ __forceinline__ void named_bar(int id, int n) { asm volatile("bar.sync %0, %1;" ::"r"(id), "r"(n) : "memory"); }
__device__ __forceinline__ void fence_mbar_init() { asm volatile("fence.mbarrier_init.release.cluster;" ::: "memory"); }
__device__ __forceinline__ void fence_async_smem() { asm volatile("fence.proxy.async.shared::cta;" ::: "memory"); }

__device__ __forceinline__ void bulk_load(uint32_t dst, const void* src, uint32_t bytes, uint32_t bar) {
    asm volatile("cp.async.bulk.shared::cluster.global.mbarrier::complete_tx::bytes [%0], [%1], %2, [%3];" ::"r"(dst), "l"(src), "r"(bytes), "r"(bar) : "memory");
}
__device__ __forceinline__ void cp_async16(uint32_t dst, const void* src) { asm volatile("cp.async.cg.shared.global [%0], [%1], 16;" ::"r"(dst), "l"(src) : "memory"); }
__device__ __forceinline__ void sts128(uint32_t a, uint32_t x, uint32_t y, uint32_t z, uint32_t w) {
    asm volatile("st.shared.v4.u32 [%0], {%1,%2,%3,%4};" ::"r"(a), "r"(x), "r"(y), "r"(z), "r"(w) : "memory");
}
__device__ __forceinline__ uint2 lds64(uint32_t a) {
    uint2 v;
    asm volatile("ld.shared.v2.u32 {%0,%1}, [%2];" : "=r"(v.x), "=r"(v.y) : "r"(a) : "memory");
    return v;
}
__device__ __forceinline__ uint32_t lds32(uint32_t a) {
    uint32_t v;
    asm volatile("ld.volatile.shared.u32 %0, [%1];" : "=r"(v) : "r"(a) : "memory");
    return v;
}
__device__ __forceinline__ void stg128(void* p, uint32_t x, uint32_t y, uint32_t z, uint32_t w) {
    asm volatile("st.global.v4.u32 [%0], {%1,%2,%3,%4};" ::"l"(p), "r"(x), "r"(y), "r"(z), "r"(w) : "memory");
}
__device__ __forceinline__ void st_relaxed(void* p, uint32_t x) { asm volatile("st.relaxed.gpu.global.b32 [%0], %1;" ::"l"(p), "r"(x) : "memory"); }
__device__ __forceinline__ void st_relaxed2(void* p, uint32_t x, uint32_t y) { asm volatile("st.relaxed.gpu.global.v2.b32 [%0], {%1, %2};" ::"l"(p), "r"(x), "r"(y) : "memory"); }
__device__ __forceinline__ void st_relaxed4(void* p, uint32_t x, uint32_t y, uint32_t z, uint32_t w) {
    asm volatile("st.relaxed.gpu.global.v4.b32 [%0], {%1, %2, %3, %4};" ::"l"(p), "r"(x), "r"(y), "r"(z), "r"(w) : "memory");
}
__device__ __forceinline__ uint32_t ld_relaxed(const void* p) {
    uint32_t v;
    asm volatile("ld.relaxed.gpu.global.b32 %0, [%1];" : "=r"(v) : "l"(p) : "memory");
    return v;
}
__device__ __forceinline__ uint2 ld_relaxed2(const void* p) {
    uint2 v;
    asm volatile("ld.relaxed.gpu.global.v2.b32 {%0, %1}, [%2];" : "=r"(v.x), "=r"(v.y) : "l"(p) : "memory");
    return v;
}
__device__ __forceinline__ uint4 ld_relaxed4(const void* p) {
    uint4 v;
    asm volatile("ld.relaxed.gpu.global.v4.b32 {%0, %1, %2, %3}, [%4];" : "=r"(v.x), "=r"(v.y), "=r"(v.z), "=r"(v.w) : "l"(p) : "memory");
    return v;
}
__device__ __forceinline__ uint32_t clk32() { uint32_t c; asm volatile("mov.u32 %0, %%clock;" : "=r"(c)); return c; }
__device__ __forceinline__ uint32_t gtime32() { uint32_t c; asm volatile("mov.u32 %0, %%globaltimer_lo;" : "=r"(c)); return c; }
__device__ __forceinline__ void sched_fence(uint32_t t) { while ((int)(clk32() - t) < 0) {} }
__device__ __forceinline__ void sleep_until(uint32_t t) { while ((int)(clk32() - t) < 0) __nanosleep(40); }

__device__ __forceinline__ void tma2(uint32_t dst, const CUtensorMap* m, int c0, int c1, uint32_t bar) {
    asm volatile("{ .reg .b64 pol; createpolicy.fractional.L2::evict_first.b64 pol;\n"
                 "cp.async.bulk.tensor.2d.shared::cluster.global.mbarrier::complete_tx::bytes.L2::cache_hint [%0], [%1, {%3, %4}], [%2], pol; }"
                 ::"r"(dst), "l"(m), "r"(bar), "r"(c0), "r"(c1) : "memory");
}
__device__ __forceinline__ void tma3(uint32_t dst, const CUtensorMap* m, int c0, int c1, uint32_t bar) {
    asm volatile("cp.async.bulk.tensor.3d.shared::cluster.global.mbarrier::complete_tx::bytes [%0], [%1, {%3, %4, %5}], [%2];"
                 ::"r"(dst), "l"(m), "r"(bar), "r"(c0), "r"(c1), "r"(0) : "memory");
}
__device__ __forceinline__ void tma4(uint32_t dst, const CUtensorMap* m, int c0, int c3, uint32_t bar) {
    asm volatile("cp.async.bulk.tensor.4d.shared::cluster.global.mbarrier::complete_tx::bytes [%0], [%1, {%3, %5, %5, %4}], [%2];"
                 ::"r"(dst), "l"(m), "r"(bar), "r"(c0), "r"(c3), "r"(0) : "memory");
}
__device__ __forceinline__ void tma5(uint32_t dst, const CUtensorMap* m, int c0, int c4, uint32_t bar) {
    asm volatile("cp.async.bulk.tensor.5d.shared::cluster.global.mbarrier::complete_tx::bytes [%0], [%1, {%3, %5, %5, %5, %4}], [%2];"
                 ::"r"(dst), "l"(m), "r"(bar), "r"(c0), "r"(c4), "r"(0) : "memory");
}
__device__ __forceinline__ void tma5b(uint32_t dst, const CUtensorMap* m, int c0, int c3, uint32_t bar) {
    asm volatile("cp.async.bulk.tensor.5d.shared::cluster.global.mbarrier::complete_tx::bytes [%0], [%1, {%3, %5, %5, %4, %5}], [%2];"
                 ::"r"(dst), "l"(m), "r"(bar), "r"(c0), "r"(c3), "r"(0) : "memory");
}
__device__ __forceinline__ void prefetch_l2(const void* p) { asm volatile("prefetch.global.L2 [%0];" ::"l"(p)); }
__device__ __forceinline__ void prefetch_slice(const CUtensorMap* m, int line, int row) {
    asm volatile("cp.async.bulk.prefetch.tensor.4d.L2.global [%0, {%3, %1, %2, %3}];" ::"l"(m), "r"(line), "r"(row), "r"(0) : "memory");
}
__device__ __forceinline__ void prefetch_map(const CUtensorMap* m) { asm volatile("prefetch.tensormap [%0];" ::"l"(m)); }
__device__ __forceinline__ uint32_t uni(uint32_t v) { return __shfl_sync(0xffffffffu, v, 0); }

__device__ __forceinline__ uint32_t make_desc(uint32_t addr) { return ((addr & 0x3FFFF) >> 4) | (1u << 16); }
__device__ __forceinline__ uint32_t make_desc_h(uint32_t addr) { return ((addr & 0x3FFFF) >> 4) | (32u << 16); }
template <int H> __device__ __forceinline__ uint64_t desc64(uint32_t lo) {
    uint64_t d;
    asm volatile("mov.b64 %0, {%1, %2};" : "=l"(d) : "r"(lo), "n"(64u | ((H ? 2u : 1u) << 30)));
    return d;
}
__device__ __forceinline__ void wgmma_fence() { asm volatile("wgmma.fence.sync.aligned;" ::: "memory"); }
__device__ __forceinline__ void wgmma_commit() { asm volatile("wgmma.commit_group.sync.aligned;" ::: "memory"); }
template <int N> __device__ __forceinline__ void wgmma_wait() { asm volatile("wgmma.wait_group.sync.aligned %0;" ::"n"(N) : "memory"); }

#define R8(d, i) "+f"(d[i]), "+f"(d[i + 1]), "+f"(d[i + 2]), "+f"(d[i + 3]), "+f"(d[i + 4]), "+f"(d[i + 5]), "+f"(d[i + 6]), "+f"(d[i + 7])
#define R64(d) R8(d, 0), R8(d, 8), R8(d, 16), R8(d, 24), R8(d, 32), R8(d, 40), R8(d, 48), R8(d, 56)
template <int TA>
__device__ __forceinline__ void wgmma_n128(float (&d)[64], uint64_t da, uint64_t db, int scale_d = 1) {
    asm volatile("{ .reg .pred p; setp.ne.b32 p, %66, 0;\n"
                 "wgmma.mma_async.sync.aligned.m64n128k16.f32.bf16.bf16 "
                 "{%0,%1,%2,%3,%4,%5,%6,%7,%8,%9,%10,%11,%12,%13,%14,%15,%16,%17,%18,%19,%20,%21,%22,%23,%24,%25,%26,%27,%28,%29,%30,%31,"
                 "%32,%33,%34,%35,%36,%37,%38,%39,%40,%41,%42,%43,%44,%45,%46,%47,%48,%49,%50,%51,%52,%53,%54,%55,%56,%57,%58,%59,%60,%61,%62,%63}, "
                 "%64, %65, p, 1, 1, %67, 0; }"
                 : R64(d)
                 : "l"(da), "l"(db), "r"(scale_d), "n"(TA));
}
__device__ __forceinline__ void pin4(float (&d)[4]) { asm volatile("" : "+f"(d[0]), "+f"(d[1]), "+f"(d[2]), "+f"(d[3])::"memory"); }
__device__ __forceinline__ void pin64(float (&d)[64]) { asm volatile("" : R64(d)::"memory"); }

template <int TA>
__device__ __forceinline__ void wgmma_n8(float (&d)[4], uint64_t da, uint64_t db, int scale_d = 1) {
    asm volatile("{ .reg .pred p; setp.ne.b32 p, %7, 0;\n"
                 "wgmma.mma_async.sync.aligned.m64n8k16.f32.bf16.bf16 {%0,%1,%2,%3}, %4, %5, p, 1, 1, %6, 0; }"
                 : "+f"(d[0]), "+f"(d[1]), "+f"(d[2]), "+f"(d[3])
                 : "l"(da), "l"(db), "n"(TA), "r"(scale_d));
}

__device__ __forceinline__ float bf_lo(uint32_t u) { return __uint_as_float(u << 16); }
__device__ __forceinline__ float bf_hi(uint32_t u) { return __uint_as_float(u & 0xFFFF0000u); }
__device__ __forceinline__ float rbf(float v) { return __bfloat162float(__float2bfloat16_rn(v)); }
__device__ __forceinline__ uint32_t pack_bf(float lo, float hi) {
    uint32_t r;
    asm("cvt.rn.bf16x2.f32 %0, %1, %2;" : "=r"(r) : "f"(hi), "f"(lo));
    return r;
}
__device__ __forceinline__ uint32_t mul_bf2(uint32_t a, uint32_t b) {
    uint32_t r;
    asm("mul.rn.bf16x2 %0, %1, %2;" : "=r"(r) : "r"(a), "r"(b));
    return r;
}
__device__ __forceinline__ uint32_t fma_bf2(uint32_t a, uint32_t b, uint32_t c) {
    uint32_t r;
    asm("fma.rn.bf16x2 %0, %1, %2, %3;" : "=r"(r) : "r"(a), "r"(b), "r"(c));
    return r;
}
__device__ __forceinline__ float2 cmul(float2 a, float2 b) { return make_float2(a.x * b.x - a.y * b.y, a.x * b.y + a.y * b.x); }
__device__ __forceinline__ float2 cfma(float2 a, float2 b, float2 c) {
    return make_float2(fmaf(a.x, b.x, fmaf(-a.y, b.y, c.x)), fmaf(a.x, b.y, fmaf(a.y, b.x, c.y)));
}
__device__ __forceinline__ float sigmoidf_(float v) { return __fdividef(1.0f, 1.0f + expf(-v)); }

#define SCHED_NAMES RT0, RT1, RT2, RT3, PF0, PF1, PF2, PF3, T_SMALL, T_INIT, T_X0, T_BASE, G_NS, GT0, GT1, GT2, G0, GAP0, GAP1, RS_E, \
    PB_E0, PB_STEP, PC_E0, PC_STEP, PC_N, PC_E1, PC_S1, GU_E0, W_NUM, GC0, N1, N2, GCS, GCS2, GCS3, GCS4, HG, DL0, DLS, DC0, DCS, DN_E0, WDBG, T_OWN, T_RETRY, NP, T_Y, T_W0, T_W3
enum { SCHED_NAMES, NTUNE };
constexpr int sched_default[NTUNE] = {
    2200, 2700, 3200, 3700,
    0, 1100, 1300, 2800,
    1000, 1000, 1, 2500, 3,
    6600, 0, 0,
    1500, 50, 50, 4,
    4, 1, 9, 4, 5, 50, 3,
    4, 9, 15, 6, 6, 7, 7, 7, 5, 43, 37, 8, 38, 1, 50,
    0, 1100, 200, 0, 700, 600, 1000};
template <int I> struct Sched { static constexpr int v = sched_default[I]; };
#define TN(i) (Sched<i>::v)
#define DBG 0
#define NKK 4
#define EARLY 1
#define TDBG 0
#define X0 2
#define CH1 52
#define GE 8
#define DOUBLE 0
#define RAISE_J 1
#define GREEDY 0
#define POLL_S 24
#define PROMO CU_TENSOR_MAP_L2_PROMOTION_L2_256B

template <int TA, class H>
__device__ __forceinline__ void run_entry(uint32_t lo32, uint32_t prev, int accumulate, float (&accA)[64], float (&accB)[64], H inside) {
    const uint64_t da = desc64<TA>(lo32), db = TA ? desc64<0>(lo32 + (2 * TILE >> 4) - (31u << 16)) : da + (2 * TILE >> 4);
    wgmma_fence();
#pragma unroll
    for (int kk = 0; kk < 4; kk++) {
        wgmma_n128<TA>(accA, da + kk * (TA ? 128 : 2), db + kk * 2, kk > 0 ? 1 : accumulate);
        wgmma_n128<TA>(accB, da + 512 + kk * (TA ? 128 : 2), db + kk * 2, kk > 0 ? 1 : accumulate);
        if (kk == 1) {
            wgmma_commit();
            wgmma_wait<1>();
            if ((threadIdx.x & 31) == 0) mbar_arrive(prev);
            inside();
        }
    }
    wgmma_commit();
}
template <int TA, class H>
__device__ __forceinline__ void run_entries(uint32_t sb, int lo, int hi, int slot, float (&accA)[64], float (&accB)[64], H after) {
    const uint32_t da0 = TA ? make_desc_h(sb) : make_desc(sb), dlast = da0 + (NST - 1) * (SLOT >> 4);
    uint32_t prev = sb + OFF_FULL + 8 * 100, bar = sb + OFF_FULL + 8 * lo, lo32 = da0 + slot * (SLOT >> 4);
    int accumulate = 0;
#pragma unroll 1
    for (int i = lo; i < hi; i++) {
        mbar_wait(bar);
        KSTAMP(i);
        run_entry<TA>(lo32, prev, accumulate, accA, accB, []() {});
        prev = bar + (OFF_EMPTY - OFF_FULL);
        bar += 8;
        lo32 = lo32 == dlast ? da0 : lo32 + (SLOT >> 4);
        accumulate = 1;
        after(i);
    }
}

template <int TA>
__device__ __forceinline__ void small_tile(float (&acc)[4], uint32_t alo, uint32_t blo, bool first) {
    const uint64_t da = desc64<0>(alo), db = desc64<0>(blo);
#pragma unroll
    for (int kk = 0; kk < 4; kk++) wgmma_n8<TA>(acc, da + kk * (TA ? 128 : 2), db + kk * 2, kk > 0 || !first);
}

template <int N>
__device__ __forceinline__ uint32_t check_tile(uint32_t sb, uint32_t dst, uint32_t probe, const char* src, uint32_t par, uint32_t bar, uint32_t phase, uint32_t pause) {
    if ((TDBG & 4) && N == 8) return phase;
#pragma unroll 1
    for (uint32_t it = 0; it < SPIN_LIMIT; it++) {
        uint32_t v[N], bad = 0;
#pragma unroll
        for (int u = 0; u < N; u++) v[u] = lds32(dst + probe + (u >> 1) * 2048 + (u & 1) * 256);
#pragma unroll
        for (int u = 0; u < N; u += 4)
            asm("{ .reg .b32 a, b; lop3.b32 a, %1, %2, %5, 0x7E; lop3.b32 b, %3, %4, %5, 0x7E; lop3.b32 %0, %0, a, b, 0xFE; }"
                : "+r"(bad) : "r"(v[u]), "r"(v[u + 1]), "r"(v[u + 2]), "r"(v[u + 3]), "r"(par));
        if (!__any_sync(0xffffffffu, bad & 1u)) return phase;
        STAMP(10);
        __nanosleep(pause);
        if (elect_one()) {
            mbar_expect_tx(bar, N * 1024);
            bulk_load(dst, src, N * 1024, bar);
        }
        mbar_wait(bar, phase);
        phase ^= 1;
    }
    __trap();
    return 0;
}

__global__ void __launch_bounds__(512, 1)
fused_kernel(const __grid_constant__ Params prm, const __grid_constant__ CUtensorMap mX, const __grid_constant__ CUtensorMap mB, const __grid_constant__ CUtensorMap mCre,
             const __grid_constant__ CUtensorMap mCim, const __grid_constant__ CUtensorMap mWg, const __grid_constant__ CUtensorMap mWu,
             const __grid_constant__ CUtensorMap mWd, const __grid_constant__ CUtensorMap mXr, const __grid_constant__ CUtensorMap mPB,
             const __grid_constant__ CUtensorMap mPC, const __grid_constant__ CUtensorMap mXe) {
    {
        const uint32_t t = threadIdx.x, b = blockIdx.x;
        const uint32_t row = t < 32 ? ((b & 60) * 2 + (b >> 6) * 4 + (b & 3)) * 16 + (t >> 1) : b * 4 + ((t >> 1) & 3);
        const char* base = (const char*)(t < 32 ? prm.x : t < 40 ? prm.b_re : prm.b_im);
        asm volatile("{ .reg .pred p; setp.lt.u32 p, %1, 48; @p prefetch.global.L2 [%0]; }" ::"l"(base + (row * 2048 + (t & 1) * 128)), "r"(t) : "memory");
    }
    extern __shared__ __align__(1024) uint8_t smem[];
    uint32_t sb;
    asm volatile("mov.u32 %0, %1;" : "=r"(sb) : "r"(smem_u32(smem)));
    const int tid = threadIdx.x, warp = __shfl_sync(0xffffffffu, tid >> 5, 0), lane = tid & 31;
    const int cta = blockIdx.x;
    const uint32_t cstart = clk32();
    const int chunk = (cta >> 2) & 15;
    const int dt = (cta >> 6) * 4 + (cta & 3);
    const int rid = chunk * 8 + dt;
    const bool has_gu = cta < 112;
    const uint32_t full = sb + OFF_FULL, empty = sb + OFF_EMPTY;
    const uint32_t ffull = full + 8 * 83, fempty = empty + 8 * 65;
    const uint32_t bar_epoch = full + 8 * 72, dfull = full + 8 * 73, bar_base = full + 8 * 101, bar_x = full + 8 * 81, bar_retry = full + 8 * 80, hfull = full + 8 * 88;
    const uint32_t bar_order = empty + 8 * 70, bar_const = empty + 8 * 85, bar_stored = empty + 8 * 72, bar_dfree = empty + 8 * 73,
                    bar_g = empty + 8 * 84, bar_out = empty + 8 * 76;
    const int w = warp & 3, g = lane >> 2, c = lane & 3, at = tid & 127;

    const uint32_t probe = (lane >> 3) * 32 + (g & 1) * 144 + (c & 1) * 520 + (c >> 1) * 1028;

    LSTAMP(tid == 0, 96);
    GSTAMP(tid == 0, 94);
    auto init_barriers = [&](uint32_t base, uint32_t cnt, auto n) {
        if (elect_one()) {
#pragma unroll
            for (int i = 0; i < n(); i++) mbar_init(base + 8 * i, cnt);
            fence_mbar_init();
        }
        __syncwarp();
    };
    if (warp != 12) {
        if (warp == 15 && !(cta & 3) && lane < 8) st_relaxed((uint32_t*)&prm.s->start[cta >> 1] + lane, (lane & 1) ? gtime32() : cstart);
        if (warp < 12) sleep_until(cstart + (warp < 4 ? TN(T_W0) : TN(T_INIT)));
    }
    if (warp < 8) {
        if (warp < 4) init_barriers(warp == 0 ? full + 40 : warp == 3 ? full + 8 * 97 : empty + 40 * (warp - 1), (warp + 1) & 2 ? 4 : 1, []() { return 5; });
        else init_barriers(full + min(80 + 176 * w, 8 * 75), 1, []() { return 22; });
        asm volatile("setmaxnreg.inc.sync.aligned.u32 192;");
        if (warp < 4) {
            named_bar(5, 160);
            asm volatile("bar.arrive 0, 480;" ::: "memory");
            asm volatile("bar.arrive 6, 160;" ::: "memory");
        } else named_bar(0, 480);
        const int wg = warp >> 2;
        const int p = wg * 512 + dt * 32 + w * 8 + g;
        uint32_t cp = sb + OFF_CONST + 8 * (wg * 64 + w * 8 + g), cw = cp + 1024 * c, cm = sb + OFF_M + 4 * (wg * 64 + w * 8 + g);
        const int j1 = chunk - 1 - c;
        uint2* cq = &prm.s->carry[j1 * 1024 + p];
        char* hd = reinterpret_cast<char*>(prm.s->h) + (size_t)chunk * 524288 + wg * 262144 + (dt >> 1) * 16384 + ((dt & 1) * 4 + w) * 1024 + g * 64 + ((c ^ (g >> 1)) << 4);
        const bool never = uni(cstart == 0 && sb == 0);
        asm volatile("" : "+l"(cq), "+l"(hd), "+r"(cp), "+r"(cw), "+r"(cm));
        float2 a[2], a32[2], a64[2], a512[2], pw32[2], pw128[2];
        uint32_t mm[2], t2, par;
        auto constants = [&](int h) {
            if (h) { t2 = lds32(sb + OFF_EPOCH + 4); par = lds32(sb + OFF_EPOCH); }
            auto ldc = [](uint32_t a) { const uint2 v = lds64(a); return make_float2(__uint_as_float(v.x), __uint_as_float(v.y)); };
            {
                a[h] = ldc(cp + 256 * h); a32[h] = ldc(cp + 256 * h + 1024); a64[h] = ldc(cp + 256 * h + 2048); a512[h] = ldc(cp + 256 * h + 7168);
                pw32[h] = ldc(cw + 256 * h);
                pw128[h] = ldc(cw + 256 * h + 3072);
                mm[h] = lds32(cm + 128 * h);
            }
        };
        if (wg == 1) {
            const int pc = w * 256 + dt * 32 + lane;
            const float lr = __bfloat162float(prm.lam_re[pc]), li = __bfloat162float(prm.lam_im[pc]), ld = __bfloat162float(prm.log_dt[pc]);
            const uint32_t dk = __ldg(reinterpret_cast<const uint32_t*>(prm.dskip + dt * 128) + (at & 63));
            reinterpret_cast<uint32_t*>(smem + OFF_DK)[at & 63] = dk;
            const float dtv = rbf(expf(ld));
            const float er = expf(dtv * lr);
            float sn, cs;
            sincosf(dtv * li, &sn, &cs);
            const float ar = er * cs, ai = er * sn;
            const float nr = ar - 1.0f, ni = ai;
            const bool big = fabsf(lr) >= fabsf(li);
            const float t = (big ? li : lr) / (big ? lr : li), dn = big ? lr + li * t : lr * t + li;
            const float cr = (big ? nr + ni * t : nr * t + ni) / dn, ci = (big ? ni - nr * t : ni * t - nr) / dn;
            float2* ct = reinterpret_cast<float2*>(smem + OFF_CONST) + at;
            float2 pw = make_float2(ar, prm.swapped ? -ai : ai);
            ct[0] = pw;
            const float mx = prm.swapped ? -2.f * ci : 2.f * cr, my = prm.swapped ? 2.f * cr : -2.f * ci;
            reinterpret_cast<uint32_t*>(smem + OFF_M)[at] = pack_bf(mx, my);
#pragma unroll
            for (int i = 0; i < 5; i++) pw = cmul(pw, pw);
#pragma unroll
            for (int i = 0; i < 2; i++) {
                const float2 p2 = cmul(pw, pw);
                ct[128 + 384 * i] = pw; ct[256 + 384 * i] = p2; ct[384 + 384 * i] = cmul(p2, pw);
                pw = cmul(p2, p2);
            }
            ct[896] = pw;
            mbar_wait(bar_epoch);
            __syncwarp();
            mbar_wait(empty + 8 * TN(RS_E));
            st_relaxed2(&prm.s->hid[cta * 128 + at], ~0u, ~0u);
            st_relaxed4(&prm.s->y[((at >> 4) * 8 + (cta >> 4)) * D_ + (cta & 15) * 64 + (at & 15) * 4], 0u, 0u, 0u, 0u);
            st_relaxed2(&prm.s->carry[chunk * 1024 + pc], 0u, 0u);
            __syncwarp();
            if (lane == 0) mbar_arrive(bar_const);

            STAMPIF(at == 0, 3);
            mbar_wait(bar_const);
            constants(0);
            constants(1);
            mbar_wait(bar_order);
        }

        float accA[64], accB[64];
        run_entries<0>(sb, wg * 16, wg * 16 + 15, wg, accA, accB, [&](int i) {
            if (i == GE - 1) {
                mbar_wait(bar_base);
                sched_fence(lds32(sb + OFF_EPOCH + 8) + TN(GT0));
            }
        });
        mbar_wait(full + 8 * (wg * 16 + 15));
        KSTAMP(wg * 16 + 15);
        if (wg == 0) {
            mbar_wait(bar_const);
            run_entry<0>(make_desc(sb), empty + 8 * 14, 1, accA, accB, [&]() { constants(0); constants(1); if (EARLY && lane == 0) mbar_arrive(bar_order); });
        } else run_entry<0>(make_desc(sb + SLOT), empty + 8 * 30, 1, accA, accB, [&]() { if (EARLY && lane == 0) mbar_arrive(bar_order + 8); });
        if (!EARLY && lane == 0) mbar_arrive(bar_order + 8 * wg);
        uint2 v[2][4];
#pragma unroll
        for (int m = 0; m < 8; m++) v[m >> 2][m & 3] = make_uint2(t2, t2);
        wgmma_wait<0>();
        pin64(accA); pin64(accB);
        if (lane == 0) mbar_arrive(empty + 8 * (wg * 16 + 15));
        LSTAMP(at == 0, 96 + 30 + 10 * wg); GSTAMP(LT && at == 0, 193 + wg);

        auto cut = [&]() { if (never) sched_fence(cstart); };
        auto poll = [&](uint2 (&u)[4], int h) {
#pragma unroll
            for (int m = 0; m < 4; m++)
                asm volatile("{ .reg .pred p; setp.ge.s32 p, %3, %4; @p ld.relaxed.gpu.global.v2.b32 {%0, %1}, [%2]; }"
                             : "+r"(u[m].x), "+r"(u[m].y) : "l"(cq + 256 * h - 4096 * m), "r"(j1), "r"(4 * m) : "memory");
        };
        auto check = [&](const uint2 (&u)[4]) {
            uint32_t bad = 0;
#pragma unroll
            for (int m = 0; m < 4; m++) bad |= (u[m].x ^ t2) | (u[m].y ^ t2);
            return bad;
        };
        auto valid = [&](const uint2 (&u)[4]) { return __all_sync(0xffffffffu, (check(u) & 3u) == 0); };

        auto horner = [&](const uint2 (&u)[4], int h) {
            float2 r = make_float2(__uint_as_float(u[3].x), __uint_as_float(u[3].y));
#pragma unroll
            for (int m = 2; m >= 0; m--) r = cfma(a512[h], r, make_float2(__uint_as_float(u[m].x), __uint_as_float(u[m].y)));
            return r;
        };
        float2 w0[2];
#pragma unroll
        for (int h = 0; h < 2; h++) {
            float (&acc)[64] = h ? accB : accA;
            float2 e = make_float2(acc[0], acc[2]);
#pragma unroll
            for (int s = 1; s < 32; s++) {
                const int i0 = 4 * (s >> 1) + (s & 1);
                e = cfma(a[h], e, make_float2(acc[i0], acc[i0 + 2]));
                if (!GREEDY && h == 1 && s == POLL_S) { cut(); poll(v[0], 0); }
            }
            float2 y = make_float2(__shfl_up_sync(0xffffffffu, e.x, 1, 4), __shfl_up_sync(0xffffffffu, e.y, 1, 4));
            if (c >= 1) e = cfma(a32[h], y, e);
            y = make_float2(__shfl_up_sync(0xffffffffu, e.x, 2, 4), __shfl_up_sync(0xffffffffu, e.y, 2, 4));
            if (c >= 2) e = cfma(a64[h], y, e);
            if (c == 3) st_relaxed2(cq + 4096 + 256 * h, (__float_as_uint(e.x) & ~3u) | t2, (__float_as_uint(e.y) & ~3u) | t2);
            if (h || !GREEDY) cut();
            w0[h] = make_float2(__shfl_up_sync(0xffffffffu, e.x, 1, 4), __shfl_up_sync(0xffffffffu, e.y, 1, 4));
            STAMPIF(at == 0 && (h || !GREEDY), 31 + h + 10 * wg);
        }
        if (GREEDY) { __nanosleep(100); poll(v[0], 0); __nanosleep(100); }
        uint32_t sx[2][16], sy[2][16], mr[2][4], tp;
        const uint32_t gap = wg ? TN(GAP1) : TN(GAP0);
#pragma unroll
        for (int h = 0; h < 2; h++) {
            const uint32_t sg = prm.swapped ? 0x80008000u : 0u;
            mr[h][0] = __byte_perm(mm[h], 0, 0x1010); mr[h][1] = __byte_perm(mm[h], 0, 0x3232);
            mr[h][2] = mr[h][1] ^ sg; mr[h][3] = mr[h][0] ^ sg ^ 0x80008000u;
        }
        auto put = [&](int e, int j) {
            uint32_t d[4];
#pragma unroll
            for (int u = 0; u < 4; u++) d[u] = fma_bf2(mr[e >> 1][2 * (e & 1)], sx[e >> 1][4 * j + u], mul_bf2(mr[e >> 1][2 * (e & 1) + 1], sy[e >> 1][4 * j + u]));
            #pragma unroll
            for (int u = 0; u < 2; u++)
                asm("lop3.b32 %0, %0, %1, %2, 0xD8;" : "+r"(d[2 * (j & 1) + u]) : "r"(par), "r"((uint32_t)((w & 1) == u)));
            stg128(hd + e * 65536 + (j >> 1) * 8192 + (j & 1) * 512, d[0], d[1], d[2], d[3]);
            if (j == 3 && lane == 0) mbar_arrive(bar_out + 32 * wg + 8 * e);
        };
#pragma unroll
        for (int h = 0; h < 2; h++) {
            float (&acc)[64] = h ? accB : accA;
            float2 hin;
            uint32_t it = 0;
            if (h == 0 && DOUBLE) {
                while (true) {
                    poll(v[1], 0);
                    if (valid(v[0])) { hin = horner(v[0], 0); break; }
                    poll(v[0], 0);
                    if (valid(v[1])) { hin = horner(v[1], 0); it++; break; }
                    if (++it > SPIN_LIMIT) __trap();
                }
            } else {
                while (!valid(v[0])) {
                    poll(v[0], h);
                    if (++it > SPIN_LIMIT) __trap();
                }
                hin = horner(v[0], h);
            }
            STAMPIF(at == 0 && it > 0 && h == 0, 39 + 10 * wg);
            if (c) hin = cmul(pw128[h], hin);
            hin.x += __shfl_xor_sync(0xffffffffu, hin.x, 1); hin.y += __shfl_xor_sync(0xffffffffu, hin.y, 1);
            hin.x += __shfl_xor_sync(0xffffffffu, hin.x, 2); hin.y += __shfl_xor_sync(0xffffffffu, hin.y, 2);
            float2 st = hin;
            if (c) st = cfma(pw32[h], hin, w0[h]);
            STAMPIF(at == 0, 33 + 3 * h + 10 * wg);
#pragma unroll
            for (int j = 0; j < 4; j++) {
#pragma unroll
                for (int u = 0; u < 4; u++) {
                    const int i0 = 16 * j + 4 * u;
                    const float2 y = cfma(a[h], st, make_float2(acc[i0], acc[i0 + 2]));
                    st = cfma(a[h], y, make_float2(acc[i0 + 1], acc[i0 + 3]));
                    sx[h][4 * j + u] = pack_bf(y.x, st.x); sy[h][4 * j + u] = pack_bf(y.y, st.y);
                }
                if (h) sleep_until(tp += gap);
                if (h == 0 && j == RAISE_J) poll(v[0], 1);
                put(2 * h, j);
                cut();
            }
            STAMPIF(at == 0, 34 + 3 * h + 10 * wg);
            tp = clk32();
#pragma unroll
            for (int j = 0; j < 4; j++) {
                sleep_until(tp += gap);
                put(2 * h + 1, j);
            }
        }
        STAMPIF(at == 0, 38 + 10 * wg);

        if (wg == 1) {
            const char* src = reinterpret_cast<const char*>(prm.s->h) + (size_t)chunk * 524288;
            uint32_t rpar = 1;
#pragma unroll 1
            for (int i = CH1 + w; i < NBIG; i += 4) {
                const uint32_t slot = i % NST;
                mbar_wait(empty + 8 * (i - NST));
                mbar_wait(hfull + 8 * slot, (i - 32) / NST & 1);
                rpar = check_tile<16>(sb, sb + slot * SLOT, probe, src + (i - 32) * 2 * TILE, par, full + 8 * w, rpar, TN(T_RETRY));
                if (lane == 0) mbar_expect_tx(full + 8 * i, 2 * TILE);
            }
#pragma unroll 1
            for (int n = w; n < 16; n += 4) {
                mbar_wait(empty + 8 * (NBIG - 7 + n));
                mbar_wait(hfull + 8 * (NST + n % 7), n / 7 & 1);
                const uint32_t dst = sb + tail_h(n);
                rpar = check_tile<8>(sb, dst, probe, src + (24 + (n & 7)) * 2 * TILE + (n >> 3) * TILE, par, full + 8 * w, rpar, TN(T_RETRY));
                if (lane == 0) mbar_expect_tx(full + 8 * (NBIG + n), n < 8 ? 2 * TILE : 0);
            }
        } else {
            asm volatile("setmaxnreg.inc.sync.aligned.u32 216;");
            const int tl = 64 * (w & 1) + 8 * (w >> 1) + g;
            float gf[4];
            float* op = prm.out + (size_t)(chunk * 128 + tl) * D_ + dt * 128 + 4 * c;
            const int xr = 2 * (g & 3) + (g >> 2);
            uint32_t xs = sb + OFF_FT + (32 * (w & 1) + 8 * (w >> 1) + xr) * 128 + (((c >> 1) ^ xr) << 4) + (c & 1) * 8;
            uint32_t gs = sb + OFF_G + 2 * tl;
            asm volatile("" : "+r"(gs), "+l"(op), "+r"(xs));
            float outA[64], outB[64];
            STAMPIF(at == 0, 9);
            mbar_wait(bar_order + 8);
            STAMPIF(at == 0, 35);
            if (TN(GT2)) sched_fence(lds32(sb + OFF_EPOCH + 8) + TN(GT2));
            run_entries<1>(sb, 32, NBIG, 32 % NST, outA, outB, [](int) {});
            uint32_t gp[4], om[4];
            uint2 xt[4][8], dk[8];
            auto load_x = [&](int q, int j) {
#pragma unroll
                for (int r = 0; r < 2; r++) xt[2 * q + r][j] = lds64((xs ^ ((j & 3) << 5)) + (5 * q + (j >> 2)) * TILE + r * 2048);
                if (q == 0) dk[j] = lds64(sb + OFF_DK + c * 8 + 32 * j);
            };
            auto term = [&](int q, int j) {
#pragma unroll
                for (int r = 2 * q; r < 2 * q + 2; r++) {
                    xt[r][j].x = mul_bf2(xt[r][j].x, fma_bf2(gp[r], dk[j].x, om[r]));
                    xt[r][j].y = mul_bf2(xt[r][j].y, fma_bf2(gp[r], dk[j].y, om[r]));
                }
            };
            auto store = [&](int q, int j) {
                const float (&acc)[64] = q ? outB : outA;
#pragma unroll
                for (int r = 0; r < 2; r++) {
                    const int o = 8 * j + 2 * r;
                    const float gv = fabsf(gf[2 * q + r]);
                    const uint2 t = xt[2 * q + r][j];
                    stg128(op + (r * 32 + q * 16) * D_ + 16 * j, __float_as_uint(fmaf(gv, acc[o], bf_lo(t.x))), __float_as_uint(fmaf(gv, acc[o + 1], bf_hi(t.x))),
                           __float_as_uint(fmaf(gv, acc[o + 4], bf_lo(t.y))), __float_as_uint(fmaf(gv, acc[o + 5], bf_hi(t.y))));
                }
            };
            uint64_t dh = desc64<1>(make_desc_h(sb)), dc = desc64<0>(make_desc(sb));
#pragma unroll
            for (int n = 0; n < 16; n++) {
                const int j = n & 7;
                if (n == 0) mbar_wait(bar_g);
                if (n == X0 || n == 15) mbar_wait(bar_x + (n == 15 ? 8 : 0));
                mbar_wait(full + 8 * (NBIG + n));
                KSTAMP(NBIG + n);
                asm volatile("mov.b64 %0, %0; mov.b64 %1, %1;" : "+l"(dh), "+l"(dc));
                const uint64_t da = dh + (tail_h(n) >> 4), db = dc + (tail_c(j) >> 4);
                const int xj = n - X0;
                wgmma_fence();
#pragma unroll
                for (int kk = 0; kk < 4; kk++) {
                    wgmma_n128<1>(n < 8 ? outA : outB, da + kk * 128, db + kk * 2);
                    if (kk == 0 && n == 0) {
#pragma unroll
                        for (int r = 0; r < 4; r++) {
                            uint32_t u;
                            asm volatile("ld.shared.u16 %0, [%1];" : "=r"(u) : "r"(gs + (r & 1) * 64 + (r >> 1) * 32) : "memory");
                            gf[r] = bf_lo(u);
                        }
                    }
                    if (kk == 0 && xj >= 0 && xj < 8) load_x(0, xj);
                    if (kk == 0 && n == 15) load_x(1, 0);
                }
                wgmma_commit();
                if (n < 10) {
                    wgmma_wait<1>();
                    if (lane == 0) mbar_arrive(empty + 8 * (NBIG + n - 1));
                    if (!(n & 7)) { LSTAMP(at == 0, 96 + 12 + n / 8); GSTAMP(LT && at == 0, 195 + n / 8); }
                } else cut();
                if (n == 0) {
#pragma unroll
                    for (int r = 0; r < 4; r++) {
                        const bool routed = (int)__float_as_uint(gf[r]) < 0;
                        gp[r] = routed ? 0u : pack_bf(gf[r], gf[r]); om[r] = routed ? 0u : pack_bf(1.0f - gf[r], 1.0f - gf[r]);
                    }
                }
                if (xj >= 0 && xj < 8) term(0, xj);
                if (n == 8) pin64(outA);
                if (n >= 8) store(0, j);
            }
            term(1, 0);
            cut();
            wgmma_wait<0>();
            pin64(outB);
            LSTAMP(at == 0, 96 + 51); GSTAMP(LT && at == 0, 197);
#pragma unroll
            for (int j = 1; j < 8; j++) load_x(1, j);
            store(1, 0);
#pragma unroll
            for (int j = 1; j < 8; j++) {
                cut();
                term(1, j);
                store(1, j);
            }
            __syncwarp();
            if (lane == 0) mbar_arrive(bar_stored);
            LSTAMP(at == 0, 96 + 52);
        }
    } else if (warp < 12) {
        asm volatile("setmaxnreg.dec.sync.aligned.u32 64;");
        init_barriers(empty + 80 + 152 * w, 4, []() { return 19; });
#pragma unroll
        for (int i = 0; i < 2; i++) sts128(sb + OFF_LIST + i * 2048 + at * 16, 0u, 0u, 0u, 0u);
        uint32_t* keys = reinterpret_cast<uint32_t*>(smem + OFF_KEYS);
        keys[4] = 0;
        named_bar(0, 480);
        mbar_wait(bar_epoch);
        const uint32_t t2 = lds32(sb + OFF_EPOCH + 4);
        STAMPIF(at == 0, 20);
        float facc[4];
        const uint32_t dft = make_desc(sb + OFF_FT), dxs = make_desc(sb + OFF_XS);
#pragma unroll 1
        for (int u = 0; u < 4; u++) {
            mbar_wait(ffull + 8 * u);
            STAMPIF(at == 0, 4 + u);
            wgmma_fence();
            small_tile<0>(facc, dft + u * (TILE >> 4), dxs + u * 64, u == 0);
            wgmma_commit();
        }
        wgmma_wait<0>();
        pin4(facc);
        if (lane < 4) mbar_arrive(fempty + 8 * lane);
        auto gate_up = [&](auto rest) {
            uint32_t slot = 4, par = 0, prev = full + 8 * 100;
#pragma unroll 1
            for (int j = 0; j < 16; j++) {
                if (j == 2) rest();
                STAMPW(at == 0, 74 + j);
                mbar_wait(ffull + 8 * slot, par);
                STAMPW(at == 0, 160 + j);
                mbar_wait(empty + 8 * prm.use[j]);
                wgmma_fence();
                small_tile<1>(facc, dft + slot * (TILE >> 4), dxs + j * 64, j == 0);
                wgmma_commit();
                if (j < TN(NP)) { wgmma_wait<0>(); prev = fempty + 8 * slot; }
                else wgmma_wait<1>();
                if (lane == 0) mbar_arrive(prev);
                prev = j < TN(NP) ? full + 8 * 100 : fempty + 8 * slot;
                if (++slot == NFT) { slot = 0; par ^= 1; }
            }
            wgmma_wait<0>();
            if (lane == 0) mbar_arrive(prev);
            pin4(facc);
        };
        auto down = [&]() {
            const uint32_t dhid = make_desc(sb + OFF_HID);
#pragma unroll 1
            for (int j = 0; j < 7; j++) {
                mbar_wait(dfull + 8 * j);
                mbar_wait(empty + 8 * prm.use[16 + j]);
                wgmma_fence();
                small_tile<1>(facc, dft + j * (TILE >> 4), dhid + j * 64, j == 0);
                wgmma_commit();
                if ((0x52 >> j) & 1) {
                    wgmma_wait<0>();
                    if (lane == 0) mbar_arrive(bar_dfree + 8 * (j / 3));
                }
            }
            wgmma_wait<0>();
            pin4(facc);
        };
        if ((c & 1) == (w >> 1)) {
            float* red = reinterpret_cast<float*>(smem + OFF_RED) + w * 32 + (c >> 1) * 16 + g;
            red[0] = (w & 1) ? facc[1] : facc[0];
            red[8] = (w & 1) ? facc[3] : facc[2];
        }
        named_bar(2, 128);
        STAMPIF(at == 0, 21);
        const uint32_t tpub = clk32();
        if (w < 2) {
            const float* red = reinterpret_cast<const float*>(smem + OFF_RED) + w * 16 + (lane & 15);
            const float v = rbf((red[0] + red[32]) + (red[64] + red[96]));
            if (w == 0) {
                uint32_t k = __float_as_uint(v);
                k = ((k ^ ((uint32_t)((int)k >> 31) | 0x80000000u)) & 0xFFFF0000u) | (t2 << 11) | (2047u - (uint32_t)(rid * 16 + (lane & 15)));
                int rank = 0;
#pragma unroll
                for (int i = 0; i < 8; i++) rank += __shfl_sync(0xffffffffu, k, (lane >> 4) * 8 + i) > k;
                rank += __shfl_xor_sync(0xffffffffu, rank, 16);
                if (rank < 8) st_relaxed(&prm.s->key[cta * 8 + rank], k);
            } else if (lane < 16) st_relaxed(&prm.s->gate[rid * 16 + lane], __float_as_uint(rbf(sigmoidf_(v))) | t2);
            __syncwarp();
        }
        uint32_t it = 0;
        uint4 ka, kb4;
        sleep_until(tpub + TN(G0));
        while (true) {
            ka = ld_relaxed4(&prm.s->key[at * 8]);
            kb4 = ld_relaxed4(&prm.s->key[at * 8 + 4]);
            if (__all_sync(0xffffffffu, (((ka.x ^ (t2 << 11)) | (kb4.x ^ (t2 << 11))) & 0x1800u) == 0)) break;
            if (++it > SPIN_LIMIT) __trap();
        }
        STAMPIF(at == 0, 22);
        STAMPIF(at == 0 && it > 0, 23);
        const uint32_t m1 = __reduce_max_sync(0xffffffffu, ka.x), m2 = __reduce_max_sync(0xffffffffu, ka.x == m1 ? ka.y : ka.x);
        if (lane == 0) keys[w] = m2;
        named_bar(2, 128);
        const uint4 th4 = *reinterpret_cast<const uint4*>(keys);
        const uint32_t th = min(min(th4.x, th4.y), min(th4.z, th4.w));
        {
            const uint32_t k8[8] = {ka.x, ka.y, ka.z, ka.w, kb4.x, kb4.y, kb4.z, kb4.w};
            auto append = [&](int lo, int hi) {
                uint32_t n = 0, pos = 0;
#pragma unroll
                for (int i = lo; i < hi; i++) n += k8[i] >= th;
                asm volatile("{ .reg .pred p; setp.ne.u32 p, %2, 0; @p atom.shared.add.u32 %0, [%1], %2; }" : "+r"(pos) : "r"(sb + OFF_KEYS + 16), "r"(n) : "memory");
#pragma unroll
                for (int i = lo; i < hi; i++)
                    if (k8[i] >= th) reinterpret_cast<uint32_t*>(smem + OFF_LIST)[pos + i - lo] = k8[i];
            };
            append(0, 2);
            if (__any_sync(0xffffffffu, k8[2] >= th)) append(2, 8);
        }
        named_bar(2, 128);
        {
            const uint32_t* list = reinterpret_cast<const uint32_t*>(smem + OFF_LIST);
            const int n = (int)keys[4];
#pragma unroll 1
            for (int i0 = w * 32; i0 < n; i0 += 128) {
                const uint32_t k = list[i0 + lane];
                int rank = 0;
#pragma unroll 2
                for (int o = 0; o < n; o += 4) {
                    const uint4 l4 = *reinterpret_cast<const uint4*>(list + o);
                    rank += (l4.x > k) + (l4.y > k) + (l4.z > k) + (l4.w > k);
                }
                if (rank < 8) reinterpret_cast<uint32_t*>(smem + OFF_SEL)[rank] = k;
            }
        }
        named_bar(2, 128);
        STAMPIF(at == 0, 24);
        const uint32_t* sel = reinterpret_cast<const uint32_t*>(smem + OFF_SEL);
        auto gates = [&]() {
            uint32_t gv;
            it = 0;
            while (true) {
                gv = ld_relaxed(&prm.s->gate[chunk * 128 + at]);
                const uint32_t ar = ld_relaxed(&prm.s->armed[((cta >> 4) * 14 + min(lane, 13)) * 4]);
                if (__all_sync(0xffffffffu, (gv & 3u) == t2 && ar == t2)) break;
                if (++it > SPIN_LIMIT) __trap();
            }
            asm volatile("fence.acquire.gpu;" ::: "memory");
#pragma unroll
            for (int s = 0; s < 8; s++)
                if ((~sel[s] & 2047u) == (uint32_t)(chunk * 128 + at)) gv |= 0x80000000u;
            reinterpret_cast<uint16_t*>(smem + OFF_G)[at] = (uint16_t)(gv >> 16);
            __syncwarp();
            if (lane == 0) mbar_arrive(bar_g);
        };
        if (has_gu) {
            const int tk = (at >> 3) & 7;
            const char* xt = (const char*)prm.x + (~sel[tk] & 2047u) * 2048 + (at >> 6) * 128 + (at & 7) * 16;
#pragma unroll
            for (int i = 0; i < 8; i++) {
                cp_async16(sb + OFF_XS + (2 * i + (at >> 6)) * 1024 + tk * 128 + (((at & 7) ^ tk) << 4), xt + i * 256);
                if (i == 0 || i == 7) asm volatile("cp.async.commit_group;" ::: "memory");
            }
            asm volatile("cp.async.wait_group 1;" ::: "memory");
            fence_async_smem();
            named_bar(2, 128);
            STAMPIF(at == 0, 25);
            gate_up([&]() {
                asm volatile("cp.async.wait_all;" ::: "memory");
                fence_async_smem();
                named_bar(2, 128);
            });
            if (!(cta & 1)) {
#pragma unroll
                for (int u = 0; u < 4; u++) {
                    const float v = rbf(facc[u]);
                    facc[u] = __fdividef(v, 1.0f + __expf(-v));
                }
            }
            st_relaxed2(&prm.s->hid[cta * 128 + at], pack_bf(facc[0], facc[1]), pack_bf(facc[2], facc[3]));
        }
        STAMPIF(at == 0, 26);
        gates();
        {
            mbar_wait(empty + 8 * max(TN(HG), 31));
            const uint2* hp = &prm.s->hid[(cta >> 4) * 14 * 128 + at];
            uint32_t hv[16];
            it = 0;
            while (true) {
                uint32_t top = 0;
#pragma unroll
                for (int j = 0; j < 7; j++) {
                    const uint2 hg = ld_relaxed2(hp + 256 * j), hu = ld_relaxed2(hp + 256 * j + 128);
                    top = max(top, max(hg.x, hu.x));
                    hv[2 * j] = mul_bf2(hg.x, hu.x); hv[2 * j + 1] = mul_bf2(hg.y, hu.y);
                }
                if (__all_sync(0xffffffffu, top != ~0u)) break;
                do {
                    if (++it > SPIN_LIMIT) __trap();
                } while (!__all_sync(0xffffffffu, ld_relaxed(hp + min(lane, 13) * 128 - lane) != ~0u));
            }
            STAMPIF(at == 0 && it > 0, 61);
            hv[14] = hv[15] = 0;
#pragma unroll
            for (int j = 0; j < 4; j++)
                asm volatile("stmatrix.sync.aligned.m8n8.x4.trans.shared.b16 [%0], {%1, %2, %3, %4};" ::"r"(
                                 sb + OFF_HID + (2 * j + (lane >> 4)) * 1024 + (lane & 7) * 128 + (((2 * w + ((lane >> 3) & 1)) ^ (lane & 7)) << 4)),
                             "r"(hv[4 * j]), "r"(hv[4 * j + 1]), "r"(hv[4 * j + 2]), "r"(hv[4 * j + 3]) : "memory");
        }
        fence_async_smem();
        named_bar(2, 128);
        STAMPIF(at == 0, 27);
        uint32_t mine = __ballot_sync(0xffffffffu, lane < 8 && (int)((~sel[lane & 7] & 2047u) >> 7) == chunk), tr;
        uint2 xr, xd;
        float gr, rs;
        auto skip = [&](int n) {
#pragma unroll 1
            for (int i = 0; i < n; i++) mine &= mine - 1;
            if (mine) {
                const uint32_t key = sel[__ffs(mine) - 1], kb = key >> 16;
                tr = ~key & 2047u;
                xr = __ldg(reinterpret_cast<const uint2*>(prm.x + (size_t)tr * D_ + dt * 128) + lane);
                rs = rbf(sigmoidf_(bf_lo((kb & 0x8000u) ? (kb & 0x7FFFu) : (~kb & 0xFFFFu))));
                gr = fabsf(__bfloat162float(reinterpret_cast<const __nv_bfloat16*>(smem + OFF_G)[tr & 127]));
                xd = lds64(sb + OFF_DK + 8 * lane);
            }
        };
        skip(w);
        down();
#pragma unroll
        for (int u = 0; u < 4; u++)
            st_relaxed(&prm.s->y[((2 * c + (u & 1)) * 8 + (cta >> 4)) * D_ + (cta & 15) * 64 + w * 16 + g + 8 * (u >> 1)], (__float_as_uint(facc[u]) & ~3u) | t2);
        STAMPIF(at == 0, 28);
        sleep_until(clk32() + TN(T_Y));
        while (mine) {
            const uint32_t* yp = &prm.s->y[(__ffs(mine) - 1) * 8 * D_ + dt * 128 + 4 * lane];
            float y[4];
            it = 0;
            while (true) {
                uint32_t bad = 0;
                y[0] = y[1] = y[2] = y[3] = 0.f;
#pragma unroll
                for (int ks = 0; ks < 8; ks++) {
                    const uint4 v = ld_relaxed4(yp + ks * D_);
                    bad |= v.x ^ t2;
                    y[0] += __uint_as_float(v.x); y[1] += __uint_as_float(v.y); y[2] += __uint_as_float(v.z); y[3] += __uint_as_float(v.w);
                }
                if (__all_sync(0xffffffffu, (bad & 3u) == 0)) break;
                if (++it > SPIN_LIMIT) __trap();
            }
            STAMPIF(lane == 0 && it, 62);
#pragma unroll
            for (int u = 0; u < 4; u++) {
                const uint32_t x2 = (u & 2) ? xr.y : xr.x, d2 = mul_bf2(x2, (u & 2) ? xd.y : xd.x);
                y[u] = fmaf(gr, (u & 1) ? bf_hi(d2) : bf_lo(d2), rbf(rbf(1.0f - gr) * rbf(((u & 1) ? bf_hi(x2) : bf_lo(x2)) + rbf(rbf(y[u]) * rs))));
            }
            STAMPIF(lane == 0, 50);
            mbar_wait(bar_stored);
            asm volatile("red.global.add.v4.f32 [%0], {%1, %2, %3, %4};" ::"l"(prm.out + (size_t)tr * D_ + dt * 128 + 4 * lane), "f"(y[0]), "f"(y[1]), "f"(y[2]), "f"(y[3]) : "memory");
            skip(4);
        }
        LSTAMP(lane == 0, 96 + 29);
    } else {
        asm volatile("setmaxnreg.dec.sync.aligned.u32 40;");
        if (warp != 12) sleep_until(cstart + (warp == 13 ? TN(T_SMALL) : TN(T_W3)));
        if (warp == 15) {
            prefetch_map(&mXr);
            named_bar(0, 480);
#pragma unroll 1
            for (int i = 0; i < 4; i++) {
                const int u = i;
                if (lane == 0) mbar_expect_tx(ffull + 8 * u, TILE);
                sleep_until(cstart + (i == 0 ? TN(RT0) : i == 1 ? TN(RT1) : i == 2 ? TN(RT2) : TN(RT3)));
                if (elect_one()) tma3(sb + OFF_FT + u * TILE, &mXr, u * 256, rid * 16, ffull + 8 * u);
                STAMP(53 + u);
            }
            const CUtensorMap* mw = (cta & 1) ? &mWu : &mWg;
            if (sb & 1023) __trap();
            prefetch_map(mw);
            prefetch_map(&mWd);
            uint32_t slot = 4, par = 1;
#pragma unroll 1
            for (int j = 0; j < (has_gu && DBG != 1 ? 16 : 0); j++) {
                mbar_wait(fempty + 8 * slot, par);
                if (lane == 0) mbar_expect_tx(ffull + 8 * slot, TILE);
                mbar_wait(empty + 8 * prm.fetch[j]);
                STAMPW(1, 176 + j);
                if (elect_one()) tma2(sb + OFF_FT + slot * TILE, mw, (cta >> 1) * 64, TN(WDBG) ? 0 : j * 64, ffull + 8 * slot);
                if (++slot == NFT) { slot = 0; par ^= 1; }
            }
            if (lane < 9) mbar_expect_tx(lane < 7 ? dfull + 8 * lane : bar_x + 8 * (lane - 7), lane < 7 ? TILE : 2 * TILE);
            if (!has_gu) mbar_wait(bar_g);
#pragma unroll 1
            for (int j = 0; j < (DBG != 1 ? 7 : 0); j++) {
                if (has_gu) mbar_wait(fempty + 8 * min(j, 4), 1);
                mbar_wait(empty + 8 * prm.fetch[16 + j]);
                if (elect_one()) tma2(sb + OFF_FT + j * TILE, &mWd, (cta & 15) * 64, (cta >> 4) * 448 + (TN(WDBG) ? 0 : j * 64), dfull + 8 * j);
            }
            prefetch_map(&mXe);
#pragma unroll 1
            for (int u = 0; u < 4; u++) {
                mbar_wait(bar_dfree + 8 * (u & 2));
                mbar_wait(empty + 8 * (TN(DN_E0) + u));
                if (elect_one())
                    asm volatile("cp.async.bulk.tensor.5d.shared::cluster.global.mbarrier::complete_tx::bytes [%0], [%1, {%3, %6, %6, %4, %5}], [%2];"
                                 ::"r"(sb + OFF_FT + (u < 2 ? u : u + 3) * TILE), "l"(&mXe), "r"(bar_x + 4 * (u & 2)), "r"(dt * 128 + (u & 1) * 64), "r"(u & 2), "r"(chunk * 4), "r"(0) : "memory");
            }
        } else if (warp == 13) {
#pragma unroll
            for (int u = 0; u < 8; u++) {
                const int row = (u >> 2) * 4 + (lane >> 3);
                cp_async16(sb + OFF_XS + (u & 3) * 1024 + row * 128 + (((lane & 7) ^ row) << 4), (const char*)(u < 4 ? prm.w_r : prm.gate_w) + (u & 3) * 512 + lane * 16);
            }
            STAMP(57);
            const uint32_t tag = ld_relaxed(&prm.s->epoch[cta]) + 1;
            named_bar(1, 64);
            *reinterpret_cast<uint2*>(smem + OFF_EPOCH) = make_uint2(tag, tag % 3u + 1u);
            STAMPIF(tag, 58);
            asm volatile("cp.async.wait_all;" ::: "memory");
            STAMP(59);
            fence_async_smem();
            __syncwarp();
            if (lane == 0) {
                mbar_arrive(bar_epoch);
                prm.s->epoch[cta] = tag;
            }
            sleep_until(cstart + TN(T_BASE));
            {
                const uint2 st = ld_relaxed2(&prm.s->start[2 * lane]);
                const uint32_t d = st.x - cstart + 512u, age = gtime32() - st.y;
                const uint32_t m = __reduce_max_sync(0xffffffffu, d < 1024u && age < 4096u ? (d << 12) | age : 0u);
                const uint32_t late = (m & 4095u) - __reduce_min_sync(0xffffffffu, age);
                *reinterpret_cast<volatile uint32_t*>(smem + OFF_EPOCH + 8) = cstart + (m ? (m >> 12) - 512u + min(late, 256u) * TN(G_NS) / 4 : 0u);
                __syncwarp();
                if (lane == 0) mbar_arrive(bar_base);
                STAMP(60);
            }
            mbar_wait(bar_const);
            asm volatile("fence.acq_rel.gpu;" ::: "memory");
            if (lane < 4) st_relaxed2(&prm.s->armed[cta * 4 + lane], tag % 3u + 1u, 0u);
            prefetch_map(&mCre);
            prefetch_map(&mCim);
            const char* src = reinterpret_cast<const char*>(prm.s->h) + (size_t)chunk * 524288;
            uint32_t slot = 32 % NST, hpar = 0, rpar = 0;
#pragma unroll 1
            for (int i = 32; i < CH1; i++) {
                mbar_wait(hfull + 8 * slot, hpar);
                STAMPIF(i == 32 || i == 33, 14 + (i & 1));
                rpar = check_tile<16>(sb, sb + slot * SLOT, probe, src, tag, bar_retry, rpar, TN(T_RETRY));
                if (lane == 0) mbar_expect_tx(full + 8 * i, 2 * TILE);
                STAMPIF(i == 32 || i == 33, 16 + (i & 1));
                src += 2 * TILE;
                slot = slot == NST - 1 ? 0 : slot + 1;
                hpar ^= slot == 32 % NST;
            }
        } else if (warp == 14) {
            prefetch_map(&mPB);
            auto pf_c = [&](int k) { prefetch_slice(&mPC, 4 * (k >> 1), cta * 8 + (k & 1) * 4); };
            named_bar(0, 480);
            asm volatile("bar.arrive 1, 64;" ::: "memory");
            if (lane < 24) st_relaxed(lane < 8 ? &prm.s->key[cta * 8 + lane] : &prm.s->gate[rid * 16 + lane - 8], 0u);
#pragma unroll 1
            for (int k = TN(PF0) ? 0 : 1; k < 4; k++) {
                sleep_until(cstart + (k == 0 ? TN(PF0) : k == 1 ? TN(PF1) : k == 2 ? TN(PF2) : TN(PF3)));
                if (elect_one()) prefetch_slice(&mPB, 4 * k, cta * 4);
            }
#pragma unroll 1
            for (int k = 0; k < 4; k++) {
                mbar_wait(empty + 8 * (TN(PB_E0) + TN(PB_STEP) * k));
                if (elect_one()) prefetch_slice(&mPB, 4 * k, 512 + cta * 4);
            }
#pragma unroll 1
            for (int k = 0; k < TN(PC_N); k++) {
                mbar_wait(empty + 8 * min(TN(PC_E0) + TN(PC_STEP) * k / 2, 26));
                if (elect_one()) pf_c(k);
            }
            int pk = TN(PC_N), pe = TN(PC_E1);
            auto own_part = [&](int e) {
                if (!mbar_test(bar_out + 8 * e, 0)) {
                    mbar_wait(bar_out + 8 * e);
                    sleep_until(clk32() + TN(T_OWN));
                    STAMP(11);
                }
            };
            const char* src = reinterpret_cast<const char*>(prm.s->h) + (size_t)chunk * 524288;
            uint32_t slot = 32 % NST;
#pragma unroll 1
            for (int i = 32; i < NBIG; i++) {
                if (!(i & 3)) own_part((i - 32) >> 2);
                mbar_wait(empty + 8 * (i - NST));
                PSTAMP(i);
                if (elect_one()) {
                    mbar_expect_tx(hfull + 8 * slot, 2 * TILE);
                    bulk_load(sb + slot * SLOT, src, 2 * TILE, hfull + 8 * slot);
                }
                if (i == pe && pk < 8) {
                    if (elect_one()) pf_c(pk);
                    pk++; pe += TN(PC_S1);
                }
                src += 2 * TILE;
                slot = slot == NST - 1 ? 0 : slot + 1;
            }
#pragma unroll
            for (int k = 0; k < 14; k++) {
                if (k == 4) continue;
                if (k == 0 || k == 2) own_part(6 + k / 2);
                if (k == 2) mbar_wait(bar_dfree + 8);
                mbar_wait(empty + 8 * (NBIG - NST + k));
                if (elect_one()) {
#pragma unroll
                    for (int n = k < 5 ? 2 * k : k + 2; n < (k < 3 ? 2 * k + 2 : k == 3 ? 7 : k + 3); n++) {
                        mbar_expect_tx(hfull + 8 * (NST + n % 7), TILE);
                        bulk_load(sb + tail_h(n), src + (n & 7) * 2 * TILE + (n >> 3) * TILE, TILE, hfull + 8 * (NST + n % 7));
                    }
                }
            }
        } else {
            if (elect_one()) {
#pragma unroll
                for (int i = 0; i < NST; i++) mbar_init(full + 8 * i, 1);
                fence_mbar_init();
            }
            __syncwarp();
            asm volatile("bar.arrive 5, 160;" ::: "memory");
#pragma unroll 1
            for (int i = 0; i < NST; i++) {
                if (elect_one()) {
                    mbar_expect_tx(full + 8 * i, SLOT);
                    tma5b(sb + i * SLOT, &mB, i * 64, dt * 4, full + 8 * i);
                    tma4(sb + i * SLOT + 2 * TILE, &mX, i * 64, chunk * 64, full + 8 * i);
                }
                STAMPIF(i == 0, 1);
            }
            STAMP(2);
            asm volatile("bar.arrive 0, 480;" ::: "memory");
            named_bar(6, 160);
            uint32_t dst = sb;
#pragma unroll 1
            for (int i = NST; i < 32; i++) {
                if (i == 2 * NST) mbar_wait(bar_base);
                if (lane == 0) mbar_expect_tx(full + 8 * i, SLOT);
                mbar_wait(empty + 8 * (i - NST));
                PSTAMP(i);
                if (elect_one()) {
                    tma5b(dst, &mB, (i & 15) * 64, (i >> 4) * 64 + dt * 4, full + 8 * i);
                    tma4(dst + 2 * TILE, &mX, (i & 15) * 64, chunk * 64, full + 8 * i);
                }
                dst = dst == sb + (NST - 1) * SLOT ? sb : dst + SLOT;
            }
#pragma unroll 1
            for (int i = 32; i < NBIG; i++) {
                mbar_wait(empty + 8 * (i - NST));
                if (elect_one()) tma5(dst + 2 * TILE, (i & 4) ? &mCim : &mCre, ((i & 3) + ((i >> 1) & 12)) * 64, dt * 8, full + 8 * i);
                dst = dst == sb + (NST - 1) * SLOT ? sb : dst + SLOT;
            }
            dst = sb + tail_c(0);
#pragma unroll 1
            for (int j = 0; j < 8; j++) {
                mbar_wait(empty + 8 * (NBIG - NST + 1 + (j >> 1)));
                if (elect_one()) tma5(dst, (j & 4) ? &mCim : &mCre, ((j & 3) + 12) * 64, dt * 8, full + 8 * (NBIG + j));
                dst = j == 5 ? sb : dst + 2 * TILE;
            }
        }
    }
}

typedef CUresult (*EncodeFn)(CUtensorMap*, CUtensorMapDataType, cuuint32_t, void*, const cuuint64_t*, const cuuint64_t*, const cuuint32_t*,
                             const cuuint32_t*, CUtensorMapInterleave, CUtensorMapSwizzle, CUtensorMapL2promotion, CUtensorMapFloatOOBfill);

bool encode(EncodeFn fn, CUtensorMap* m, const void* ptr, int rank, const cuuint64_t* dims, const cuuint64_t* strides, const cuuint32_t* box,
            CUtensorMapL2promotion promo = CU_TENSOR_MAP_L2_PROMOTION_NONE) {
    const cuuint32_t es[5] = {1, 1, 1, 1, 1};
    return fn(m, CU_TENSOR_MAP_DATA_TYPE_BFLOAT16, rank, const_cast<void*>(ptr), dims, strides, box, es, CU_TENSOR_MAP_INTERLEAVE_NONE,
              CU_TENSOR_MAP_SWIZZLE_128B, promo, CU_TENSOR_MAP_FLOAT_OOB_FILL_NONE) == CUDA_SUCCESS;
}

}

extern "C" void kernel_launch(void* const* d_in, const int* in_sizes, int n_in, void* d_out, int out_size) {
    (void)in_sizes; (void)n_in; (void)out_size;
    Params prm;
    prm.x = (const __nv_bfloat16*)d_in[0];
    prm.lam_re = (const __nv_bfloat16*)d_in[1];
    prm.lam_im = (const __nv_bfloat16*)d_in[2];
    prm.b_re = (const __nv_bfloat16*)d_in[3];
    prm.b_im = (const __nv_bfloat16*)d_in[4];
    prm.c_re = (const __nv_bfloat16*)d_in[5];
    prm.c_im = (const __nv_bfloat16*)d_in[6];
    prm.log_dt = (const __nv_bfloat16*)d_in[7];
    prm.dskip = (const __nv_bfloat16*)d_in[8];
    prm.w_r = (const __nv_bfloat16*)d_in[10];
    prm.gate_w = (const __nv_bfloat16*)d_in[14];
    prm.out = (float*)d_out;
    cudaGetSymbolAddress((void**)&prm.s, g_scratch);
    prm.swapped = prm.b_im < prm.b_re;

    void* fnp = nullptr;
    cudaDriverEntryPointQueryResult qr;
    cudaGetDriverEntryPoint("cuTensorMapEncodeTiled", &fnp, cudaEnableDefault, &qr);
    EncodeFn fn = (EncodeFn)fnp;
    cudaFuncSetAttribute(fused_kernel, cudaFuncAttributeMaxDynamicSharedMemorySize, SMEM_BYTES);

    CUtensorMap mX, mB, mCre, mCim, mWg, mWu, mWd, mXr, mPB, mPC, mXe;
    const cuuint64_t row = 2048;
    {
        const cuuint64_t dims[4] = {1024, 2, 4, 976}, st[3] = {row, 32 * row, 2 * row};
        const cuuint32_t box[4] = {64, 2, 4, 16};
        encode(fn, &mX, prm.x, 4, dims, st, box, PROMO);
    }
    {
        const char *lo = (const char*)(prm.swapped ? prm.b_im : prm.b_re), *hi = (const char*)(prm.swapped ? prm.b_re : prm.b_im);
        const cuuint64_t dims[5] = {1024, 8, 2, 96, 2}, st[4] = {row, (cuuint64_t)(hi - lo), 8 * row, 256 * row};
        const cuuint32_t box[5] = {64, 8, 2, 4, 2};
        encode(fn, &mB, lo, 5, dims, st, box, PROMO);
    }
    {
        const cuuint64_t dims[5] = {1024, 2, 4, 2, 64}, st[4] = {row, 4 * row, 2 * row, 16 * row};
        const cuuint32_t box[5] = {64, 2, 4, 2, 8};
        encode(fn, &mCre, prm.c_re, 5, dims, st, box);
        encode(fn, &mCim, prm.c_im, 5, dims, st, box);
    }
    {
        const cuuint64_t dims[2] = {F_, D_}, st[1] = {F_ * 2}, dimsd[2] = {D_, F_}, std_[1] = {row};
        const cuuint32_t box[2] = {64, 64};
        encode(fn, &mWg, d_in[11], 2, dims, st, box);
        encode(fn, &mWu, d_in[12], 2, dims, st, box);
        encode(fn, &mWd, d_in[13], 2, dimsd, std_, box);
    }
    for (int i = 0; i < 2; i++) {
        const char *p = (const char*)(i ? prm.c_re : prm.b_re), *q = (const char*)(i ? prm.c_im : prm.b_im);
        const cuuint64_t dims[4] = {64, 16, 1024, 2}, st[3] = {128, row, (cuuint64_t)(p < q ? q - p : p - q)};
        const cuuint32_t box[4] = {16, 4, 4, 2};
        encode(fn, i ? &mPC : &mPB, p < q ? p : q, 4, dims, st, box, CU_TENSOR_MAP_L2_PROMOTION_L2_128B);
    }
    {
        const cuuint64_t dims[3] = {D_ - 192, S_, 4}, st[2] = {row, 128};
        const cuuint32_t box[3] = {64, 16, 4};
        encode(fn, &mXr, prm.x, 3, dims, st, box);
    }
    {
        const cuuint64_t dims[5] = {1024, 2, 4, 4, S_ / 32}, st[4] = {4 * row, row, 8 * row, 32 * row};
        const cuuint32_t box[5] = {64, 2, 4, 2, 4};
        encode(fn, &mXe, prm.x, 5, dims, st, box);
    }
    for (int j = 0, e4 = 4 * TN(GC0); j < 23; j++) {
        prm.fetch[j] = j < NFT ? TN(GU_E0) + j * TN(W_NUM) / 4 : j < 16 ? 0 : TN(DL0) + (j - 16) * TN(DLS) / 4;
        prm.use[j] = j < 16 ? e4 / 4 : TN(DC0) + (j - 16) * TN(DCS) / 4;
        const int last = 54;
        if (prm.fetch[j] > last) prm.fetch[j] = last;
        if (prm.use[j] > last) prm.use[j] = last;
        e4 += j < TN(N1) ? TN(GCS) : j < TN(N2) ? TN(GCS2) : j < 10 ? TN(GCS3) : TN(GCS4);
    }
    fused_kernel<<<NCTA, 512, SMEM_BYTES, cudaStreamPerThread>>>(prm, mX, mB, mCre, mCim, mWg, mWu, mWd, mXr, mPB, mPC, mXe);
}
```

```cpp
#include <cuda_runtime.h>
#include <cuda_bf16.h>
#include <cuda.h>
#include <stdint.h>

namespace {

constexpr int S_ = 2048, D_ = 1024, F_ = 3584;
constexpr int NCTA = 128;
constexpr int NBIG = 56, NENT = 72;
constexpr int NST = 5;
constexpr int NFT = 5;
constexpr uint32_t SLOT = 32768, TILE = 8192;
constexpr uint32_t OFF_FT = NST * SLOT;
constexpr uint32_t OFF_XS = OFF_FT + NFT * TILE;
constexpr uint32_t OFF_LIST = OFF_XS + 8192;
constexpr uint32_t OFF_RED = OFF_XS + 4096;
constexpr uint32_t OFF_CONST = OFF_XS + 16384;
constexpr uint32_t OFF_M = OFF_CONST + 8192, OFF_ONE = OFF_M + 512;
constexpr uint32_t OFF_HID = OFF_CONST;
constexpr uint32_t OFF_G = OFF_ONE + 16;
constexpr uint32_t OFF_DK = OFF_G + 256;
constexpr uint32_t OFF_FULL = OFF_DK + 256;
constexpr uint32_t OFF_EMPTY = OFF_FULL + 102 * 8;
constexpr uint32_t OFF_KEYS = OFF_EMPTY + 86 * 8;
constexpr uint32_t OFF_SEL = OFF_KEYS + 32;
constexpr uint32_t OFF_EPOCH = OFF_SEL + 32;
constexpr uint32_t OFF_PROF = OFF_EPOCH + 16;
constexpr uint32_t SMEM_BYTES = OFF_PROF + 432;
static_assert(SMEM_BYTES <= 232448, "smem");

static_assert(NBIG % NST == 1, "tail layout");
__host__ __device__ constexpr uint32_t tail_c(int j) { return j < 6 ? 2 * SLOT + j * 2 * TILE : (j - 6) * 2 * TILE; }
__host__ __device__ constexpr uint32_t tail_h(int n) { return n % 7 < 4 ? SLOT + n % 7 * TILE : OFF_FT + (n % 7 - 2) * TILE; }

constexpr uint32_t SPIN_LIMIT = 1u << 18;

struct Scratch {
    uint2 carry[16 * 1024];
    uint2 hid[NCTA * 128];
    uint32_t y[8 * 8 * D_];
    uint32_t key[NCTA * 8];
    uint32_t gate[S_];
    uint2 armed[NCTA * 4];
    unsigned int epoch[256];
    uint4 start[32 * 2];
    uint4 h[16 * 32 * 1024];
};
__device__ __align__(1024) Scratch g_scratch;
#define STAMPW_(cond, w) do {} while (0)
#define GSTAMP(cond, w) do {} while (0)
#define LSTAMP(cond, w) STAMPW_(cond, w)
#define LT 0
#define STAMPW(cond, w) STAMPW_(cond, w)
#define STAMPIF(cond, i) STAMPW(cond, 96 + (i))
#define STAMP(i) STAMPW(1, 96 + (i))
#define KSTAMP(i) STAMPW((threadIdx.x & 127) == 0, i)
#define PSTAMP(i) STAMPW((i) < 56 && (i) >= 32, 160 + (i))

struct Params {
    const __nv_bfloat16 *x, *b_re, *b_im, *lam_re, *lam_im, *c_re, *c_im, *log_dt, *dskip, *w_r, *gate_w;
    float* out;
    Scratch* s;
    int fetch[23], use[23];
    int swapped;
};

__device__ __forceinline__ uint32_t smem_u32(const void* p) { return (uint32_t)__cvta_generic_to_shared(p); }
__device__ __forceinline__ void mbar_init(uint32_t bar, uint32_t cnt) { asm volatile("mbarrier.init.shared::cta.b64 [%0], %1;" ::"r"(bar), "r"(cnt) : "memory"); }
__device__ __forceinline__ void mbar_expect_tx(uint32_t bar, uint32_t bytes) { asm volatile("mbarrier.arrive.expect_tx.shared::cta.b64 _, [%0], %1;" ::"r"(bar), "r"(bytes) : "memory"); }
__device__ __forceinline__ void mbar_arrive(uint32_t bar) { asm volatile("mbarrier.arrive.shared::cta.b64 _, [%0];" ::"r"(bar) : "memory"); }
__device__ __forceinline__ bool mbar_try(uint32_t bar, uint32_t parity) {
    uint32_t ok;
    asm volatile("{ .reg .pred p; mbarrier.try_wait.parity.shared::cta.b64 p, [%1], %2; selp.u32 %0, 1, 0, p; }" : "=r"(ok) : "r"(bar), "r"(parity) : "memory");
    return ok;
}
__device__ __forceinline__ bool mbar_test(uint32_t bar, uint32_t parity) {
    uint32_t ok;
    asm volatile("{ .reg .pred p; mbarrier.test_wait.parity.shared::cta.b64 p, [%1], %2; selp.u32 %0, 1, 0, p; }" : "=r"(ok) : "r"(bar), "r"(parity) : "memory");
    return __all_sync(0xffffffffu, ok);
}
__device__ __forceinline__ void mbar_wait(uint32_t bar, uint32_t parity = 0) {
    if (mbar_try(bar, parity)) return;
#pragma unroll 1
    for (uint32_t it = 0; it < SPIN_LIMIT; ++it)
        if (mbar_try(bar, parity)) return;
    __trap();
}
__device__ __forceinline__ bool elect_one() {
    uint32_t pred;
    asm volatile("{ .reg .pred P; elect.sync _|P, 0xffffffff; selp.b32 %0, 1, 0, P; }" : "=r"(pred));
    return pred;
}
__device__ __forceinline__ void named_bar(int id, int n) { asm volatile("bar.sync %0, %1;" ::"r"(id), "r"(n) : "memory"); }
__device__ __forceinline__ void fence_mbar_init() { asm volatile("fence.mbarrier_init.release.cluster;" ::: "memory"); }
__device__ __forceinline__ void fence_async_smem() { asm volatile("fence.proxy.async.shared::cta;" ::: "memory"); }

__device__ __forceinline__ void bulk_load(uint32_t dst, const void* src, uint32_t bytes, uint32_t bar) {
    asm volatile("cp.async.bulk.shared::cluster.global.mbarrier::complete_tx::bytes [%0], [%1], %2, [%3];" ::"r"(dst), "l"(src), "r"(bytes), "r"(bar) : "memory");
}
__device__ __forceinline__ void cp_async16(uint32_t dst, const void* src) { asm volatile("cp.async.cg.shared.global [%0], [%1], 16;" ::"r"(dst), "l"(src) : "memory"); }
__device__ __forceinline__ void sts128(uint32_t a, uint32_t x, uint32_t y, uint32_t z, uint32_t w) {
    asm volatile("st.shared.v4.u32 [%0], {%1,%2,%3,%4};" ::"r"(a), "r"(x), "r"(y), "r"(z), "r"(w) : "memory");
}
__device__ __forceinline__ uint2 lds64(uint32_t a) {
    uint2 v;
    asm volatile("ld.shared.v2.u32 {%0,%1}, [%2];" : "=r"(v.x), "=r"(v.y) : "r"(a) : "memory");
    return v;
}
__device__ __forceinline__ uint32_t lds32(uint32_t a) {
    uint32_t v;
    asm volatile("ld.volatile.shared.u32 %0, [%1];" : "=r"(v) : "r"(a) : "memory");
    return v;
}
__device__ __forceinline__ void stg128(void* p, uint32_t x, uint32_t y, uint32_t z, uint32_t w) {
    asm volatile("st.global.v4.u32 [%0], {%1,%2,%3,%4};" ::"l"(p), "r"(x), "r"(y), "r"(z), "r"(w) : "memory");
}
__device__ __forceinline__ void st_relaxed(void* p, uint32_t x) { asm volatile("st.relaxed.gpu.global.b32 [%0], %1;" ::"l"(p), "r"(x) : "memory"); }
__device__ __forceinline__ void st_relaxed2(void* p, uint32_t x, uint32_t y) { asm volatile("st.relaxed.gpu.global.v2.b32 [%0], {%1, %2};" ::"l"(p), "r"(x), "r"(y) : "memory"); }
__device__ __forceinline__ void st_relaxed4(void* p, uint32_t x, uint32_t y, uint32_t z, uint32_t w) {
    asm volatile("st.relaxed.gpu.global.v4.b32 [%0], {%1, %2, %3, %4};" ::"l"(p), "r"(x), "r"(y), "r"(z), "r"(w) : "memory");
}
__device__ __forceinline__ uint32_t ld_relaxed(const void* p) {
    uint32_t v;
    asm volatile("ld.relaxed.gpu.global.b32 %0, [%1];" : "=r"(v) : "l"(p) : "memory");
    return v;
}
__device__ __forceinline__ uint2 ld_relaxed2(const void* p) {
    uint2 v;
    asm volatile("ld.relaxed.gpu.global.v2.b32 {%0, %1}, [%2];" : "=r"(v.x), "=r"(v.y) : "l"(p) : "memory");
    return v;
}
__device__ __forceinline__ uint4 ld_relaxed4(const void* p) {
    uint4 v;
    asm volatile("ld.relaxed.gpu.global.v4.b32 {%0, %1, %2, %3}, [%4];" : "=r"(v.x), "=r"(v.y), "=r"(v.z), "=r"(v.w) : "l"(p) : "memory");
    return v;
}
__device__ __forceinline__ uint32_t clk32() { uint32_t c; asm volatile("mov.u32 %0, %%clock;" : "=r"(c)); return c; }
__device__ __forceinline__ uint32_t gtime32() { uint32_t c; asm volatile("mov.u32 %0, %%globaltimer_lo;" : "=r"(c)); return c; }
__device__ __forceinline__ void sched_fence(uint32_t t) { while ((int)(clk32() - t) < 0) {} }
__device__ __forceinline__ void sleep_until(uint32_t t) { while ((int)(clk32() - t) < 0) __nanosleep(40); }

__device__ __forceinline__ void tma2(uint32_t dst, const CUtensorMap* m, int c0, int c1, uint32_t bar) {
    asm volatile("{ .reg .b64 pol; createpolicy.fractional.L2::evict_first.b64 pol;\n"
                 "cp.async.bulk.tensor.2d.shared::cluster.global.mbarrier::complete_tx::bytes.L2::cache_hint [%0], [%1, {%3, %4}], [%2], pol; }"
                 ::"r"(dst), "l"(m), "r"(bar), "r"(c0), "r"(c1) : "memory");
}
__device__ __forceinline__ void tma3(uint32_t dst, const CUtensorMap* m, int c0, int c1, uint32_t bar) {
    asm volatile("cp.async.bulk.tensor.3d.shared::cluster.global.mbarrier::complete_tx::bytes [%0], [%1, {%3, %4, %5}], [%2];"
                 ::"r"(dst), "l"(m), "r"(bar), "r"(c0), "r"(c1), "r"(0) : "memory");
}
__device__ __forceinline__ void tma4(uint32_t dst, const CUtensorMap* m, int c0, int c3, uint32_t bar) {
    asm volatile("cp.async.bulk.tensor.4d.shared::cluster.global.mbarrier::complete_tx::bytes [%0], [%1, {%3, %5, %5, %4}], [%2];"
                 ::"r"(dst), "l"(m), "r"(bar), "r"(c0), "r"(c3), "r"(0) : "memory");
}
__device__ __forceinline__ void tma5(uint32_t dst, const CUtensorMap* m, int c0, int c4, uint32_t bar) {
    asm volatile("cp.async.bulk.tensor.5d.shared::cluster.global.mbarrier::complete_tx::bytes [%0], [%1, {%3, %5, %5, %5, %4}], [%2];"
                 ::"r"(dst), "l"(m), "r"(bar), "r"(c0), "r"(c4), "r"(0) : "memory");
}
__device__ __forceinline__ void tma5b(uint32_t dst, const CUtensorMap* m, int c0, int c3, uint32_t bar) {
    asm volatile("cp.async.bulk.tensor.5d.shared::cluster.global.mbarrier::complete_tx::bytes [%0], [%1, {%3, %5, %5, %4, %5}], [%2];"
                 ::"r"(dst), "l"(m), "r"(bar), "r"(c0), "r"(c3), "r"(0) : "memory");
}
__device__ __forceinline__ void prefetch_l2(const void* p) { asm volatile("prefetch.global.L2 [%0];" ::"l"(p)); }
__device__ __forceinline__ void prefetch_slice(const CUtensorMap* m, int line, int row) {
    asm volatile("cp.async.bulk.prefetch.tensor.4d.L2.global [%0, {%3, %1, %2, %3}];" ::"l"(m), "r"(line), "r"(row), "r"(0) : "memory");
}
__device__ __forceinline__ void prefetch_map(const CUtensorMap* m) { asm volatile("prefetch.tensormap [%0];" ::"l"(m)); }
__device__ __forceinline__ uint32_t uni(uint32_t v) { return __shfl_sync(0xffffffffu, v, 0); }

__device__ __forceinline__ uint32_t make_desc(uint32_t addr) { return ((addr & 0x3FFFF) >> 4) | (1u << 16); }
__device__ __forceinline__ uint32_t make_desc_h(uint32_t addr) { return ((addr & 0x3FFFF) >> 4) | (32u << 16); }
template <int H> __device__ __forceinline__ uint64_t desc64(uint32_t lo) {
    uint64_t d;
    asm volatile("mov.b64 %0, {%1, %2};" : "=l"(d) : "r"(lo), "n"(64u | ((H ? 2u : 1u) << 30)));
    return d;
}
__device__ __forceinline__ void wgmma_fence() { asm volatile("wgmma.fence.sync.aligned;" ::: "memory"); }
__device__ __forceinline__ void wgmma_commit() { asm volatile("wgmma.commit_group.sync.aligned;" ::: "memory"); }
template <int N> __device__ __forceinline__ void wgmma_wait() { asm volatile("wgmma.wait_group.sync.aligned %0;" ::"n"(N) : "memory"); }

#define R8(d, i) "+f"(d[i]), "+f"(d[i + 1]), "+f"(d[i + 2]), "+f"(d[i + 3]), "+f"(d[i + 4]), "+f"(d[i + 5]), "+f"(d[i + 6]), "+f"(d[i + 7])
#define R64(d) R8(d, 0), R8(d, 8), R8(d, 16), R8(d, 24), R8(d, 32), R8(d, 40), R8(d, 48), R8(d, 56)
template <int TA>
__device__ __forceinline__ void wgmma_n128(float (&d)[64], uint64_t da, uint64_t db, int scale_d = 1) {
    asm volatile("{ .reg .pred p; setp.ne.b32 p, %66, 0;\n"
                 "wgmma.mma_async.sync.aligned.m64n128k16.f32.bf16.bf16 "
                 "{%0,%1,%2,%3,%4,%5,%6,%7,%8,%9,%10,%11,%12,%13,%14,%15,%16,%17,%18,%19,%20,%21,%22,%23,%24,%25,%26,%27,%28,%29,%30,%31,"
                 "%32,%33,%34,%35,%36,%37,%38,%39,%40,%41,%42,%43,%44,%45,%46,%47,%48,%49,%50,%51,%52,%53,%54,%55,%56,%57,%58,%59,%60,%61,%62,%63}, "
                 "%64, %65, p, 1, 1, %67, 0; }"
                 : R64(d)
                 : "l"(da), "l"(db), "r"(scale_d), "n"(TA));
}
__device__ __forceinline__ void pin4(float (&d)[4]) { asm volatile("" : "+f"(d[0]), "+f"(d[1]), "+f"(d[2]), "+f"(d[3])::"memory"); }
__device__ __forceinline__ void pin64(float (&d)[64]) { asm volatile("" : R64(d)::"memory"); }

template <int TA>
__device__ __forceinline__ void wgmma_n8(float (&d)[4], uint64_t da, uint64_t db, int scale_d = 1) {
    asm volatile("{ .reg .pred p; setp.ne.b32 p, %7, 0;\n"
                 "wgmma.mma_async.sync.aligned.m64n8k16.f32.bf16.bf16 {%0,%1,%2,%3}, %4, %5, p, 1, 1, %6, 0; }"
                 : "+f"(d[0]), "+f"(d[1]), "+f"(d[2]), "+f"(d[3])
                 : "l"(da), "l"(db), "n"(TA), "r"(scale_d));
}

__device__ __forceinline__ float bf_lo(uint32_t u) { return __uint_as_float(u << 16); }
__device__ __forceinline__ float bf_hi(uint32_t u) { return __uint_as_float(u & 0xFFFF0000u); }
__device__ __forceinline__ float rbf(float v) { return __bfloat162float(__float2bfloat16_rn(v)); }
__device__ __forceinline__ uint32_t pack_bf(float lo, float hi) {
    uint32_t r;
    asm("cvt.rn.bf16x2.f32 %0, %1, %2;" : "=r"(r) : "f"(hi), "f"(lo));
    return r;
}
__device__ __forceinline__ uint32_t mul_bf2(uint32_t a, uint32_t b) {
    uint32_t r;
    asm("mul.rn.bf16x2 %0, %1, %2;" : "=r"(r) : "r"(a), "r"(b));
    return r;
}
__device__ __forceinline__ uint32_t fma_bf2(uint32_t a, uint32_t b, uint32_t c) {
    uint32_t r;
    asm("fma.rn.bf16x2 %0, %1, %2, %3;" : "=r"(r) : "r"(a), "r"(b), "r"(c));
    return r;
}
__device__ __forceinline__ float2 cmul(float2 a, float2 b) { return make_float2(a.x * b.x - a.y * b.y, a.x * b.y + a.y * b.x); }
__device__ __forceinline__ float2 cfma(float2 a, float2 b, float2 c) {
    return make_float2(fmaf(a.x, b.x, fmaf(-a.y, b.y, c.x)), fmaf(a.x, b.y, fmaf(a.y, b.x, c.y)));
}
__device__ __forceinline__ float sigmoidf_(float v) { return __fdividef(1.0f, 1.0f + expf(-v)); }

#define SCHED_NAMES RT0, RT1, RT2, RT3, PF0, PF1, PF2, PF3, T_SMALL, T_INIT, T_X0, T_BASE, G_NS, GT0, GT1, GT2, G0, GAP0, GAP1, RS_E, \
    PB_E0, PB_STEP, PC_E0, PC_STEP, PC_N, PC_E1, PC_S1, GU_E0, W_NUM, GC0, N1, N2, GCS, GCS2, GCS3, GCS4, HG, DL0, DLS, DC0, DCS, DN_E0, WDBG, T_OWN, T_RETRY, NP, T_Y, T_W0, T_W3
enum { SCHED_NAMES, NTUNE };
constexpr int sched_default[NTUNE] = {
    2200, 2700, 3200, 3700,
    0, 1100, 1300, 2800,
    1000, 1000, 200, 2500, 3,
    6600, 0, 0,
    1500, 250, 300, 4,
    4, 1, 9, 4, 5, 50, 3,
    4, 9, 15, 6, 6, 7, 7, 7, 5, 43, 37, 8, 38, 1, 50,
    0, 1100, 200, 0, 700, 600, 1000};
template <int I> struct Sched { static constexpr int v = sched_default[I]; };
#define TN(i) (Sched<i>::v)
#define DBG 0
#define NKK 4
#define EARLY 1
#define MERGE 1
#define FROT 0
#define NOPF 0
#define NOGAP 0
#define TDBG 0
#define X0 1
#define CH1 56
#define GE 8
#define DOUBLE 0
#define RAISE_J 1
#define GREEDY 0
#define POLL_S 24
#define PROMO CU_TENSOR_MAP_L2_PROMOTION_L2_256B

template <int TA, class H>
__device__ __forceinline__ void run_entry(uint32_t lo32, uint32_t prev, int accumulate, float (&accA)[64], float (&accB)[64], H inside) {
    const uint64_t da = desc64<TA>(lo32), db = TA ? desc64<0>(lo32 + (2 * TILE >> 4) - (31u << 16)) : da + (2 * TILE >> 4);
    wgmma_fence();
#pragma unroll
    for (int kk = 0; kk < 4; kk++) {
        wgmma_n128<TA>(accA, da + kk * (TA ? 128 : 2), db + kk * 2, kk > 0 ? 1 : accumulate);
        wgmma_n128<TA>(accB, da + 512 + kk * (TA ? 128 : 2), db + kk * 2, kk > 0 ? 1 : accumulate);
        if (kk == 1) {
            wgmma_commit();
            wgmma_wait<1>();
            if ((threadIdx.x & 31) == 0) mbar_arrive(prev);
            inside();
        }
    }
    wgmma_commit();
}
template <int TA, class H>
__device__ __forceinline__ void run_entries(uint32_t sb, int lo, int hi, int slot, float (&accA)[64], float (&accB)[64], H after) {
    const uint32_t da0 = TA ? make_desc_h(sb) : make_desc(sb), dlast = da0 + (NST - 1) * (SLOT >> 4);
    uint32_t prev = sb + OFF_FULL + 8 * 100, bar = sb + OFF_FULL + 8 * lo, lo32 = da0 + slot * (SLOT >> 4);
    int accumulate = 0;
#pragma unroll 1
    for (int i = lo; i < hi; i++) {
        mbar_wait(bar);
        KSTAMP(i);
        run_entry<TA>(lo32, prev, accumulate, accA, accB, []() {});
        prev = bar + (OFF_EMPTY - OFF_FULL);
        bar += 8;
        lo32 = lo32 == dlast ? da0 : lo32 + (SLOT >> 4);
        accumulate = 1;
        after(i);
    }
}

template <int TA>
__device__ __forceinline__ void small_tile(float (&acc)[4], uint32_t alo, uint32_t blo, bool first) {
    const uint64_t da = desc64<0>(alo), db = desc64<0>(blo);
#pragma unroll
    for (int kk = 0; kk < 4; kk++) wgmma_n8<TA>(acc, da + kk * (TA ? 128 : 2), db + kk * 2, kk > 0 || !first);
}

template <int N>
__device__ __forceinline__ uint32_t check_tile(uint32_t sb, uint32_t dst, uint32_t probe, const char* src, uint32_t par, uint32_t bar, uint32_t phase, uint32_t pause) {
    if ((TDBG & 4) && N == 8) return phase;
#pragma unroll 1
    for (uint32_t it = 0; it < SPIN_LIMIT; it++) {
        uint32_t v[N], bad = 0;
#pragma unroll
        for (int u = 0; u < N; u++) v[u] = lds32(dst + probe + (u >> 1) * 2048 + (u & 1) * 256);
#pragma unroll
        for (int u = 0; u < N; u += 4)
            asm("{ .reg .b32 a, b; lop3.b32 a, %1, %2, %5, 0x7E; lop3.b32 b, %3, %4, %5, 0x7E; lop3.b32 %0, %0, a, b, 0xFE; }"
                : "+r"(bad) : "r"(v[u]), "r"(v[u + 1]), "r"(v[u + 2]), "r"(v[u + 3]), "r"(par));
        if (!__any_sync(0xffffffffu, bad & 1u)) return phase;
        STAMP(10);
        __nanosleep(pause);
        if (elect_one()) {
            mbar_expect_tx(bar, N * 1024);
            bulk_load(dst, src, N * 1024, bar);
        }
        mbar_wait(bar, phase);
        phase ^= 1;
    }
    __trap();
    return 0;
}

__global__ void __launch_bounds__(512, 1)
fused_kernel(const __grid_constant__ Params prm, const __grid_constant__ CUtensorMap mX, const __grid_constant__ CUtensorMap mB, const __grid_constant__ CUtensorMap mCre,
             const __grid_constant__ CUtensorMap mCim, const __grid_constant__ CUtensorMap mWg, const __grid_constant__ CUtensorMap mWu,
             const __grid_constant__ CUtensorMap mWd, const __grid_constant__ CUtensorMap mXr, const __grid_constant__ CUtensorMap mPB,
             const __grid_constant__ CUtensorMap mPC, const __grid_constant__ CUtensorMap mXe) {
    {
        const uint32_t t = threadIdx.x, b = blockIdx.x;
        const uint32_t row = t < 32 ? ((b & 60) * 2 + (b >> 6) * 4 + (b & 3)) * 16 + (t >> 1) : b * 4 + ((t >> 1) & 3);
        const char* base = (const char*)(t < 32 ? prm.x : t < 40 ? prm.b_re : prm.b_im);
        asm volatile("{ .reg .pred p; setp.lt.u32 p, %1, 48; @p prefetch.global.L2 [%0]; }" ::"l"(base + (row * 2048 + (t & 1) * 128)), "r"(t) : "memory");
    }
    extern __shared__ __align__(1024) uint8_t smem[];
    uint32_t sb;
    asm volatile("mov.u32 %0, %1;" : "=r"(sb) : "r"(smem_u32(smem)));
    const int tid = threadIdx.x, warp = __shfl_sync(0xffffffffu, tid >> 5, 0), lane = tid & 31;
    const int cta = blockIdx.x;
    const uint32_t cstart = clk32();
    const int chunk = (cta >> 2) & 15;
    const int dt = (cta >> 6) * 4 + (cta & 3);
    const int rid = chunk * 8 + dt;
    const int fid = (cta + FROT) & 127;
    const bool has_gu = fid < 112;
    const uint32_t full = sb + OFF_FULL, empty = sb + OFF_EMPTY;
    const uint32_t ffull = full + 8 * 83, fempty = empty + 8 * 65;
    const uint32_t bar_epoch = full + 8 * 72, dfull = full + 8 * 73, bar_base = full + 8 * 101, bar_x = full + 8 * 81, bar_retry = full + 8 * 80, hfull = full + 8 * 88;
    const uint32_t bar_order = empty + 8 * 70, bar_const = empty + 8 * 85, bar_stored = empty + 8 * 72, bar_dfree = empty + 8 * 73,
                    bar_g = empty + 8 * 84, bar_out = empty + 8 * 76;
    const int w = warp & 3, g = lane >> 2, c = lane & 3, at = tid & 127;

    const uint32_t probe = (lane >> 3) * 32 + (g & 1) * 144 + (c & 1) * 520 + (c >> 1) * 1028;

    LSTAMP(tid == 0, 96);
    GSTAMP(tid == 0, 94);
    auto init_barriers = [&](uint32_t base, uint32_t cnt, auto n) {
        if (elect_one()) {
#pragma unroll
            for (int i = 0; i < n(); i++) mbar_init(base + 8 * i, cnt);
            fence_mbar_init();
        }
        __syncwarp();
    };
    if (warp != 12) {
        if (warp == 15 && !(cta & 3) && lane < 8) st_relaxed((uint32_t*)&prm.s->start[cta >> 1] + lane, (lane & 1) ? gtime32() : cstart);
        if (warp < 12) sleep_until(cstart + (warp < 4 ? TN(T_W0) : TN(T_INIT)));
    }
    if (warp < 8) {
        if (warp < 4) init_barriers(warp == 0 ? full + 40 : warp == 3 ? full + 8 * 97 : empty + 40 * (warp - 1), (warp + 1) & 2 ? 4 : 1, []() { return 5; });
        else init_barriers(full + min(80 + 176 * w, 8 * 75), 1, []() { return 22; });
        asm volatile("setmaxnreg.inc.sync.aligned.u32 192;");
        if (warp < 4) {
            named_bar(5, 160);
            asm volatile("bar.arrive 0, 480;" ::: "memory");
            asm volatile("bar.arrive 6, 160;" ::: "memory");
        } else named_bar(0, 480);
        const int wg = warp >> 2;
        const int p = wg * 512 + dt * 32 + w * 8 + g;
        uint32_t cp = sb + OFF_CONST + 8 * (wg * 64 + w * 8 + g), cw = cp + 1024 * c, cm = sb + OFF_M + 4 * (wg * 64 + w * 8 + g);
        const int j1 = chunk - 1 - c;
        uint2* cq = &prm.s->carry[j1 * 1024 + p];
        char* hd = reinterpret_cast<char*>(prm.s->h) + (size_t)chunk * 524288 + wg * 262144 + (dt >> 1) * 16384 + ((dt & 1) * 4 + w) * 1024 + g * 64 + ((c ^ (g >> 1)) << 4);
        const bool never = uni(cstart == 0 && sb == 0);
        asm volatile("" : "+l"(cq), "+l"(hd), "+r"(cp), "+r"(cw), "+r"(cm));
        float2 a[2], a32[2], a64[2], a512[2], pw32[2], pw128[2];
        uint32_t mm[2], t2, par;
        auto constants = [&](int h) {
            if (h) { t2 = lds32(sb + OFF_EPOCH + 4); par = lds32(sb + OFF_EPOCH); }
            auto ldc = [](uint32_t a) { const uint2 v = lds64(a); return make_float2(__uint_as_float(v.x), __uint_as_float(v.y)); };
            {
                a[h] = ldc(cp + 256 * h); a32[h] = ldc(cp + 256 * h + 1024); a64[h] = ldc(cp + 256 * h + 2048); a512[h] = ldc(cp + 256 * h + 7168);
                pw32[h] = ldc(cw + 256 * h);
                pw128[h] = ldc(cw + 256 * h + 3072);
                mm[h] = lds32(cm + 128 * h);
            }
        };
        if (wg == 1) {
            const int pc = w * 256 + dt * 32 + lane;
            const float lr = __bfloat162float(prm.lam_re[pc]), li = __bfloat162float(prm.lam_im[pc]), ld = __bfloat162float(prm.log_dt[pc]);
            const uint32_t dk = __ldg(reinterpret_cast<const uint32_t*>(prm.dskip + dt * 128) + (at & 63));
            reinterpret_cast<uint32_t*>(smem + OFF_DK)[at & 63] = dk;
            const float dtv = rbf(expf(ld));
            const float er = expf(dtv * lr);
            float sn, cs;
            sincosf(dtv * li, &sn, &cs);
            const float ar = er * cs, ai = er * sn;
            const float nr = ar - 1.0f, ni = ai;
            const bool big = fabsf(lr) >= fabsf(li);
            const float t = (big ? li : lr) / (big ? lr : li), dn = big ? lr + li * t : lr * t + li;
            const float cr = (big ? nr + ni * t : nr * t + ni) / dn, ci = (big ? ni - nr * t : ni * t - nr) / dn;
            float2* ct = reinterpret_cast<float2*>(smem + OFF_CONST) + at;
            float2 pw = make_float2(ar, prm.swapped ? -ai : ai);
            ct[0] = pw;
            const float mx = prm.swapped ? -2.f * ci : 2.f * cr, my = prm.swapped ? 2.f * cr : -2.f * ci;
            reinterpret_cast<uint32_t*>(smem + OFF_M)[at] = pack_bf(mx, my);
#pragma unroll
            for (int i = 0; i < 5; i++) pw = cmul(pw, pw);
#pragma unroll
            for (int i = 0; i < 2; i++) {
                const float2 p2 = cmul(pw, pw);
                ct[128 + 384 * i] = pw; ct[256 + 384 * i] = p2; ct[384 + 384 * i] = cmul(p2, pw);
                pw = cmul(p2, p2);
            }
            ct[896] = pw;
            mbar_wait(bar_epoch);
            __syncwarp();
            mbar_wait(empty + 8 * TN(RS_E));
            st_relaxed2(&prm.s->hid[fid * 128 + at], ~0u, ~0u);
            st_relaxed4(&prm.s->y[((at >> 4) * 8 + (cta >> 4)) * D_ + (cta & 15) * 64 + (at & 15) * 4], 0u, 0u, 0u, 0u);
            st_relaxed2(&prm.s->carry[chunk * 1024 + pc], 0u, 0u);
            __syncwarp();
            if (lane == 0) mbar_arrive(bar_const);

            STAMPIF(at == 0, 3);
            mbar_wait(bar_const);
            constants(0);
            constants(1);
            mbar_wait(bar_order);
        }

        float accA[64], accB[64];
        run_entries<0>(sb, wg * 16, wg * 16 + 15, wg, accA, accB, [&](int i) {
            if (i == GE - 1) {
                mbar_wait(bar_base);
                sched_fence(lds32(sb + OFF_EPOCH + 8) + TN(GT0));
            }
        });
        mbar_wait(full + 8 * (wg * 16 + 15));
        KSTAMP(wg * 16 + 15);
        if (wg == 0) {
            mbar_wait(bar_const);
            run_entry<0>(make_desc(sb), empty + 8 * 14, 1, accA, accB, [&]() { constants(0); constants(1); if (EARLY && lane == 0) mbar_arrive(bar_order); });
        } else run_entry<0>(make_desc(sb + SLOT), empty + 8 * 30, 1, accA, accB, [&]() { if (EARLY && lane == 0) mbar_arrive(bar_order + 8); });
        if (!EARLY && lane == 0) mbar_arrive(bar_order + 8 * wg);
        uint2 v[2][4];
#pragma unroll
        for (int m = 0; m < 8; m++) v[m >> 2][m & 3] = make_uint2(t2, t2);
        wgmma_wait<0>();
        pin64(accA); pin64(accB);
        if (lane == 0) mbar_arrive(empty + 8 * (wg * 16 + 15));
        LSTAMP(at == 0, 96 + 30 + 10 * wg); GSTAMP(LT && at == 0, 193 + wg);

        auto cut = [&]() { if (never) sched_fence(cstart); };
        auto poll = [&](uint2 (&u)[4], int h) {
#pragma unroll
            for (int m = 0; m < 4; m++)
                asm volatile("{ .reg .pred p; setp.ge.s32 p, %3, %4; @p ld.relaxed.gpu.global.v2.b32 {%0, %1}, [%2]; }"
                             : "+r"(u[m].x), "+r"(u[m].y) : "l"(cq + 256 * h - 4096 * m), "r"(j1), "r"(4 * m) : "memory");
        };
        auto check = [&](const uint2 (&u)[4]) {
            uint32_t bad = 0;
#pragma unroll
            for (int m = 0; m < 4; m++) bad |= (u[m].x ^ t2) | (u[m].y ^ t2);
            return bad;
        };
        auto valid = [&](const uint2 (&u)[4]) { return __all_sync(0xffffffffu, (check(u) & 3u) == 0); };

        auto horner = [&](const uint2 (&u)[4], int h) {
            float2 r = make_float2(__uint_as_float(u[3].x), __uint_as_float(u[3].y));
#pragma unroll
            for (int m = 2; m >= 0; m--) r = cfma(a512[h], r, make_float2(__uint_as_float(u[m].x), __uint_as_float(u[m].y)));
            return r;
        };
        float2 w0[2];
#pragma unroll
        for (int h = 0; h < 2; h++) {
            float (&acc)[64] = h ? accB : accA;
            float2 e = make_float2(acc[0], acc[2]);
#pragma unroll
            for (int s = 1; s < 32; s++) {
                const int i0 = 4 * (s >> 1) + (s & 1);
                e = cfma(a[h], e, make_float2(acc[i0], acc[i0 + 2]));
                if (!GREEDY && h == 1 && s == POLL_S) { cut(); poll(v[0], 0); }
            }
            float2 y = make_float2(__shfl_up_sync(0xffffffffu, e.x, 1, 4), __shfl_up_sync(0xffffffffu, e.y, 1, 4));
            if (c >= 1) e = cfma(a32[h], y, e);
            y = make_float2(__shfl_up_sync(0xffffffffu, e.x, 2, 4), __shfl_up_sync(0xffffffffu, e.y, 2, 4));
            if (c >= 2) e = cfma(a64[h], y, e);
            if (c == 3) st_relaxed2(cq + 4096 + 256 * h, (__float_as_uint(e.x) & ~3u) | t2, (__float_as_uint(e.y) & ~3u) | t2);
            if (h || !GREEDY) cut();
            w0[h] = make_float2(__shfl_up_sync(0xffffffffu, e.x, 1, 4), __shfl_up_sync(0xffffffffu, e.y, 1, 4));
            STAMPIF(at == 0 && (h || !GREEDY), 31 + h + 10 * wg);
        }
        if (GREEDY) { __nanosleep(100); poll(v[0], 0); __nanosleep(100); }
        uint32_t sx[2][16], sy[2][16], mr[2][4], tp;
        const uint32_t gap = wg ? TN(GAP1) : TN(GAP0);
#pragma unroll
        for (int h = 0; h < 2; h++) {
            const uint32_t sg = prm.swapped ? 0x80008000u : 0u;
            mr[h][0] = __byte_perm(mm[h], 0, 0x1010); mr[h][1] = __byte_perm(mm[h], 0, 0x3232);
            mr[h][2] = mr[h][1] ^ sg; mr[h][3] = mr[h][0] ^ sg ^ 0x80008000u;
        }
        auto put = [&](int e, int j) {
            uint32_t d[4];
#pragma unroll
            for (int u = 0; u < 4; u++) d[u] = fma_bf2(mr[e >> 1][2 * (e & 1)], sx[e >> 1][4 * j + u], mul_bf2(mr[e >> 1][2 * (e & 1) + 1], sy[e >> 1][4 * j + u]));
            #pragma unroll
            for (int u = 0; u < 2; u++)
                asm("lop3.b32 %0, %0, %1, %2, 0xD8;" : "+r"(d[2 * (j & 1) + u]) : "r"(par), "r"((uint32_t)((w & 1) == u)));
            stg128(hd + e * 65536 + (j >> 1) * 8192 + (j & 1) * 512, d[0], d[1], d[2], d[3]);
            if (j == 3 && lane == 0) mbar_arrive(bar_out + 32 * wg + 8 * e);
        };
#pragma unroll
        for (int h = 0; h < 2; h++) {
            float (&acc)[64] = h ? accB : accA;
            float2 hin;
            uint32_t it = 0;
            if (h == 0 && DOUBLE) {
                while (true) {
                    poll(v[1], 0);
                    if (valid(v[0])) { hin = horner(v[0], 0); break; }
                    poll(v[0], 0);
                    if (valid(v[1])) { hin = horner(v[1], 0); it++; break; }
                    if (++it > SPIN_LIMIT) __trap();
                }
            } else {
                while (!valid(v[0])) {
                    poll(v[0], h);
                    if (++it > SPIN_LIMIT) __trap();
                }
                hin = horner(v[0], h);
            }
            STAMPIF(at == 0 && it > 0 && h == 0, 39 + 10 * wg);
            if (c) hin = cmul(pw128[h], hin);
            hin.x += __shfl_xor_sync(0xffffffffu, hin.x, 1); hin.y += __shfl_xor_sync(0xffffffffu, hin.y, 1);
            hin.x += __shfl_xor_sync(0xffffffffu, hin.x, 2); hin.y += __shfl_xor_sync(0xffffffffu, hin.y, 2);
            float2 st = hin;
            if (c) st = cfma(pw32[h], hin, w0[h]);
            STAMPIF(at == 0, 33 + 3 * h + 10 * wg);
#pragma unroll
            for (int j = 0; j < 4; j++) {
#pragma unroll
                for (int u = 0; u < 4; u++) {
                    const int i0 = 16 * j + 4 * u;
                    const float2 y = cfma(a[h], st, make_float2(acc[i0], acc[i0 + 2]));
                    st = cfma(a[h], y, make_float2(acc[i0 + 1], acc[i0 + 3]));
                    sx[h][4 * j + u] = pack_bf(y.x, st.x); sy[h][4 * j + u] = pack_bf(y.y, st.y);
                }
                if (h && !NOGAP) sleep_until(tp += gap);
                if (h == 0 && j == RAISE_J) poll(v[0], 1);
                put(2 * h, j);
                cut();
            }
            STAMPIF(at == 0, 34 + 3 * h + 10 * wg);
            tp = clk32();
#pragma unroll
            for (int j = 0; j < 4; j++) {
                if (!NOGAP) sleep_until(tp += gap); else if (NOGAP == 2) __nanosleep(50); else cut();
                put(2 * h + 1, j);
            }
        }
        STAMPIF(at == 0, 38 + 10 * wg);

        if (wg == 1) {
            const char* src = reinterpret_cast<const char*>(prm.s->h) + (size_t)chunk * 524288;
            uint32_t rpar = 1;
#pragma unroll 1
            for (int i = CH1 + w; i < NBIG; i += 4) {
                const uint32_t slot = i % NST;
                mbar_wait(empty + 8 * (i - NST));
                mbar_wait(hfull + 8 * slot, (i - 32) / NST & 1);
                rpar = check_tile<16>(sb, sb + slot * SLOT, probe, src + (i - 32) * 2 * TILE, par, full + 8 * w, rpar, TN(T_RETRY));
                if (lane == 0) mbar_expect_tx(full + 8 * i, 2 * TILE);
            }
#pragma unroll 1
            for (int n = w; n < 16; n += 4) {
                mbar_wait(empty + 8 * (NBIG - 7 + n));
                mbar_wait(hfull + 8 * (NST + n % 7), n / 7 & 1);
                const uint32_t dst = sb + tail_h(n);
                rpar = check_tile<8>(sb, dst, probe, src + (24 + (n & 7)) * 2 * TILE + (n >> 3) * TILE, par, full + 8 * w, rpar, TN(T_RETRY));
                if (lane == 0) mbar_expect_tx(full + 8 * (NBIG + n), n < 8 ? 2 * TILE : 0);
            }
        } else {
            asm volatile("setmaxnreg.inc.sync.aligned.u32 216;");
            const int tl = 64 * (w & 1) + 8 * (w >> 1) + g;
            float gf[4];
            float* op = prm.out + (size_t)(chunk * 128 + tl) * D_ + dt * 128 + 4 * c;
            const int xr = 2 * (g & 3) + (g >> 2);
            uint32_t xs = sb + OFF_FT + (32 * (w & 1) + 8 * (w >> 1) + xr) * 128 + (((c >> 1) ^ xr) << 4) + (c & 1) * 8;
            uint32_t gs = sb + OFF_G + 2 * tl;
            asm volatile("" : "+r"(gs), "+l"(op), "+r"(xs));
            float outA[64], outB[64];
            STAMPIF(at == 0, 9);
            mbar_wait(bar_order + 8);
            STAMPIF(at == 0, 35);
            if (TN(GT2)) sched_fence(lds32(sb + OFF_EPOCH + 8) + TN(GT2));
            run_entries<1>(sb, 32, NBIG, 32 % NST, outA, outB, [](int) {});
            uint32_t gp[4], om[4];
            uint2 xt[4][8], dk[8];
            auto load_x = [&](int q, int j) {
#pragma unroll
                for (int r = 0; r < 2; r++) xt[2 * q + r][j] = lds64((xs ^ ((j & 3) << 5)) + (5 * q + (j >> 2)) * TILE + r * 2048);
                if (q == 0) dk[j] = lds64(sb + OFF_DK + c * 8 + 32 * j);
            };
            auto term = [&](int q, int j) {
#pragma unroll
                for (int r = 2 * q; r < 2 * q + 2; r++) {
                    xt[r][j].x = mul_bf2(xt[r][j].x, fma_bf2(gp[r], dk[j].x, om[r]));
                    xt[r][j].y = mul_bf2(xt[r][j].y, fma_bf2(gp[r], dk[j].y, om[r]));
                }
            };
            auto store = [&](int q, int j) {
                const float (&acc)[64] = q ? outB : outA;
#pragma unroll
                for (int r = 0; r < 2; r++) {
                    const int o = 8 * j + 2 * r;
                    const float gv = fabsf(gf[2 * q + r]);
                    const uint2 t = xt[2 * q + r][j];
                    stg128(op + (r * 32 + q * 16) * D_ + 16 * j, __float_as_uint(fmaf(gv, acc[o], bf_lo(t.x))), __float_as_uint(fmaf(gv, acc[o + 1], bf_hi(t.x))),
                           __float_as_uint(fmaf(gv, acc[o + 4], bf_lo(t.y))), __float_as_uint(fmaf(gv, acc[o + 5], bf_hi(t.y))));
                }
            };
            uint64_t dh = desc64<1>(make_desc_h(sb)), dc = desc64<0>(make_desc(sb));
#pragma unroll
            for (int n = 0; n < 16; n++) {
                const int j = n & 7;
                if (n == 0) mbar_wait(bar_g);
                if (n == X0 || n == 15) mbar_wait(bar_x + (n == 15 ? 8 : 0));
                mbar_wait(full + 8 * (NBIG + n));
                KSTAMP(NBIG + n);
                asm volatile("mov.b64 %0, %0; mov.b64 %1, %1;" : "+l"(dh), "+l"(dc));
                const uint64_t da = dh + (tail_h(n) >> 4), db = dc + (tail_c(j) >> 4);
                const int xj = n - X0;
                wgmma_fence();
#pragma unroll
                for (int kk = 0; kk < 4; kk++) {
                    wgmma_n128<1>(n < 8 ? outA : outB, da + kk * 128, db + kk * 2);
                    if (kk == 0 && n == 0) {
#pragma unroll
                        for (int r = 0; r < 4; r++) {
                            uint32_t u;
                            asm volatile("ld.shared.u16 %0, [%1];" : "=r"(u) : "r"(gs + (r & 1) * 64 + (r >> 1) * 32) : "memory");
                            gf[r] = bf_lo(u);
                        }
                    }
                    if (kk == 0 && xj >= 0 && xj < 8) load_x(0, xj);
                    if (kk == 0 && n == 15) load_x(1, 0);
                }
                wgmma_commit();
                if (n < 10) {
                    wgmma_wait<1>();
                    if (lane == 0) mbar_arrive(empty + 8 * (NBIG + n - 1));
                    if (!(n & 7)) { LSTAMP(at == 0, 96 + 12 + n / 8); GSTAMP(LT && at == 0, 195 + n / 8); }
                } else cut();
                if (n == 0) {
#pragma unroll
                    for (int r = 0; r < 4; r++) {
                        const bool routed = (int)__float_as_uint(gf[r]) < 0;
                        gp[r] = routed ? 0u : pack_bf(gf[r], gf[r]); om[r] = routed ? 0u : pack_bf(1.0f - gf[r], 1.0f - gf[r]);
                    }
                }
                if (xj >= 0 && xj < 8) term(0, xj);
                if (n == 8) pin64(outA);
                if (n >= 8) store(0, j);
            }
            term(1, 0);
            cut();
            wgmma_wait<0>();
            pin64(outB);
            LSTAMP(at == 0, 96 + 51); GSTAMP(LT && at == 0, 197);
#pragma unroll
            for (int j = 1; j < 8; j++) load_x(1, j);
            store(1, 0);
#pragma unroll
            for (int j = 1; j < 8; j++) {
                cut();
                term(1, j);
                store(1, j);
            }
            __syncwarp();
            if (lane == 0) mbar_arrive(bar_stored);
            LSTAMP(at == 0, 96 + 52);
        }
    } else if (warp < 12) {
        asm volatile("setmaxnreg.dec.sync.aligned.u32 64;");
        init_barriers(empty + 80 + 152 * w, 4, []() { return 19; });
#pragma unroll
        for (int i = 0; i < 2; i++) sts128(sb + OFF_LIST + i * 2048 + at * 16, 0u, 0u, 0u, 0u);
        uint32_t* keys = reinterpret_cast<uint32_t*>(smem + OFF_KEYS);
        keys[4] = 0;
        named_bar(0, 480);
        mbar_wait(bar_epoch);
        const uint32_t t2 = lds32(sb + OFF_EPOCH + 4);
        STAMPIF(at == 0, 20);
        float facc[4];
        const uint32_t dft = make_desc(sb + OFF_FT), dxs = make_desc(sb + OFF_XS);
#pragma unroll 1
        for (int u = 0; u < 4; u++) {
            mbar_wait(ffull + 8 * u);
            STAMPIF(at == 0, 4 + u);
            wgmma_fence();
            small_tile<0>(facc, dft + u * (TILE >> 4), dxs + u * 64, u == 0);
            wgmma_commit();
        }
        wgmma_wait<0>();
        pin4(facc);
        if (lane < 4) mbar_arrive(fempty + 8 * lane);
        auto gate_up = [&](auto rest) {
            uint32_t slot = 4, par = 0, prev = full + 8 * 100;
#pragma unroll 1
            for (int j = 0; j < 16; j++) {
                if (j == 2) rest();
                STAMPW(at == 0, 74 + j);
                mbar_wait(ffull + 8 * slot, par);
                STAMPW(at == 0, 160 + j);
                mbar_wait(empty + 8 * prm.use[j]);
                wgmma_fence();
                small_tile<1>(facc, dft + slot * (TILE >> 4), dxs + j * 64, j == 0);
                wgmma_commit();
                if (j < TN(NP)) { wgmma_wait<0>(); prev = fempty + 8 * slot; }
                else wgmma_wait<1>();
                if (lane == 0) mbar_arrive(prev);
                prev = j < TN(NP) ? full + 8 * 100 : fempty + 8 * slot;
                if (++slot == NFT) { slot = 0; par ^= 1; }
            }
            wgmma_wait<0>();
            if (lane == 0) mbar_arrive(prev);
            pin4(facc);
        };
        auto down = [&]() {
            const uint32_t dhid = make_desc(sb + OFF_HID);
#pragma unroll 1
            for (int j = 0; j < 7; j++) {
                mbar_wait(dfull + 8 * j);
                mbar_wait(empty + 8 * prm.use[16 + j]);
                wgmma_fence();
                small_tile<1>(facc, dft + j * (TILE >> 4), dhid + j * 64, j == 0);
                wgmma_commit();
                if ((0x52 >> j) & 1) {
                    wgmma_wait<0>();
                    if (lane == 0) mbar_arrive(bar_dfree + 8 * (j / 3));
                }
            }
            wgmma_wait<0>();
            pin4(facc);
        };
        if ((c & 1) == (w >> 1)) {
            float* red = reinterpret_cast<float*>(smem + OFF_RED) + w * 32 + (c >> 1) * 16 + g;
            red[0] = (w & 1) ? facc[1] : facc[0];
            red[8] = (w & 1) ? facc[3] : facc[2];
        }
        named_bar(2, 128);
        STAMPIF(at == 0, 21);
        const uint32_t tpub = clk32();
        if (w < 2) {
            const float* red = reinterpret_cast<const float*>(smem + OFF_RED) + w * 16 + (lane & 15);
            const float v = rbf((red[0] + red[32]) + (red[64] + red[96]));
            if (w == 0) {
                uint32_t k = __float_as_uint(v);
                k = ((k ^ ((uint32_t)((int)k >> 31) | 0x80000000u)) & 0xFFFF0000u) | (t2 << 11) | (2047u - (uint32_t)(rid * 16 + (lane & 15)));
                int rank = 0;
#pragma unroll
                for (int i = 0; i < 8; i++) rank += __shfl_sync(0xffffffffu, k, (lane >> 4) * 8 + i) > k;
                rank += __shfl_xor_sync(0xffffffffu, rank, 16);
                if (rank < 8) st_relaxed(&prm.s->key[cta * 8 + rank], k);
            } else if (lane < 16) st_relaxed(&prm.s->gate[rid * 16 + lane], __float_as_uint(rbf(sigmoidf_(v))) | t2);
            __syncwarp();
        }
        uint32_t it = 0;
        uint4 ka, kb4;
        sleep_until(tpub + TN(G0));
        while (true) {
            ka = ld_relaxed4(&prm.s->key[at * 8]);
            kb4 = ld_relaxed4(&prm.s->key[at * 8 + 4]);
            if (__all_sync(0xffffffffu, (((ka.x ^ (t2 << 11)) | (kb4.x ^ (t2 << 11))) & 0x1800u) == 0)) break;
            if (++it > SPIN_LIMIT) __trap();
        }
        STAMPIF(at == 0, 22);
        STAMPIF(at == 0 && it > 0, 23);
        const uint32_t m1 = __reduce_max_sync(0xffffffffu, ka.x), m2 = __reduce_max_sync(0xffffffffu, ka.x == m1 ? ka.y : ka.x);
        if (lane == 0) keys[w] = m2;
        named_bar(2, 128);
        const uint4 th4 = *reinterpret_cast<const uint4*>(keys);
        const uint32_t th = min(min(th4.x, th4.y), min(th4.z, th4.w));
        {
            const uint32_t k8[8] = {ka.x, ka.y, ka.z, ka.w, kb4.x, kb4.y, kb4.z, kb4.w};
            auto append = [&](int lo, int hi) {
                uint32_t n = 0, pos = 0;
#pragma unroll
                for (int i = lo; i < hi; i++) n += k8[i] >= th;
                asm volatile("{ .reg .pred p; setp.ne.u32 p, %2, 0; @p atom.shared.add.u32 %0, [%1], %2; }" : "+r"(pos) : "r"(sb + OFF_KEYS + 16), "r"(n) : "memory");
#pragma unroll
                for (int i = lo; i < hi; i++)
                    if (k8[i] >= th) reinterpret_cast<uint32_t*>(smem + OFF_LIST)[pos + i - lo] = k8[i];
            };
            append(0, 2);
            if (__any_sync(0xffffffffu, k8[2] >= th)) append(2, 8);
        }
        named_bar(2, 128);
        {
            const uint32_t* list = reinterpret_cast<const uint32_t*>(smem + OFF_LIST);
            const int n = (int)keys[4];
#pragma unroll 1
            for (int i0 = w * 32; i0 < n; i0 += 128) {
                const uint32_t k = list[i0 + lane];
                int rank = 0;
#pragma unroll 2
                for (int o = 0; o < n; o += 4) {
                    const uint4 l4 = *reinterpret_cast<const uint4*>(list + o);
                    rank += (l4.x > k) + (l4.y > k) + (l4.z > k) + (l4.w > k);
                }
                if (rank < 8) reinterpret_cast<uint32_t*>(smem + OFF_SEL)[rank] = k;
            }
        }
        named_bar(2, 128);
        STAMPIF(at == 0, 24);
        const uint32_t* sel = reinterpret_cast<const uint32_t*>(smem + OFF_SEL);
        auto gates = [&]() {
            uint32_t gv;
            it = 0;
            while (true) {
                gv = ld_relaxed(&prm.s->gate[chunk * 128 + at]);
                const uint32_t ar = ld_relaxed(&prm.s->armed[((cta >> 4) * 14 + min(lane, 13)) * 4]);
                if (__all_sync(0xffffffffu, (gv & 3u) == t2 && ar == t2)) break;
                if (++it > SPIN_LIMIT) __trap();
            }
            asm volatile("fence.acquire.gpu;" ::: "memory");
#pragma unroll
            for (int s = 0; s < 8; s++)
                if ((~sel[s] & 2047u) == (uint32_t)(chunk * 128 + at)) gv |= 0x80000000u;
            reinterpret_cast<uint16_t*>(smem + OFF_G)[at] = (uint16_t)(gv >> 16);
            __syncwarp();
            if (lane == 0) mbar_arrive(bar_g);
        };
        if (has_gu) {
            const int tk = (at >> 3) & 7;
            const char* xt = (const char*)prm.x + (~sel[tk] & 2047u) * 2048 + (at >> 6) * 128 + (at & 7) * 16;
#pragma unroll
            for (int i = 0; i < 8; i++) {
                cp_async16(sb + OFF_XS + (2 * i + (at >> 6)) * 1024 + tk * 128 + (((at & 7) ^ tk) << 4), xt + i * 256);
                if (i == 0 || i == 7) asm volatile("cp.async.commit_group;" ::: "memory");
            }
            asm volatile("cp.async.wait_group 1;" ::: "memory");
            fence_async_smem();
            named_bar(2, 128);
            STAMPIF(at == 0, 25);
            gate_up([&]() {
                asm volatile("cp.async.wait_all;" ::: "memory");
                fence_async_smem();
                named_bar(2, 128);
            });
            if (!(cta & 1)) {
#pragma unroll
                for (int u = 0; u < 4; u++) {
                    const float v = rbf(facc[u]);
                    facc[u] = __fdividef(v, 1.0f + __expf(-v));
                }
            }
            st_relaxed2(&prm.s->hid[fid * 128 + at], pack_bf(facc[0], facc[1]), pack_bf(facc[2], facc[3]));
        }
        STAMPIF(at == 0, 26);
        gates();
        {
            mbar_wait(empty + 8 * max(TN(HG), 31));
            const uint2* hp = &prm.s->hid[(cta >> 4) * 14 * 128 + at];
            uint32_t hv[16];
            it = 0;
            while (true) {
                uint32_t top = 0;
#pragma unroll
                for (int j = 0; j < 7; j++) {
                    const uint2 hg = ld_relaxed2(hp + 256 * j), hu = ld_relaxed2(hp + 256 * j + 128);
                    top = max(top, max(hg.x, hu.x));
                    hv[2 * j] = mul_bf2(hg.x, hu.x); hv[2 * j + 1] = mul_bf2(hg.y, hu.y);
                }
                if (__all_sync(0xffffffffu, top != ~0u)) break;
                do {
                    if (++it > SPIN_LIMIT) __trap();
                } while (!__all_sync(0xffffffffu, ld_relaxed(hp + min(lane, 13) * 128 - lane) != ~0u));
            }
            STAMPIF(at == 0 && it > 0, 61);
            hv[14] = hv[15] = 0;
#pragma unroll
            for (int j = 0; j < 4; j++)
                asm volatile("stmatrix.sync.aligned.m8n8.x4.trans.shared.b16 [%0], {%1, %2, %3, %4};" ::"r"(
                                 sb + OFF_HID + (2 * j + (lane >> 4)) * 1024 + (lane & 7) * 128 + (((2 * w + ((lane >> 3) & 1)) ^ (lane & 7)) << 4)),
                             "r"(hv[4 * j]), "r"(hv[4 * j + 1]), "r"(hv[4 * j + 2]), "r"(hv[4 * j + 3]) : "memory");
        }
        fence_async_smem();
        named_bar(2, 128);
        STAMPIF(at == 0, 27);
        uint32_t mine = __ballot_sync(0xffffffffu, lane < 8 && (int)((~sel[lane & 7] & 2047u) >> 7) == chunk), tr;
        uint2 xr, xd;
        float gr, rs;
        auto skip = [&](int n) {
#pragma unroll 1
            for (int i = 0; i < n; i++) mine &= mine - 1;
            if (mine) {
                const uint32_t key = sel[__ffs(mine) - 1], kb = key >> 16;
                tr = ~key & 2047u;
                xr = __ldg(reinterpret_cast<const uint2*>(prm.x + (size_t)tr * D_ + dt * 128) + lane);
                rs = rbf(sigmoidf_(bf_lo((kb & 0x8000u) ? (kb & 0x7FFFu) : (~kb & 0xFFFFu))));
                gr = fabsf(__bfloat162float(reinterpret_cast<const __nv_bfloat16*>(smem + OFF_G)[tr & 127]));
                xd = lds64(sb + OFF_DK + 8 * lane);
            }
        };
        skip(w);
        down();
#pragma unroll
        for (int u = 0; u < 4; u++)
            st_relaxed(&prm.s->y[((2 * c + (u & 1)) * 8 + (cta >> 4)) * D_ + (cta & 15) * 64 + w * 16 + g + 8 * (u >> 1)], (__float_as_uint(facc[u]) & ~3u) | t2);
        STAMPIF(at == 0, 28);
        sleep_until(clk32() + TN(T_Y));
        while (mine) {
            const uint32_t* yp = &prm.s->y[(__ffs(mine) - 1) * 8 * D_ + dt * 128 + 4 * lane];
            float y[4];
            it = 0;
            while (true) {
                uint32_t bad = 0;
                y[0] = y[1] = y[2] = y[3] = 0.f;
#pragma unroll
                for (int ks = 0; ks < 8; ks++) {
                    const uint4 v = ld_relaxed4(yp + ks * D_);
                    bad |= v.x ^ t2;
                    y[0] += __uint_as_float(v.x); y[1] += __uint_as_float(v.y); y[2] += __uint_as_float(v.z); y[3] += __uint_as_float(v.w);
                }
                if (__all_sync(0xffffffffu, (bad & 3u) == 0)) break;
                if (++it > SPIN_LIMIT) __trap();
            }
            STAMPIF(lane == 0 && it, 62);
#pragma unroll
            for (int u = 0; u < 4; u++) {
                const uint32_t x2 = (u & 2) ? xr.y : xr.x, d2 = mul_bf2(x2, (u & 2) ? xd.y : xd.x);
                y[u] = fmaf(gr, (u & 1) ? bf_hi(d2) : bf_lo(d2), rbf(rbf(1.0f - gr) * rbf(((u & 1) ? bf_hi(x2) : bf_lo(x2)) + rbf(rbf(y[u]) * rs))));
            }
            STAMPIF(lane == 0, 50);
            mbar_wait(bar_stored);
            asm volatile("red.global.add.v4.f32 [%0], {%1, %2, %3, %4};" ::"l"(prm.out + (size_t)tr * D_ + dt * 128 + 4 * lane), "f"(y[0]), "f"(y[1]), "f"(y[2]), "f"(y[3]) : "memory");
            skip(4);
        }
        LSTAMP(lane == 0, 96 + 29);
    } else {
        asm volatile("setmaxnreg.dec.sync.aligned.u32 40;");
        if (warp != 12) sleep_until(cstart + (warp == 13 ? TN(T_SMALL) : TN(T_W3)));
        auto behind = [&](int e) {
            if (!mbar_test(empty + 8 * e, 0)) {
                mbar_wait(empty + 8 * e);
                if (TN(T_X0)) sleep_until(clk32() + TN(T_X0));
            }
        };
        if (warp == 15) {
            prefetch_map(&mXr);
            named_bar(0, 480);
#pragma unroll 1
            for (int i = 0; i < 4; i++) {
                const int u = i;
                if (lane == 0) mbar_expect_tx(ffull + 8 * u, TILE);
                sleep_until(cstart + (i == 0 ? TN(RT0) : i == 1 ? TN(RT1) : i == 2 ? TN(RT2) : TN(RT3)));
                if (elect_one()) tma3(sb + OFF_FT + u * TILE, &mXr, u * 256, rid * 16, ffull + 8 * u);
                STAMP(53 + u);
            }
            const CUtensorMap* mw = (cta & 1) ? &mWu : &mWg;
            if (sb & 1023) __trap();
            prefetch_map(mw);
            prefetch_map(&mWd);
            uint32_t slot = 4, par = 1;
#pragma unroll 1
            for (int j = 0; j < (has_gu && DBG != 1 ? 16 : 0); j++) {
                mbar_wait(fempty + 8 * slot, par);
                if (lane == 0) mbar_expect_tx(ffull + 8 * slot, TILE);
                behind(prm.fetch[j]);
                STAMPW(1, 176 + j);
                if (elect_one()) tma2(sb + OFF_FT + slot * TILE, mw, (fid >> 1) * 64, TN(WDBG) ? 0 : j * 64, ffull + 8 * slot);
                if (++slot == NFT) { slot = 0; par ^= 1; }
            }
            if (lane < 9) mbar_expect_tx(lane < 7 ? dfull + 8 * lane : bar_x + 8 * (lane - 7), lane < 7 ? TILE : 2 * TILE);
            if (!has_gu) mbar_wait(bar_g);
#pragma unroll 1
            for (int j = 0; j < (DBG != 1 ? 7 : 0); j++) {
                if (has_gu) mbar_wait(fempty + 8 * min(j, 4), 1);
                behind(prm.fetch[16 + j]);
                if (elect_one()) tma2(sb + OFF_FT + j * TILE, &mWd, (cta & 15) * 64, (cta >> 4) * 448 + (TN(WDBG) ? 0 : j * 64), dfull + 8 * j);
            }
            prefetch_map(&mXe);
#pragma unroll 1
            for (int u = 0; u < 4; u++) {
                mbar_wait(bar_dfree + 8 * (u & 2));
                behind(TN(DN_E0) + u);
                if (elect_one())
                    asm volatile("cp.async.bulk.tensor.5d.shared::cluster.global.mbarrier::complete_tx::bytes [%0], [%1, {%3, %6, %6, %4, %5}], [%2];"
                                 ::"r"(sb + OFF_FT + (u < 2 ? u : u + 3) * TILE), "l"(&mXe), "r"(bar_x + 4 * (u & 2)), "r"(dt * 128 + (u & 1) * 64), "r"(u & 2), "r"(chunk * 4), "r"(0) : "memory");
            }
        } else if (warp == 13) {
#pragma unroll
            for (int u = 0; u < 8; u++) {
                const int row = (u >> 2) * 4 + (lane >> 3);
                cp_async16(sb + OFF_XS + (u & 3) * 1024 + row * 128 + (((lane & 7) ^ row) << 4), (const char*)(u < 4 ? prm.w_r : prm.gate_w) + (u & 3) * 512 + lane * 16);
            }
            STAMP(57);
            const uint32_t tag = ld_relaxed(&prm.s->epoch[cta]) + 1;
            named_bar(1, 64);
            *reinterpret_cast<uint2*>(smem + OFF_EPOCH) = make_uint2(tag, tag % 3u + 1u);
            STAMPIF(tag, 58);
            asm volatile("cp.async.wait_all;" ::: "memory");
            STAMP(59);
            fence_async_smem();
            __syncwarp();
            if (lane == 0) {
                mbar_arrive(bar_epoch);
                prm.s->epoch[cta] = tag;
            }
            sleep_until(cstart + TN(T_BASE));
            {
                const uint2 st = ld_relaxed2(&prm.s->start[2 * lane]);
                const uint32_t d = st.x - cstart + 512u, age = gtime32() - st.y;
                const uint32_t m = __reduce_max_sync(0xffffffffu, d < 1024u && age < 4096u ? (d << 12) | age : 0u);
                const uint32_t late = (m & 4095u) - __reduce_min_sync(0xffffffffu, age);
                *reinterpret_cast<volatile uint32_t*>(smem + OFF_EPOCH + 8) = cstart + (m ? (m >> 12) - 512u + min(late, 256u) * TN(G_NS) / 4 : 0u);
                __syncwarp();
                if (lane == 0) mbar_arrive(bar_base);
                STAMP(60);
            }
            mbar_wait(bar_const);
            asm volatile("fence.acq_rel.gpu;" ::: "memory");
            if (lane < 4) st_relaxed2(&prm.s->armed[fid * 4 + lane], tag % 3u + 1u, 0u);
            prefetch_map(&mCre);
            prefetch_map(&mCim);
            const char* src = reinterpret_cast<const char*>(prm.s->h) + (size_t)chunk * 524288;
            uint32_t slot = 32 % NST, hpar = 0, rpar = 0;
#pragma unroll 1
            for (int i = 32; i < CH1; i++) {
                mbar_wait(hfull + 8 * slot, hpar);
                STAMPIF(i == 32 || i == 33, 14 + (i & 1));
                rpar = check_tile<16>(sb, sb + slot * SLOT, probe, src, tag, bar_retry, rpar, TN(T_RETRY));
                if (lane == 0) mbar_expect_tx(full + 8 * i, 2 * TILE);
                STAMPIF(i == 32 || i == 33, 16 + (i & 1));
                src += 2 * TILE;
                slot = slot == NST - 1 ? 0 : slot + 1;
                hpar ^= slot == 32 % NST;
            }
        } else if (warp == 14) {
            prefetch_map(&mPB);
            auto pf_c = [&](int k) { if (!(NOPF & 4)) prefetch_slice(&mPC, 4 * (k >> 1), cta * 8 + (k & 1) * 4); };
            named_bar(0, 480);
            asm volatile("bar.arrive 1, 64;" ::: "memory");
            if (lane < 24) st_relaxed(lane < 8 ? &prm.s->key[cta * 8 + lane] : &prm.s->gate[rid * 16 + lane - 8], 0u);
#pragma unroll 1
            for (int k = TN(PF0) ? 0 : 1; k < 4; k++) {
                sleep_until(cstart + (k == 0 ? TN(PF0) : k == 1 ? TN(PF1) : k == 2 ? TN(PF2) : TN(PF3)));
                if (!(NOPF & 1)) { if (elect_one()) prefetch_slice(&mPB, 4 * k, cta * 4); }
            }
#pragma unroll 1
            for (int k = 0; k < 4; k++) {
                behind(TN(PB_E0) + TN(PB_STEP) * k);
                if (!(NOPF & 2)) { if (elect_one()) prefetch_slice(&mPB, 4 * k, 512 + cta * 4); }
            }
#pragma unroll 1
            for (int k = 0; k < TN(PC_N); k++) {
                behind(min(TN(PC_E0) + TN(PC_STEP) * k / 2, 25));
                if (elect_one()) pf_c(k);
            }
            int pk = TN(PC_N), pe = TN(PC_E1);
            auto own_part = [&](int e) {
                if (!mbar_test(bar_out + 8 * e, 0)) {
                    mbar_wait(bar_out + 8 * e);
                    sleep_until(clk32() + TN(T_OWN));
                    STAMP(11);
                }
            };
            const char* src = reinterpret_cast<const char*>(prm.s->h) + (size_t)chunk * 524288;
            uint32_t slot = 32 % NST;
#pragma unroll 1
            for (int i = 32; i < NBIG; i++) {
                if (!(i & 3)) own_part((i - 32) >> 2);
                mbar_wait(empty + 8 * (i - NST));
                PSTAMP(i);
                if (elect_one()) {
                    mbar_expect_tx(hfull + 8 * slot, 2 * TILE);
                    bulk_load(sb + slot * SLOT, src, 2 * TILE, hfull + 8 * slot);
                    if (MERGE) tma5(sb + slot * SLOT + 2 * TILE, (i & 4) ? &mCim : &mCre, ((i & 3) + ((i >> 1) & 12)) * 64, dt * 8, full + 8 * i);
                }
                if (i == pe && pk < 8) {
                    if (elect_one()) pf_c(pk);
                    pk++; pe += TN(PC_S1);
                }
                src += 2 * TILE;
                slot = slot == NST - 1 ? 0 : slot + 1;
            }
#pragma unroll
            for (int k = 0; k < 14; k++) {
                if (!MERGE && k == 4) continue;
                if (k == 0 || k == 2) own_part(6 + k / 2);
                mbar_wait(empty + 8 * (NBIG - NST + k));
                if (MERGE && k >= 1 && k <= 4) {
                    if (elect_one()) {
#pragma unroll
                        for (int j = 2 * k - 2; j < 2 * k; j++) tma5(sb + tail_c(j), (j & 4) ? &mCim : &mCre, ((j & 3) + 12) * 64, dt * 8, full + 8 * (NBIG + j));
                    }
                }
                if (k == 4) continue;
                if (k == 2) mbar_wait(bar_dfree + 8);
                if (elect_one()) {
#pragma unroll
                    for (int n = k < 5 ? 2 * k : k + 2; n < (k < 3 ? 2 * k + 2 : k == 3 ? 7 : k + 3); n++) {
                        mbar_expect_tx(hfull + 8 * (NST + n % 7), TILE);
                        bulk_load(sb + tail_h(n), src + (n & 7) * 2 * TILE + (n >> 3) * TILE, TILE, hfull + 8 * (NST + n % 7));
                    }
                }
            }
        } else {
            if (elect_one()) {
#pragma unroll
                for (int i = 0; i < NST; i++) mbar_init(full + 8 * i, 1);
                fence_mbar_init();
            }
            __syncwarp();
            asm volatile("bar.arrive 5, 160;" ::: "memory");
#pragma unroll 1
            for (int i = 0; i < NST; i++) {
                if (elect_one()) {
                    mbar_expect_tx(full + 8 * i, SLOT);
                    tma5b(sb + i * SLOT, &mB, i * 64, dt * 4, full + 8 * i);
                    tma4(sb + i * SLOT + 2 * TILE, &mX, i * 64, chunk * 64, full + 8 * i);
                }
                STAMPIF(i == 0, 1);
            }
            STAMP(2);
            asm volatile("bar.arrive 0, 480;" ::: "memory");
            named_bar(6, 160);
            uint32_t dst = sb;
#pragma unroll 1
            for (int i = NST; i < 32; i++) {
                if (i == 2 * NST) mbar_wait(bar_base);
                if (lane == 0) mbar_expect_tx(full + 8 * i, SLOT);
                mbar_wait(empty + 8 * (i - NST));
                PSTAMP(i);
                if (elect_one()) {
                    tma5b(dst, &mB, (i & 15) * 64, (i >> 4) * 64 + dt * 4, full + 8 * i);
                    tma4(dst + 2 * TILE, &mX, (i & 15) * 64, chunk * 64, full + 8 * i);
                }
                dst = dst == sb + (NST - 1) * SLOT ? sb : dst + SLOT;
            }
        }
    }
}

typedef CUresult (*EncodeFn)(CUtensorMap*, CUtensorMapDataType, cuuint32_t, void*, const cuuint64_t*, const cuuint64_t*, const cuuint32_t*,
                             const cuuint32_t*, CUtensorMapInterleave, CUtensorMapSwizzle, CUtensorMapL2promotion, CUtensorMapFloatOOBfill);

bool encode(EncodeFn fn, CUtensorMap* m, const void* ptr, int rank, const cuuint64_t* dims, const cuuint64_t* strides, const cuuint32_t* box,
            CUtensorMapL2promotion promo = CU_TENSOR_MAP_L2_PROMOTION_NONE) {
    const cuuint32_t es[5] = {1, 1, 1, 1, 1};
    return fn(m, CU_TENSOR_MAP_DATA_TYPE_BFLOAT16, rank, const_cast<void*>(ptr), dims, strides, box, es, CU_TENSOR_MAP_INTERLEAVE_NONE,
              CU_TENSOR_MAP_SWIZZLE_128B, promo, CU_TENSOR_MAP_FLOAT_OOB_FILL_NONE) == CUDA_SUCCESS;
}

}

extern "C" void kernel_launch(void* const* d_in, const int* in_sizes, int n_in, void* d_out, int out_size) {
    (void)in_sizes; (void)n_in; (void)out_size;
    Params prm;
    prm.x = (const __nv_bfloat16*)d_in[0];
    prm.lam_re = (const __nv_bfloat16*)d_in[1];
    prm.lam_im = (const __nv_bfloat16*)d_in[2];
    prm.b_re = (const __nv_bfloat16*)d_in[3];
    prm.b_im = (const __nv_bfloat16*)d_in[4];
    prm.c_re = (const __nv_bfloat16*)d_in[5];
    prm.c_im = (const __nv_bfloat16*)d_in[6];
    prm.log_dt = (const __nv_bfloat16*)d_in[7];
    prm.dskip = (const __nv_bfloat16*)d_in[8];
    prm.w_r = (const __nv_bfloat16*)d_in[10];
    prm.gate_w = (const __nv_bfloat16*)d_in[14];
    prm.out = (float*)d_out;
    cudaGetSymbolAddress((void**)&prm.s, g_scratch);
    prm.swapped = prm.b_im < prm.b_re;

    void* fnp = nullptr;
    cudaDriverEntryPointQueryResult qr;
    cudaGetDriverEntryPoint("cuTensorMapEncodeTiled", &fnp, cudaEnableDefault, &qr);
    EncodeFn fn = (EncodeFn)fnp;
    cudaFuncSetAttribute(fused_kernel, cudaFuncAttributeMaxDynamicSharedMemorySize, SMEM_BYTES);

    CUtensorMap mX, mB, mCre, mCim, mWg, mWu, mWd, mXr, mPB, mPC, mXe;
    const cuuint64_t row = 2048;
    {
        const cuuint64_t dims[4] = {1024, 2, 4, 976}, st[3] = {row, 32 * row, 2 * row};
        const cuuint32_t box[4] = {64, 2, 4, 16};
        encode(fn, &mX, prm.x, 4, dims, st, box, PROMO);
    }
    {
        const char *lo = (const char*)(prm.swapped ? prm.b_im : prm.b_re), *hi = (const char*)(prm.swapped ? prm.b_re : prm.b_im);
        const cuuint64_t dims[5] = {1024, 8, 2, 96, 2}, st[4] = {row, (cuuint64_t)(hi - lo), 8 * row, 256 * row};
        const cuuint32_t box[5] = {64, 8, 2, 4, 2};
        encode(fn, &mB, lo, 5, dims, st, box, PROMO);
    }
    {
        const cuuint64_t dims[5] = {1024, 2, 4, 2, 64}, st[4] = {row, 4 * row, 2 * row, 16 * row};
        const cuuint32_t box[5] = {64, 2, 4, 2, 8};
        encode(fn, &mCre, prm.c_re, 5, dims, st, box);
        encode(fn, &mCim, prm.c_im, 5, dims, st, box);
    }
    {
        const cuuint64_t dims[2] = {F_, D_}, st[1] = {F_ * 2}, dimsd[2] = {D_, F_}, std_[1] = {row};
        const cuuint32_t box[2] = {64, 64};
        encode(fn, &mWg, d_in[11], 2, dims, st, box);
        encode(fn, &mWu, d_in[12], 2, dims, st, box);
        encode(fn, &mWd, d_in[13], 2, dimsd, std_, box);
    }
    for (int i = 0; i < 2; i++) {
        const char *p = (const char*)(i ? prm.c_re : prm.b_re), *q = (const char*)(i ? prm.c_im : prm.b_im);
        const cuuint64_t dims[4] = {64, 16, 1024, 2}, st[3] = {128, row, (cuuint64_t)(p < q ? q - p : p - q)};
        const cuuint32_t box[4] = {16, 4, 4, 2};
        encode(fn, i ? &mPC : &mPB, p < q ? p : q, 4, dims, st, box, CU_TENSOR_MAP_L2_PROMOTION_L2_128B);
    }
    {
        const cuuint64_t dims[3] = {D_ - 192, S_, 4}, st[2] = {row, 128};
        const cuuint32_t box[3] = {64, 16, 4};
        encode(fn, &mXr, prm.x, 3, dims, st, box);
    }
    {
        const cuuint64_t dims[5] = {1024, 2, 4, 4, S_ / 32}, st[4] = {4 * row, row, 8 * row, 32 * row};
        const cuuint32_t box[5] = {64, 2, 4, 2, 4};
        encode(fn, &mXe, prm.x, 5, dims, st, box);
    }
    for (int j = 0, e4 = 4 * TN(GC0); j < 23; j++) {
        prm.fetch[j] = j < NFT ? TN(GU_E0) + j * TN(W_NUM) / 4 : j < 16 ? 0 : TN(DL0) + (j - 16) * TN(DLS) / 4;
        prm.use[j] = j < 16 ? e4 / 4 : TN(DC0) + (j - 16) * TN(DCS) / 4;
        const int last = 54;
        if (prm.fetch[j] > last) prm.fetch[j] = last;
        if (prm.use[j] > last) prm.use[j] = last;
        e4 += j < TN(N1) ? TN(GCS) : j < TN(N2) ? TN(GCS2) : j < 10 ? TN(GCS3) : TN(GCS4);
    }
    fused_kernel<<<NCTA, 512, SMEM_BYTES, cudaStreamPerThread>>>(prm, mX, mB, mCre, mCim, mWg, mWu, mWd, mXr, mPB, mPC, mXe);
}
```

```cpp
#include <cuda_runtime.h>
#include <cuda_bf16.h>
#include <cuda.h>
#include <stdint.h>

namespace {

constexpr int S_ = 2048, D_ = 1024, F_ = 3584;
constexpr int NCTA = 128;
constexpr int NSPL = 9, NBIG = 64 - NSPL, NENT = NBIG + 2 * NSPL;
constexpr int NST = 5;
constexpr int NFT = 5;
constexpr uint32_t SLOT = 32768, TILE = 8192;
constexpr uint32_t OFF_FT = NST * SLOT;
constexpr uint32_t OFF_XS = OFF_FT + NFT * TILE;
constexpr uint32_t OFF_LIST = OFF_XS + 8192;
constexpr uint32_t OFF_RED = OFF_XS + 4096;
constexpr uint32_t OFF_CONST = OFF_XS + 16384;
constexpr uint32_t OFF_M = OFF_CONST + 8192;
constexpr uint32_t OFF_HID = OFF_CONST;
constexpr uint32_t OFF_G = OFF_M + 512;
constexpr uint32_t OFF_DK = OFF_G + 256;
constexpr uint32_t OFF_FULL = OFF_DK + 256;
constexpr uint32_t OFF_EMPTY = OFF_FULL + 103 * 8;
constexpr uint32_t OFF_KEYS = OFF_EMPTY + 87 * 8;
constexpr uint32_t OFF_SEL = OFF_KEYS + 32;
constexpr uint32_t OFF_EPOCH = OFF_SEL + 32;
constexpr uint32_t OFF_PROF = OFF_EPOCH + 16;
constexpr uint32_t SMEM_BYTES = OFF_PROF + 432;
static_assert(SMEM_BYTES <= 232448, "smem");

static_assert(NBIG % NST == 0, "tail layout");
__host__ __device__ constexpr uint32_t tail_c(int j) { return j < 8 ? SLOT + j * 2 * TILE : OFF_FT + 5 * TILE; }
__host__ __device__ constexpr uint32_t tail_h(int n) { return n % 7 < 4 ? n % 7 * TILE : OFF_FT + (n % 7 - 2) * TILE; }
__host__ __device__ constexpr uint32_t tail_src(int n) { return (n % NSPL + NBIG - 32) * 2 * TILE + n / NSPL * TILE; }
__host__ __device__ constexpr int c_col(int i) { return ((i & 3) + ((i >> 1) & 12)) * 64; }

constexpr uint32_t SPIN_LIMIT = 1u << 18;

struct Scratch {
    uint2 carry[16 * 1024];
    uint2 hid[NCTA * 128];
    uint32_t y[8 * 8 * D_];
    uint32_t key[NCTA * 8];
    uint32_t gate[S_];
    uint2 armed[NCTA * 4];
    unsigned int epoch[256];
    uint4 start[32 * 2];
    uint4 h[16 * 32 * 1024];
};
__device__ __align__(1024) Scratch g_scratch;
#define STAMPW_(cond, w) do {} while (0)
#define GSTAMP(cond, w) do {} while (0)
#define LSTAMP(cond, w) STAMPW_(cond, w)
#define LT 0
#define STAMPW(cond, w) STAMPW_(cond, w)
#define STAMPIF(cond, i) STAMPW(cond, 96 + (i))
#define STAMP(i) STAMPW(1, 96 + (i))
#define KSTAMP(i) STAMPW((threadIdx.x & 127) == 0, i)
#define PSTAMP(i) STAMPW((i) < 56 && (i) >= 32, 160 + (i))

struct Params {
    const __nv_bfloat16 *x, *b_re, *b_im, *lam_re, *lam_im, *c_re, *c_im, *log_dt, *dskip, *w_r, *gate_w;
    float* out;
    Scratch* s;
    int fetch[23], use[23];
    int swapped;
};

__device__ __forceinline__ uint32_t smem_u32(const void* p) { return (uint32_t)__cvta_generic_to_shared(p); }
__device__ __forceinline__ void mbar_init(uint32_t bar, uint32_t cnt) { asm volatile("mbarrier.init.shared::cta.b64 [%0], %1;" ::"r"(bar), "r"(cnt) : "memory"); }
__device__ __forceinline__ void mbar_expect_tx(uint32_t bar, uint32_t bytes) { asm volatile("mbarrier.arrive.expect_tx.shared::cta.b64 _, [%0], %1;" ::"r"(bar), "r"(bytes) : "memory"); }
__device__ __forceinline__ void mbar_arrive(uint32_t bar) { asm volatile("mbarrier.arrive.shared::cta.b64 _, [%0];" ::"r"(bar) : "memory"); }
__device__ __forceinline__ bool mbar_try(uint32_t bar, uint32_t parity) {
    uint32_t ok;
    asm volatile("{ .reg .pred p; mbarrier.try_wait.parity.shared::cta.b64 p, [%1], %2; selp.u32 %0, 1, 0, p; }" : "=r"(ok) : "r"(bar), "r"(parity) : "memory");
    return ok;
}
__device__ __forceinline__ bool mbar_test(uint32_t bar, uint32_t parity) {
    uint32_t ok;
    asm volatile("{ .reg .pred p; mbarrier.test_wait.parity.shared::cta.b64 p, [%1], %2; selp.u32 %0, 1, 0, p; }" : "=r"(ok) : "r"(bar), "r"(parity) : "memory");
    return __all_sync(0xffffffffu, ok);
}
__device__ __forceinline__ void mbar_wait(uint32_t bar, uint32_t parity = 0) {
    if (mbar_try(bar, parity)) return;
#pragma unroll 1
    for (uint32_t it = 0; it < SPIN_LIMIT; ++it)
        if (mbar_try(bar, parity)) return;
    __trap();
}
__device__ __forceinline__ bool elect_one() {
    uint32_t pred;
    asm volatile("{ .reg .pred P; elect.sync _|P, 0xffffffff; selp.b32 %0, 1, 0, P; }" : "=r"(pred));
    return pred;
}
__device__ __forceinline__ void named_bar(int id, int n) { asm volatile("bar.sync %0, %1;" ::"r"(id), "r"(n) : "memory"); }
__device__ __forceinline__ void fence_mbar_init() { asm volatile("fence.mbarrier_init.release.cluster;" ::: "memory"); }
__device__ __forceinline__ void fence_async_smem() { asm volatile("fence.proxy.async.shared::cta;" ::: "memory"); }

__device__ __forceinline__ void bulk_load(uint32_t dst, const void* src, uint32_t bytes, uint32_t bar) {
    asm volatile("cp.async.bulk.shared::cluster.global.mbarrier::complete_tx::bytes [%0], [%1], %2, [%3];" ::"r"(dst), "l"(src), "r"(bytes), "r"(bar) : "memory");
}
__device__ __forceinline__ void cp_async16(uint32_t dst, const void* src) { asm volatile("cp.async.cg.shared.global [%0], [%1], 16;" ::"r"(dst), "l"(src) : "memory"); }
__device__ __forceinline__ void sts128(uint32_t a, uint32_t x, uint32_t y, uint32_t z, uint32_t w) {
    asm volatile("st.shared.v4.u32 [%0], {%1,%2,%3,%4};" ::"r"(a), "r"(x), "r"(y), "r"(z), "r"(w) : "memory");
}
__device__ __forceinline__ uint2 lds64(uint32_t a) {
    uint2 v;
    asm volatile("ld.shared.v2.u32 {%0,%1}, [%2];" : "=r"(v.x), "=r"(v.y) : "r"(a) : "memory");
    return v;
}
__device__ __forceinline__ uint32_t lds32(uint32_t a) {
    uint32_t v;
    asm volatile("ld.volatile.shared.u32 %0, [%1];" : "=r"(v) : "r"(a) : "memory");
    return v;
}
__device__ __forceinline__ void stg128(void* p, uint32_t x, uint32_t y, uint32_t z, uint32_t w) {
    asm volatile("st.global.v4.u32 [%0], {%1,%2,%3,%4};" ::"l"(p), "r"(x), "r"(y), "r"(z), "r"(w) : "memory");
}
__device__ __forceinline__ void st_relaxed(void* p, uint32_t x) { asm volatile("st.relaxed.gpu.global.b32 [%0], %1;" ::"l"(p), "r"(x) : "memory"); }
__device__ __forceinline__ void st_relaxed2(void* p, uint32_t x, uint32_t y) { asm volatile("st.relaxed.gpu.global.v2.b32 [%0], {%1, %2};" ::"l"(p), "r"(x), "r"(y) : "memory"); }
__device__ __forceinline__ void st_relaxed4(void* p, uint32_t x, uint32_t y, uint32_t z, uint32_t w) {
    asm volatile("st.relaxed.gpu.global.v4.b32 [%0], {%1, %2, %3, %4};" ::"l"(p), "r"(x), "r"(y), "r"(z), "r"(w) : "memory");
}
__device__ __forceinline__ uint32_t ld_relaxed(const void* p) {
    uint32_t v;
    asm volatile("ld.relaxed.gpu.global.b32 %0, [%1];" : "=r"(v) : "l"(p) : "memory");
    return v;
}
__device__ __forceinline__ uint2 ld_relaxed2(const void* p) {
    uint2 v;
    asm volatile("ld.relaxed.gpu.global.v2.b32 {%0, %1}, [%2];" : "=r"(v.x), "=r"(v.y) : "l"(p) : "memory");
    return v;
}
__device__ __forceinline__ uint4 ld_relaxed4(const void* p) {
    uint4 v;
    asm volatile("ld.relaxed.gpu.global.v4.b32 {%0, %1, %2, %3}, [%4];" : "=r"(v.x), "=r"(v.y), "=r"(v.z), "=r"(v.w) : "l"(p) : "memory");
    return v;
}
__device__ __forceinline__ uint32_t clk32() { uint32_t c; asm volatile("mov.u32 %0, %%clock;" : "=r"(c)); return c; }
__device__ __forceinline__ uint32_t gtime32() { uint32_t c; asm volatile("mov.u32 %0, %%globaltimer_lo;" : "=r"(c)); return c; }
__device__ __forceinline__ void sched_fence(uint32_t t) { while ((int)(clk32() - t) < 0) {} }
__device__ __forceinline__ void sleep_until(uint32_t t) { while ((int)(clk32() - t) < 0) __nanosleep(40); }

__device__ __forceinline__ void tma2(uint32_t dst, const CUtensorMap* m, int c0, int c1, uint32_t bar) {
    asm volatile("{ .reg .b64 pol; createpolicy.fractional.L2::evict_first.b64 pol;\n"
                 "cp.async.bulk.tensor.2d.shared::cluster.global.mbarrier::complete_tx::bytes.L2::cache_hint [%0], [%1, {%3, %4}], [%2], pol; }"
                 ::"r"(dst), "l"(m), "r"(bar), "r"(c0), "r"(c1) : "memory");
}
__device__ __forceinline__ void tma3(uint32_t dst, const CUtensorMap* m, int c0, int c1, uint32_t bar) {
    asm volatile("cp.async.bulk.tensor.3d.shared::cluster.global.mbarrier::complete_tx::bytes [%0], [%1, {%3, %4, %5}], [%2];"
                 ::"r"(dst), "l"(m), "r"(bar), "r"(c0), "r"(c1), "r"(0) : "memory");
}
__device__ __forceinline__ void tma4(uint32_t dst, const CUtensorMap* m, int c0, int c3, uint32_t bar) {
    asm volatile("cp.async.bulk.tensor.4d.shared::cluster.global.mbarrier::complete_tx::bytes [%0], [%1, {%3, %5, %5, %4}], [%2];"
                 ::"r"(dst), "l"(m), "r"(bar), "r"(c0), "r"(c3), "r"(0) : "memory");
}
__device__ __forceinline__ void tma5(uint32_t dst, const CUtensorMap* m, int c0, int c4, uint32_t bar) {
    asm volatile("cp.async.bulk.tensor.5d.shared::cluster.global.mbarrier::complete_tx::bytes [%0], [%1, {%3, %5, %5, %5, %4}], [%2];"
                 ::"r"(dst), "l"(m), "r"(bar), "r"(c0), "r"(c4), "r"(0) : "memory");
}
__device__ __forceinline__ void tma5b(uint32_t dst, const CUtensorMap* m, int c0, int c3, uint32_t bar) {
    asm volatile("cp.async.bulk.tensor.5d.shared::cluster.global.mbarrier::complete_tx::bytes [%0], [%1, {%3, %5, %5, %4, %5}], [%2];"
                 ::"r"(dst), "l"(m), "r"(bar), "r"(c0), "r"(c3), "r"(0) : "memory");
}
__device__ __forceinline__ void prefetch_l2(const void* p) { asm volatile("prefetch.global.L2 [%0];" ::"l"(p)); }
__device__ __forceinline__ void prefetch_slice(const CUtensorMap* m, int line, int row) {
    asm volatile("cp.async.bulk.prefetch.tensor.4d.L2.global [%0, {%3, %1, %2, %3}];" ::"l"(m), "r"(line), "r"(row), "r"(0) : "memory");
}
__device__ __forceinline__ void prefetch_map(const CUtensorMap* m) { asm volatile("prefetch.tensormap [%0];" ::"l"(m)); }
__device__ __forceinline__ uint32_t uni(uint32_t v) { return __shfl_sync(0xffffffffu, v, 0); }

__device__ __forceinline__ uint32_t make_desc(uint32_t addr) { return ((addr & 0x3FFFF) >> 4) | (1u << 16); }
__device__ __forceinline__ uint32_t make_desc_h(uint32_t addr) { return ((addr & 0x3FFFF) >> 4) | (32u << 16); }
template <int H> __device__ __forceinline__ uint64_t desc64(uint32_t lo) {
    uint64_t d;
    asm volatile("mov.b64 %0, {%1, %2};" : "=l"(d) : "r"(lo), "n"(64u | ((H ? 2u : 1u) << 30)));
    return d;
}
__device__ __forceinline__ void wgmma_fence() { asm volatile("wgmma.fence.sync.aligned;" ::: "memory"); }
__device__ __forceinline__ void wgmma_commit() { asm volatile("wgmma.commit_group.sync.aligned;" ::: "memory"); }
template <int N> __device__ __forceinline__ void wgmma_wait() { asm volatile("wgmma.wait_group.sync.aligned %0;" ::"n"(N) : "memory"); }

#define R8(d, i) "+f"(d[i]), "+f"(d[i + 1]), "+f"(d[i + 2]), "+f"(d[i + 3]), "+f"(d[i + 4]), "+f"(d[i + 5]), "+f"(d[i + 6]), "+f"(d[i + 7])
#define R64(d) R8(d, 0), R8(d, 8), R8(d, 16), R8(d, 24), R8(d, 32), R8(d, 40), R8(d, 48), R8(d, 56)
template <int TA>
__device__ __forceinline__ void wgmma_n128(float (&d)[64], uint64_t da, uint64_t db, int scale_d = 1) {
    asm volatile("{ .reg .pred p; setp.ne.b32 p, %66, 0;\n"
                 "wgmma.mma_async.sync.aligned.m64n128k16.f32.bf16.bf16 "
                 "{%0,%1,%2,%3,%4,%5,%6,%7,%8,%9,%10,%11,%12,%13,%14,%15,%16,%17,%18,%19,%20,%21,%22,%23,%24,%25,%26,%27,%28,%29,%30,%31,"
                 "%32,%33,%34,%35,%36,%37,%38,%39,%40,%41,%42,%43,%44,%45,%46,%47,%48,%49,%50,%51,%52,%53,%54,%55,%56,%57,%58,%59,%60,%61,%62,%63}, "
                 "%64, %65, p, 1, 1, %67, 0; }"
                 : R64(d)
                 : "l"(da), "l"(db), "r"(scale_d), "n"(TA));
}
__device__ __forceinline__ void pin4(float (&d)[4]) { asm volatile("" : "+f"(d[0]), "+f"(d[1]), "+f"(d[2]), "+f"(d[3])::"memory"); }
__device__ __forceinline__ void pin64(float (&d)[64]) { asm volatile("" : R64(d)::"memory"); }

template <int TA>
__device__ __forceinline__ void wgmma_n8(float (&d)[4], uint64_t da, uint64_t db, int scale_d = 1) {
    asm volatile("{ .reg .pred p; setp.ne.b32 p, %7, 0;\n"
                 "wgmma.mma_async.sync.aligned.m64n8k16.f32.bf16.bf16 {%0,%1,%2,%3}, %4, %5, p, 1, 1, %6, 0; }"
                 : "+f"(d[0]), "+f"(d[1]), "+f"(d[2]), "+f"(d[3])
                 : "l"(da), "l"(db), "n"(TA), "r"(scale_d));
}

__device__ __forceinline__ float bf_lo(uint32_t u) { return __uint_as_float(u << 16); }
__device__ __forceinline__ float bf_hi(uint32_t u) { return __uint_as_float(u & 0xFFFF0000u); }
__device__ __forceinline__ float rbf(float v) { return __bfloat162float(__float2bfloat16_rn(v)); }
__device__ __forceinline__ uint32_t pack_bf(float lo, float hi) {
    uint32_t r;
    asm("cvt.rn.bf16x2.f32 %0, %1, %2;" : "=r"(r) : "f"(hi), "f"(lo));
    return r;
}
__device__ __forceinline__ uint32_t mul_bf2(uint32_t a, uint32_t b) {
    uint32_t r;
    asm("mul.rn.bf16x2 %0, %1, %2;" : "=r"(r) : "r"(a), "r"(b));
    return r;
}
__device__ __forceinline__ uint32_t fma_bf2(uint32_t a, uint32_t b, uint32_t c) {
    uint32_t r;
    asm("fma.rn.bf16x2 %0, %1, %2, %3;" : "=r"(r) : "r"(a), "r"(b), "r"(c));
    return r;
}
__device__ __forceinline__ float2 cmul(float2 a, float2 b) { return make_float2(a.x * b.x - a.y * b.y, a.x * b.y + a.y * b.x); }
__device__ __forceinline__ float2 cfma(float2 a, float2 b, float2 c) {
    return make_float2(fmaf(a.x, b.x, fmaf(-a.y, b.y, c.x)), fmaf(a.x, b.y, fmaf(a.y, b.x, c.y)));
}
__device__ __forceinline__ float sigmoidf_(float v) { return __fdividef(1.0f, 1.0f + expf(-v)); }

#define SCHED_NAMES RT0, RT1, RT2, RT3, PF0, PF1, PF2, PF3, T_SMALL, T_INIT, T_X0, T_BASE, G_NS, GT0, GT1, GT2, G0, GAP0, GAP1, RS_E, \
    PB_E0, PB_STEP, PC_E0, PC_STEP, PC_N, PC_E1, PC_S1, GU_E0, W_NUM, GC0, N1, N2, GCS, GCS2, GCS3, GCS4, HG, DL0, DLS, DC0, DCS, DN_E0, WDBG, T_OWN, T_RETRY, NP, T_Y, T_W0, T_W3
enum { SCHED_NAMES, NTUNE };
constexpr int sched_default[NTUNE] = {
    2200, 2700, 3200, 3700,
    0, 1100, 1300, 2800,
    1000, 1000, 200, 2500, 7,
    6200, 0, 0,
    1500, 250, 300, 4,
    4, 1, 9, 4, 5, 50, 3,
    4, 9, 15, 6, 6, 7, 7, 7, 5, 43, 37, 8, 38, 1, 49,
    0, 1100, 200, 0, 700, 600, 1000};
template <int I> struct Sched { static constexpr int v = sched_default[I]; };
#define TN(i) (Sched<i>::v)
#define DBG 0
#define NKK 4
#define EARLY 1
#define FROT 0
#define NOPF 0
#define NOGAP 0
#define TDBG 0
#define SRND 4
#define XPF 1
#define X0 1
#define GE 8
#define DOUBLE 0
#define RAISE_J 1
#define GREEDY 0
#define POLL_S 24
#define PROMO CU_TENSOR_MAP_L2_PROMOTION_L2_256B

template <int TA, class H>
__device__ __forceinline__ void run_entry(uint32_t lo32, uint32_t prev, int accumulate, float (&accA)[64], float (&accB)[64], H inside) {
    const uint64_t da = desc64<TA>(lo32), db = TA ? desc64<0>(lo32 + (2 * TILE >> 4) - (31u << 16)) : da + (2 * TILE >> 4);
    wgmma_fence();
#pragma unroll
    for (int kk = 0; kk < 4; kk++) {
        wgmma_n128<TA>(accA, da + kk * (TA ? 128 : 2), db + kk * 2, kk > 0 ? 1 : accumulate);
        wgmma_n128<TA>(accB, da + 512 + kk * (TA ? 128 : 2), db + kk * 2, kk > 0 ? 1 : accumulate);
        if (kk == 1) {
            wgmma_commit();
            wgmma_wait<1>();
            if ((threadIdx.x & 31) == 0) mbar_arrive(prev);
            inside();
        }
    }
    wgmma_commit();
}
template <int TA, class H>
__device__ __forceinline__ void run_entries(uint32_t sb, int lo, int hi, int slot, float (&accA)[64], float (&accB)[64], H after) {
    const uint32_t da0 = TA ? make_desc_h(sb) : make_desc(sb), dlast = da0 + (NST - 1) * (SLOT >> 4);
    uint32_t prev = sb + OFF_FULL + 8 * 101, bar = sb + OFF_FULL + 8 * lo, lo32 = da0 + slot * (SLOT >> 4);
    int accumulate = 0;
#pragma unroll 1
    for (int i = lo; i < hi; i++) {
        mbar_wait(bar);
        KSTAMP(i);
        run_entry<TA>(lo32, prev, accumulate, accA, accB, []() {});
        prev = bar + (OFF_EMPTY - OFF_FULL);
        bar += 8;
        lo32 = lo32 == dlast ? da0 : lo32 + (SLOT >> 4);
        accumulate = 1;
        after(i);
    }
}

template <int TA>
__device__ __forceinline__ void small_tile(float (&acc)[4], uint32_t alo, uint32_t blo, bool first) {
    const uint64_t da = desc64<0>(alo), db = desc64<0>(blo);
#pragma unroll
    for (int kk = 0; kk < 4; kk++) wgmma_n8<TA>(acc, da + kk * (TA ? 128 : 2), db + kk * 2, kk > 0 || !first);
}

template <int N>
__device__ __forceinline__ uint32_t check_tile(uint32_t sb, uint32_t dst, uint32_t probe, const char* src, uint32_t par, uint32_t bar, uint32_t phase, uint32_t pause) {
    if ((TDBG & 4) && N == 8) return phase;
#pragma unroll 1
    for (uint32_t it = 0; it < SPIN_LIMIT; it++) {
        uint32_t v[N], bad = 0;
#pragma unroll
        for (int u = 0; u < N; u++) v[u] = lds32(dst + probe + (u >> 1) * 2048 + (u & 1) * 256);
#pragma unroll
        for (int u = 0; u < N; u += 4)
            asm("{ .reg .b32 a, b; lop3.b32 a, %1, %2, %5, 0x7E; lop3.b32 b, %3, %4, %5, 0x7E; lop3.b32 %0, %0, a, b, 0xFE; }"
                : "+r"(bad) : "r"(v[u]), "r"(v[u + 1]), "r"(v[u + 2]), "r"(v[u + 3]), "r"(par));
        if (!__any_sync(0xffffffffu, bad & 1u)) return phase;
        STAMP(10);
        __nanosleep(pause);
        if (elect_one()) {
            mbar_expect_tx(bar, N * 1024);
            bulk_load(dst, src, N * 1024, bar);
        }
        mbar_wait(bar, phase);
        phase ^= 1;
    }
    __trap();
    return 0;
}

__global__ void __launch_bounds__(512, 1)
fused_kernel(const __grid_constant__ Params prm, const __grid_constant__ CUtensorMap mX, const __grid_constant__ CUtensorMap mB, const __grid_constant__ CUtensorMap mCre,
             const __grid_constant__ CUtensorMap mCim, const __grid_constant__ CUtensorMap mWg, const __grid_constant__ CUtensorMap mWu,
             const __grid_constant__ CUtensorMap mWd, const __grid_constant__ CUtensorMap mXr, const __grid_constant__ CUtensorMap mPB,
             const __grid_constant__ CUtensorMap mPC, const __grid_constant__ CUtensorMap mXe) {
    {
        const uint32_t t = threadIdx.x, b = blockIdx.x;
        const uint32_t row = t < 32 ? ((b & 60) * 2 + (b >> 6) * 4 + (b & 3)) * 16 + (t >> 1) : b * 4 + ((t >> 1) & 3);
        const char* base = (const char*)(t < 32 ? prm.x : t < 40 ? prm.b_re : prm.b_im);
        asm volatile("{ .reg .pred p; setp.lt.u32 p, %1, 48; @p prefetch.global.L2 [%0]; }" ::"l"(base + (row * 2048 + (t & 1) * 128)), "r"(t) : "memory");
    }
    extern __shared__ __align__(1024) uint8_t smem[];
    uint32_t sb;
    asm volatile("mov.u32 %0, %1;" : "=r"(sb) : "r"(smem_u32(smem)));
    const int tid = threadIdx.x, warp = __shfl_sync(0xffffffffu, tid >> 5, 0), lane = tid & 31;
    const int cta = blockIdx.x;
    const uint32_t cstart = clk32();
    const int chunk = (cta >> 2) & 15;
    const int dt = (cta >> 6) * 4 + (cta & 3);
    const int rid = chunk * 8 + dt;
    const int fid = (cta + FROT) & 127;
    const bool has_gu = fid < 112;
    const uint32_t full = sb + OFF_FULL, empty = sb + OFF_EMPTY;
    const uint32_t bar_epoch = full + 8 * 73, dfull = full + 8 * 74, bar_retry = full + 8 * 81, bar_x = full + 8 * 82, ffull = full + 8 * 84,
                   hfull = full + 8 * 89, bar_base = full + 8 * 102;
    const uint32_t fempty = empty + 8 * 66, bar_order = empty + 8 * 71, bar_stored = empty + 8 * 73, bar_dfree = empty + 8 * 74,
                   bar_out = empty + 8 * 77, bar_g = empty + 8 * 85, bar_const = empty + 8 * 86;
    const int w = warp & 3, g = lane >> 2, c = lane & 3, at = tid & 127;

    const uint32_t probe = (lane >> 3) * 32 + (g & 1) * 144 + (c & 1) * 520 + (c >> 1) * 1028;

    LSTAMP(tid == 0, 96);
    GSTAMP(tid == 0, 94);
    auto init_barriers = [&](uint32_t base, uint32_t cnt, auto n) {
        if (elect_one()) {
#pragma unroll
            for (int i = 0; i < n(); i++) mbar_init(base + 8 * i, cnt);
            fence_mbar_init();
        }
        __syncwarp();
    };
    if (warp != 12) {
        if (warp == 15 && !(cta & 3) && lane < 8) st_relaxed((uint32_t*)&prm.s->start[cta >> 1] + lane, (lane & 1) ? gtime32() : cstart);
        if (warp < 12) sleep_until(cstart + (warp < 4 ? TN(T_W0) : TN(T_INIT)));
    }
    if (warp < 8) {
        if (warp < 4) init_barriers(warp == 0 ? full + 40 : warp == 3 ? full + 8 * 98 : empty + 40 * (warp - 1), (warp + 1) & 2 ? 4 : 1, []() { return 5; });
        else init_barriers(full + 80 + 176 * w, 1, []() { return 22; });
        asm volatile("setmaxnreg.inc.sync.aligned.u32 192;");
        if (warp < 4) {
            named_bar(5, 160);
            asm volatile("bar.arrive 0, 480;" ::: "memory");
            asm volatile("bar.arrive 6, 160;" ::: "memory");
        } else named_bar(0, 480);
        const int wg = warp >> 2;
        const int p = wg * 512 + dt * 32 + w * 8 + g;
        uint32_t cp = sb + OFF_CONST + 8 * (wg * 64 + w * 8 + g), cw = cp + 1024 * c, cm = sb + OFF_M + 4 * (wg * 64 + w * 8 + g);
        const int j1 = chunk - 1 - c;
        uint2* cq = &prm.s->carry[j1 * 1024 + p];
        char* hd = reinterpret_cast<char*>(prm.s->h) + (size_t)chunk * 524288 + wg * 262144 + (dt >> 1) * 16384 + ((dt & 1) * 4 + w) * 1024 + g * 64 + ((c ^ (g >> 1)) << 4);
        const bool never = uni(cstart == 0 && sb == 0);
        asm volatile("" : "+l"(cq), "+l"(hd), "+r"(cp), "+r"(cw), "+r"(cm));
        float2 a[2], a32[2], a64[2], a512[2], pw32[2], pw128[2];
        uint32_t mm[2], t2, par;
        auto constants = [&](int h) {
            if (h) { t2 = lds32(sb + OFF_EPOCH + 4); par = lds32(sb + OFF_EPOCH); }
            auto ldc = [](uint32_t a) { const uint2 v = lds64(a); return make_float2(__uint_as_float(v.x), __uint_as_float(v.y)); };
            {
                a[h] = ldc(cp + 256 * h); a32[h] = ldc(cp + 256 * h + 1024); a64[h] = ldc(cp + 256 * h + 2048); a512[h] = ldc(cp + 256 * h + 7168);
                pw32[h] = ldc(cw + 256 * h);
                pw128[h] = ldc(cw + 256 * h + 3072);
                mm[h] = lds32(cm + 128 * h);
            }
        };
        if (wg == 1) {
            const int pc = w * 256 + dt * 32 + lane;
            const float lr = __bfloat162float(prm.lam_re[pc]), li = __bfloat162float(prm.lam_im[pc]), ld = __bfloat162float(prm.log_dt[pc]);
            const uint32_t dk = __ldg(reinterpret_cast<const uint32_t*>(prm.dskip + dt * 128) + (at & 63));
            reinterpret_cast<uint32_t*>(smem + OFF_DK)[at & 63] = dk;
            const float dtv = rbf(expf(ld));
            const float er = expf(dtv * lr);
            float sn, cs;
            sincosf(dtv * li, &sn, &cs);
            const float ar = er * cs, ai = er * sn;
            const float nr = ar - 1.0f, ni = ai;
            const bool big = fabsf(lr) >= fabsf(li);
            const float t = (big ? li : lr) / (big ? lr : li), dn = big ? lr + li * t : lr * t + li;
            const float cr = (big ? nr + ni * t : nr * t + ni) / dn, ci = (big ? ni - nr * t : ni * t - nr) / dn;
            float2* ct = reinterpret_cast<float2*>(smem + OFF_CONST) + at;
            float2 pw = make_float2(ar, prm.swapped ? -ai : ai);
            ct[0] = pw;
            const float mx = prm.swapped ? -2.f * ci : 2.f * cr, my = prm.swapped ? 2.f * cr : -2.f * ci;
            reinterpret_cast<uint32_t*>(smem + OFF_M)[at] = pack_bf(mx, my);
#pragma unroll
            for (int i = 0; i < 5; i++) pw = cmul(pw, pw);
#pragma unroll
            for (int i = 0; i < 2; i++) {
                const float2 p2 = cmul(pw, pw);
                ct[128 + 384 * i] = pw; ct[256 + 384 * i] = p2; ct[384 + 384 * i] = cmul(p2, pw);
                pw = cmul(p2, p2);
            }
            ct[896] = pw;
            mbar_wait(bar_epoch);
            __syncwarp();
            mbar_wait(empty + 8 * TN(RS_E));
            st_relaxed2(&prm.s->hid[fid * 128 + at], ~0u, ~0u);
            st_relaxed4(&prm.s->y[((at >> 4) * 8 + (cta >> 4)) * D_ + (cta & 15) * 64 + (at & 15) * 4], 0u, 0u, 0u, 0u);
            st_relaxed2(&prm.s->carry[chunk * 1024 + pc], 0u, 0u);
            __syncwarp();
            if (lane == 0) mbar_arrive(bar_const);

            STAMPIF(at == 0, 3);
            mbar_wait(bar_const);
            constants(0);
            constants(1);
            mbar_wait(bar_order);
        }

        float accA[64], accB[64];
        run_entries<0>(sb, wg * 16, wg * 16 + 15, wg, accA, accB, [&](int i) {
            if (i == GE - 1) {
                mbar_wait(bar_base);
                sched_fence(lds32(sb + OFF_EPOCH + 8) + TN(GT0));
            }
        });
        mbar_wait(full + 8 * (wg * 16 + 15));
        KSTAMP(wg * 16 + 15);
        if (wg == 0) {
            mbar_wait(bar_const);
            run_entry<0>(make_desc(sb), empty + 8 * 14, 1, accA, accB, [&]() { constants(0); constants(1); if (EARLY && lane == 0) mbar_arrive(bar_order); });
        } else run_entry<0>(make_desc(sb + SLOT), empty + 8 * 30, 1, accA, accB, [&]() { if (EARLY && lane == 0) mbar_arrive(bar_order + 8); });
        if (!EARLY && lane == 0) mbar_arrive(bar_order + 8 * wg);
        uint2 v[2][4];
#pragma unroll
        for (int m = 0; m < 8; m++) v[m >> 2][m & 3] = make_uint2(t2, t2);
        wgmma_wait<0>();
        pin64(accA); pin64(accB);
        if (lane == 0) mbar_arrive(empty + 8 * (wg * 16 + 15));
        LSTAMP(at == 0, 96 + 30 + 10 * wg); GSTAMP(LT && at == 0, 193 + wg);

        auto cut = [&]() { if (never) sched_fence(cstart); };
        auto poll = [&](uint2 (&u)[4], int h) {
#pragma unroll
            for (int m = 0; m < 4; m++)
                asm volatile("{ .reg .pred p; setp.ge.s32 p, %3, %4; @p ld.relaxed.gpu.global.v2.b32 {%0, %1}, [%2]; }"
                             : "+r"(u[m].x), "+r"(u[m].y) : "l"(cq + 256 * h - 4096 * m), "r"(j1), "r"(4 * m) : "memory");
        };
        auto check = [&](const uint2 (&u)[4]) {
            uint32_t bad = 0;
#pragma unroll
            for (int m = 0; m < 4; m++) bad |= (u[m].x ^ t2) | (u[m].y ^ t2);
            return bad;
        };
        auto valid = [&](const uint2 (&u)[4]) { return __all_sync(0xffffffffu, (check(u) & 3u) == 0); };

        auto horner = [&](const uint2 (&u)[4], int h) {
            float2 r = make_float2(__uint_as_float(u[3].x), __uint_as_float(u[3].y));
#pragma unroll
            for (int m = 2; m >= 0; m--) r = cfma(a512[h], r, make_float2(__uint_as_float(u[m].x), __uint_as_float(u[m].y)));
            return r;
        };
        float2 w0[2];
#pragma unroll
        for (int h = 0; h < 2; h++) {
            float (&acc)[64] = h ? accB : accA;
            float2 e = make_float2(acc[0], acc[2]);
#pragma unroll
            for (int s = 1; s < 32; s++) {
                const int i0 = 4 * (s >> 1) + (s & 1);
                e = cfma(a[h], e, make_float2(acc[i0], acc[i0 + 2]));
                if (!GREEDY && h == 1 && s == POLL_S) { cut(); poll(v[0], 0); }
            }
            float2 y = make_float2(__shfl_up_sync(0xffffffffu, e.x, 1, 4), __shfl_up_sync(0xffffffffu, e.y, 1, 4));
            if (c >= 1) e = cfma(a32[h], y, e);
            y = make_float2(__shfl_up_sync(0xffffffffu, e.x, 2, 4), __shfl_up_sync(0xffffffffu, e.y, 2, 4));
            if (c >= 2) e = cfma(a64[h], y, e);
            if (c == 3) st_relaxed2(cq + 4096 + 256 * h, (__float_as_uint(e.x) & ~3u) | t2, (__float_as_uint(e.y) & ~3u) | t2);
            if (h || !GREEDY) cut();
            w0[h] = make_float2(__shfl_up_sync(0xffffffffu, e.x, 1, 4), __shfl_up_sync(0xffffffffu, e.y, 1, 4));
            STAMPIF(at == 0 && (h || !GREEDY), 31 + h + 10 * wg);
        }
        if (GREEDY) { __nanosleep(100); poll(v[0], 0); __nanosleep(100); }
        uint32_t sx[2][16], sy[2][16], mr[2][4], tp;
        const uint32_t gap = wg ? TN(GAP1) : TN(GAP0);
#pragma unroll
        for (int h = 0; h < 2; h++) {
            const uint32_t sg = prm.swapped ? 0x80008000u : 0u;
            mr[h][0] = __byte_perm(mm[h], 0, 0x1010); mr[h][1] = __byte_perm(mm[h], 0, 0x3232);
            mr[h][2] = mr[h][1] ^ sg; mr[h][3] = mr[h][0] ^ sg ^ 0x80008000u;
        }
        auto put = [&](int e, int j) {
            uint32_t d[4];
#pragma unroll
            for (int u = 0; u < 4; u++) d[u] = fma_bf2(mr[e >> 1][2 * (e & 1)], sx[e >> 1][4 * j + u], mul_bf2(mr[e >> 1][2 * (e & 1) + 1], sy[e >> 1][4 * j + u]));
            #pragma unroll
            for (int u = 0; u < 2; u++)
                asm("lop3.b32 %0, %0, %1, %2, 0xD8;" : "+r"(d[2 * (j & 1) + u]) : "r"(par), "r"((uint32_t)((w & 1) == u)));
            stg128(hd + e * 65536 + (j >> 1) * 8192 + (j & 1) * 512, d[0], d[1], d[2], d[3]);
            if (j == 3 && lane == 0) mbar_arrive(bar_out + 32 * wg + 8 * e);
        };
#pragma unroll
        for (int h = 0; h < 2; h++) {
            float (&acc)[64] = h ? accB : accA;
            float2 hin;
            uint32_t it = 0;
            if (h == 0 && DOUBLE) {
                while (true) {
                    poll(v[1], 0);
                    if (valid(v[0])) { hin = horner(v[0], 0); break; }
                    poll(v[0], 0);
                    if (valid(v[1])) { hin = horner(v[1], 0); it++; break; }
                    if (++it > SPIN_LIMIT) __trap();
                }
            } else {
                while (!valid(v[0])) {
                    poll(v[0], h);
                    if (++it > SPIN_LIMIT) __trap();
                }
                hin = horner(v[0], h);
            }
            STAMPIF(at == 0 && it > 0 && h == 0, 39 + 10 * wg);
            if (c) hin = cmul(pw128[h], hin);
            hin.x += __shfl_xor_sync(0xffffffffu, hin.x, 1); hin.y += __shfl_xor_sync(0xffffffffu, hin.y, 1);
            hin.x += __shfl_xor_sync(0xffffffffu, hin.x, 2); hin.y += __shfl_xor_sync(0xffffffffu, hin.y, 2);
            float2 st = hin;
            if (c) st = cfma(pw32[h], hin, w0[h]);
            STAMPIF(at == 0, 33 + 3 * h + 10 * wg);
#pragma unroll
            for (int j = 0; j < 4; j++) {
#pragma unroll
                for (int u = 0; u < 4; u++) {
                    const int i0 = 16 * j + 4 * u;
                    const float2 y = cfma(a[h], st, make_float2(acc[i0], acc[i0 + 2]));
                    st = cfma(a[h], y, make_float2(acc[i0 + 1], acc[i0 + 3]));
                    sx[h][4 * j + u] = pack_bf(y.x, st.x); sy[h][4 * j + u] = pack_bf(y.y, st.y);
                }
                if (h && !NOGAP) sleep_until(tp += gap);
                if (h == 0 && j == RAISE_J) poll(v[0], 1);
                put(2 * h, j);
                cut();
            }
            STAMPIF(at == 0, 34 + 3 * h + 10 * wg);
            tp = clk32();
#pragma unroll
            for (int j = 0; j < 4; j++) {
                if (!NOGAP) sleep_until(tp += gap); else if (NOGAP == 2) __nanosleep(50); else cut();
                put(2 * h + 1, j);
            }
        }
        STAMPIF(at == 0, 38 + 10 * wg);

        if (wg == 1) {
            const char* src = reinterpret_cast<const char*>(prm.s->h) + (size_t)chunk * 524288;
            uint32_t rpar = 1;
#pragma unroll 1
            for (int n = w; n < 2 * NSPL; n += 4) {
                mbar_wait(empty + 8 * (NBIG - 7 + n));
                mbar_wait(hfull + 8 * (NST + n % 7), n / 7 & 1);
                const uint32_t dst = sb + tail_h(n);
                rpar = check_tile<8>(sb, dst, probe, src + tail_src(n), par, full + 8 * w, rpar, TN(T_RETRY));
                if (lane == 0) mbar_expect_tx(full + 8 * (NBIG + n), n < NSPL ? 2 * TILE : 0);
            }
        } else {
            asm volatile("setmaxnreg.inc.sync.aligned.u32 216;");
            const int tl = 64 * (w & 1) + 8 * (w >> 1) + g;
            float gf[4];
            float* op = prm.out + (size_t)(chunk * 128 + tl) * D_ + dt * 128 + 4 * c;
            const int xr = 2 * (g & 3) + (g >> 2);
            uint32_t xs = sb + (32 * (w & 1) + 8 * (w >> 1) + xr) * 128 + (((c >> 1) ^ xr) << 4) + (c & 1) * 8;
            uint32_t gs = sb + OFF_G + 2 * tl;
            asm volatile("" : "+r"(gs), "+l"(op), "+r"(xs));
            float outA[64], outB[64];
            STAMPIF(at == 0, 9);
            mbar_wait(bar_order + 8);
            STAMPIF(at == 0, 35);
            if (TN(GT2)) sched_fence(lds32(sb + OFF_EPOCH + 8) + TN(GT2));
            run_entries<1>(sb, 32, NBIG, 32 % NST, outA, outB, [](int) {});
            uint32_t gp[4], om[4];
            uint2 xt[4][8], dk[8];
            auto load_x = [&](int q, int j) {
#pragma unroll
                for (int r = 0; r < 2; r++) xt[2 * q + r][j] = lds64((xs ^ ((j & 3) << 5)) + (q ? tail_c(0) : OFF_FT) + (j >> 2) * TILE + r * 2048);
                if (q == 0) dk[j] = lds64(sb + OFF_DK + c * 8 + 32 * j);
            };
            auto term = [&](int q, int j) {
#pragma unroll
                for (int r = 2 * q; r < 2 * q + 2; r++) {
                    xt[r][j].x = mul_bf2(xt[r][j].x, fma_bf2(gp[r], dk[j].x, om[r]));
                    xt[r][j].y = mul_bf2(xt[r][j].y, fma_bf2(gp[r], dk[j].y, om[r]));
                }
            };
            auto store = [&](int q, int u0, int u1) {
                const float (&acc)[64] = q ? outB : outA;
#pragma unroll
                for (int u = u0; u < u1; u++) {
                    const int j = u >> 1, r = u & 1;
                    const int o = 8 * j + 2 * r;
                    const float gv = fabsf(gf[2 * q + r]);
                    const uint2 t = xt[2 * q + r][j];
                    stg128(op + (r * 32 + q * 16) * D_ + 16 * j, __float_as_uint(fmaf(gv, acc[o], bf_lo(t.x))), __float_as_uint(fmaf(gv, acc[o + 1], bf_hi(t.x))),
                           __float_as_uint(fmaf(gv, acc[o + 4], bf_lo(t.y))), __float_as_uint(fmaf(gv, acc[o + 5], bf_hi(t.y))));
                }
            };
            uint64_t dh = desc64<1>(make_desc_h(sb)), dc = desc64<0>(make_desc(sb));
#pragma unroll
            for (int n = 0; n < 2 * NSPL; n++) {
                const int j = n % NSPL;
                if (n == 0) mbar_wait(bar_g);
                if (n == X0 || n == 2 * NSPL - 1) mbar_wait(bar_x + (n == X0 ? 0 : 8));
                mbar_wait(full + 8 * (NBIG + n));
                KSTAMP(NBIG + n);
                asm volatile("mov.b64 %0, %0; mov.b64 %1, %1;" : "+l"(dh), "+l"(dc));
                const uint64_t da = dh + (tail_h(n) >> 4), db = dc + (tail_c(j) >> 4);
                const int xj = n - X0;
                wgmma_fence();
#pragma unroll
                for (int kk = 0; kk < 4; kk++) {
                    wgmma_n128<1>(n < NSPL ? outA : outB, da + kk * 128, db + kk * 2);
                    if (kk == 0 && n == 0) {
#pragma unroll
                        for (int r = 0; r < 4; r++) {
                            uint32_t u;
                            asm volatile("ld.shared.u16 %0, [%1];" : "=r"(u) : "r"(gs + (r & 1) * 64 + (r >> 1) * 32) : "memory");
                            gf[r] = bf_lo(u);
                        }
                    }
                    if (kk == 0 && xj >= 0 && xj < 8) load_x(0, xj);
                    if (kk == 0 && n == 2 * NSPL - 1) load_x(1, 0);
                }
                wgmma_commit();
                if (n <= 2 * NSPL - 7) {
                    wgmma_wait<1>();
                    if (lane == 0) mbar_arrive(empty + 8 * (NBIG + n - 1));
                    if (!j) { LSTAMP(at == 0, 96 + 12 + n / NSPL); GSTAMP(LT && at == 0, 195 + n / NSPL); }
                } else cut();
                if (n == 0) {
#pragma unroll
                    for (int r = 0; r < 4; r++) {
                        const bool routed = (int)__float_as_uint(gf[r]) < 0;
                        gp[r] = routed ? 0u : pack_bf(gf[r], gf[r]); om[r] = routed ? 0u : pack_bf(1.0f - gf[r], 1.0f - gf[r]);
                    }
                }
                if (xj >= 0 && xj < 8) term(0, xj);
                if (n == NSPL) pin64(outA);
                if (n >= NSPL) store(0, (j * 16 + SRND) / NSPL, j == NSPL - 1 ? 16 : ((j + 1) * 16 + SRND) / NSPL);
            }
            term(1, 0);
            cut();
            wgmma_wait<0>();
            pin64(outB);
            LSTAMP(at == 0, 96 + 51); GSTAMP(LT && at == 0, 197);
#pragma unroll
            for (int j = 1; j < 8; j++) load_x(1, j);
            store(1, 0, 2);
#pragma unroll
            for (int j = 1; j < 8; j++) {
                cut();
                term(1, j);
                store(1, 2 * j, 2 * j + 2);
            }
            __syncwarp();
            if (lane == 0) mbar_arrive(bar_stored);
            LSTAMP(at == 0, 96 + 52);
        }
    } else if (warp < 12) {
        asm volatile("setmaxnreg.dec.sync.aligned.u32 64;");
        init_barriers(empty + min(80 + 160 * w, 8 * 67), 4, []() { return 20; });
#pragma unroll
        for (int i = 0; i < 2; i++) sts128(sb + OFF_LIST + i * 2048 + at * 16, 0u, 0u, 0u, 0u);
        uint32_t* keys = reinterpret_cast<uint32_t*>(smem + OFF_KEYS);
        keys[4] = 0;
        named_bar(0, 480);
        mbar_wait(bar_epoch);
        const uint32_t t2 = lds32(sb + OFF_EPOCH + 4);
        STAMPIF(at == 0, 20);
        float facc[4];
        const uint32_t dft = make_desc(sb + OFF_FT), dxs = make_desc(sb + OFF_XS);
#pragma unroll 1
        for (int u = 0; u < 4; u++) {
            mbar_wait(ffull + 8 * u);
            STAMPIF(at == 0, 4 + u);
            wgmma_fence();
            small_tile<0>(facc, dft + u * (TILE >> 4), dxs + u * 64, u == 0);
            wgmma_commit();
        }
        wgmma_wait<0>();
        pin4(facc);
        if (lane < 4) mbar_arrive(fempty + 8 * lane);
        auto gate_up = [&](auto rest) {
            uint32_t slot = 4, par = 0, prev = full + 8 * 101;
#pragma unroll 1
            for (int j = 0; j < 16; j++) {
                if (j == 2) rest();
                STAMPW(at == 0, 75 + j);
                mbar_wait(ffull + 8 * slot, par);
                STAMPW(at == 0, 160 + j);
                mbar_wait(empty + 8 * prm.use[j]);
                wgmma_fence();
                small_tile<1>(facc, dft + slot * (TILE >> 4), dxs + j * 64, j == 0);
                wgmma_commit();
                if (j < TN(NP)) { wgmma_wait<0>(); prev = fempty + 8 * slot; }
                else wgmma_wait<1>();
                if (lane == 0) mbar_arrive(prev);
                prev = j < TN(NP) ? full + 8 * 101 : fempty + 8 * slot;
                if (++slot == NFT) { slot = 0; par ^= 1; }
            }
            wgmma_wait<0>();
            if (lane == 0) mbar_arrive(prev);
            pin4(facc);
        };
        auto down = [&]() {
            const uint32_t dhid = make_desc(sb + OFF_HID);
#pragma unroll 1
            for (int j = 0; j < 7; j++) {
                mbar_wait(dfull + 8 * j);
                mbar_wait(empty + 8 * prm.use[16 + j]);
                wgmma_fence();
                small_tile<1>(facc, dft + j * (TILE >> 4), dhid + j * 64, j == 0);
                wgmma_commit();
                if ((0x52 >> j) & 1) {
                    wgmma_wait<0>();
                    if (lane == 0) mbar_arrive(bar_dfree + 8 * (j / 3));
                }
            }
            wgmma_wait<0>();
            pin4(facc);
        };
        if ((c & 1) == (w >> 1)) {
            float* red = reinterpret_cast<float*>(smem + OFF_RED) + w * 32 + (c >> 1) * 16 + g;
            red[0] = (w & 1) ? facc[1] : facc[0];
            red[8] = (w & 1) ? facc[3] : facc[2];
        }
        named_bar(2, 128);
        STAMPIF(at == 0, 21);
        const uint32_t tpub = clk32();
        if (w < 2) {
            const float* red = reinterpret_cast<const float*>(smem + OFF_RED) + w * 16 + (lane & 15);
            const float v = rbf((red[0] + red[32]) + (red[64] + red[96]));
            if (w == 0) {
                uint32_t k = __float_as_uint(v);
                k = ((k ^ ((uint32_t)((int)k >> 31) | 0x80000000u)) & 0xFFFF0000u) | (t2 << 11) | (2047u - (uint32_t)(rid * 16 + (lane & 15)));
                int rank = 0;
#pragma unroll
                for (int i = 0; i < 8; i++) rank += __shfl_sync(0xffffffffu, k, (lane >> 4) * 8 + i) > k;
                rank += __shfl_xor_sync(0xffffffffu, rank, 16);
                if (rank < 8) st_relaxed(&prm.s->key[cta * 8 + rank], k);
            } else if (lane < 16) st_relaxed(&prm.s->gate[rid * 16 + lane], __float_as_uint(rbf(sigmoidf_(v))) | t2);
            __syncwarp();
        }
        uint32_t it = 0;
        uint4 ka, kb4;
        sleep_until(tpub + TN(G0));
        while (true) {
            ka = ld_relaxed4(&prm.s->key[at * 8]);
            kb4 = ld_relaxed4(&prm.s->key[at * 8 + 4]);
            if (__all_sync(0xffffffffu, (((ka.x ^ (t2 << 11)) | (kb4.x ^ (t2 << 11))) & 0x1800u) == 0)) break;
            if (++it > SPIN_LIMIT) __trap();
        }
        STAMPIF(at == 0, 22);
        STAMPIF(at == 0 && it > 0, 23);
        const uint32_t m1 = __reduce_max_sync(0xffffffffu, ka.x), m2 = __reduce_max_sync(0xffffffffu, ka.x == m1 ? ka.y : ka.x);
        if (lane == 0) keys[w] = m2;
        named_bar(2, 128);
        const uint4 th4 = *reinterpret_cast<const uint4*>(keys);
        const uint32_t th = min(min(th4.x, th4.y), min(th4.z, th4.w));
        {
            const uint32_t k8[8] = {ka.x, ka.y, ka.z, ka.w, kb4.x, kb4.y, kb4.z, kb4.w};
            auto append = [&](int lo, int hi) {
                uint32_t n = 0, pos = 0;
#pragma unroll
                for (int i = lo; i < hi; i++) n += k8[i] >= th;
                asm volatile("{ .reg .pred p; setp.ne.u32 p, %2, 0; @p atom.shared.add.u32 %0, [%1], %2; }" : "+r"(pos) : "r"(sb + OFF_KEYS + 16), "r"(n) : "memory");
#pragma unroll
                for (int i = lo; i < hi; i++)
                    if (k8[i] >= th) reinterpret_cast<uint32_t*>(smem + OFF_LIST)[pos + i - lo] = k8[i];
            };
            append(0, 2);
            if (__any_sync(0xffffffffu, k8[2] >= th)) append(2, 8);
        }
        named_bar(2, 128);
        {
            const uint32_t* list = reinterpret_cast<const uint32_t*>(smem + OFF_LIST);
            const int n = (int)keys[4];
#pragma unroll 1
            for (int i0 = w * 32; i0 < n; i0 += 128) {
                const uint32_t k = list[i0 + lane];
                int rank = 0;
#pragma unroll 2
                for (int o = 0; o < n; o += 4) {
                    const uint4 l4 = *reinterpret_cast<const uint4*>(list + o);
                    rank += (l4.x > k) + (l4.y > k) + (l4.z > k) + (l4.w > k);
                }
                if (rank < 8) reinterpret_cast<uint32_t*>(smem + OFF_SEL)[rank] = k;
            }
        }
        named_bar(2, 128);
        STAMPIF(at == 0, 24);
        const uint32_t* sel = reinterpret_cast<const uint32_t*>(smem + OFF_SEL);
        auto gates = [&]() {
            uint32_t gv;
            it = 0;
            while (true) {
                gv = ld_relaxed(&prm.s->gate[chunk * 128 + at]);
                const uint32_t ar = ld_relaxed(&prm.s->armed[((cta >> 4) * 14 + min(lane, 13)) * 4]);
                if (__all_sync(0xffffffffu, (gv & 3u) == t2 && ar == t2)) break;
                if (++it > SPIN_LIMIT) __trap();
            }
            asm volatile("fence.acquire.gpu;" ::: "memory");
#pragma unroll
            for (int s = 0; s < 8; s++)
                if ((~sel[s] & 2047u) == (uint32_t)(chunk * 128 + at)) gv |= 0x80000000u;
            reinterpret_cast<uint16_t*>(smem + OFF_G)[at] = (uint16_t)(gv >> 16);
            __syncwarp();
            if (lane == 0) mbar_arrive(bar_g);
        };
        if (has_gu) {
            const int tk = (at >> 3) & 7;
            const char* xt = (const char*)prm.x + (~sel[tk] & 2047u) * 2048 + (at >> 6) * 128 + (at & 7) * 16;
#pragma unroll
            for (int i = 0; i < 8; i++) {
                cp_async16(sb + OFF_XS + (2 * i + (at >> 6)) * 1024 + tk * 128 + (((at & 7) ^ tk) << 4), xt + i * 256);
                if (i == 0 || i == 7) asm volatile("cp.async.commit_group;" ::: "memory");
            }
            asm volatile("cp.async.wait_group 1;" ::: "memory");
            fence_async_smem();
            named_bar(2, 128);
            STAMPIF(at == 0, 25);
            gate_up([&]() {
                asm volatile("cp.async.wait_all;" ::: "memory");
                fence_async_smem();
                named_bar(2, 128);
            });
            if (!(cta & 1)) {
#pragma unroll
                for (int u = 0; u < 4; u++) {
                    const float v = rbf(facc[u]);
                    facc[u] = __fdividef(v, 1.0f + __expf(-v));
                }
            }
            st_relaxed2(&prm.s->hid[fid * 128 + at], pack_bf(facc[0], facc[1]), pack_bf(facc[2], facc[3]));
        }
        STAMPIF(at == 0, 26);
        gates();
        {
            mbar_wait(empty + 8 * max(TN(HG), 31));
            const uint2* hp = &prm.s->hid[(cta >> 4) * 14 * 128 + at];
            uint32_t hv[16];
            it = 0;
            while (true) {
                uint32_t top = 0;
#pragma unroll
                for (int j = 0; j < 7; j++) {
                    const uint2 hg = ld_relaxed2(hp + 256 * j), hu = ld_relaxed2(hp + 256 * j + 128);
                    top = max(top, max(hg.x, hu.x));
                    hv[2 * j] = mul_bf2(hg.x, hu.x); hv[2 * j + 1] = mul_bf2(hg.y, hu.y);
                }
                if (__all_sync(0xffffffffu, top != ~0u)) break;
                do {
                    if (++it > SPIN_LIMIT) __trap();
                } while (!__all_sync(0xffffffffu, ld_relaxed(hp + min(lane, 13) * 128 - lane) != ~0u));
            }
            STAMPIF(at == 0 && it > 0, 61);
            hv[14] = hv[15] = 0;
#pragma unroll
            for (int j = 0; j < 4; j++)
                asm volatile("stmatrix.sync.aligned.m8n8.x4.trans.shared.b16 [%0], {%1, %2, %3, %4};" ::"r"(
                                 sb + OFF_HID + (2 * j + (lane >> 4)) * 1024 + (lane & 7) * 128 + (((2 * w + ((lane >> 3) & 1)) ^ (lane & 7)) << 4)),
                             "r"(hv[4 * j]), "r"(hv[4 * j + 1]), "r"(hv[4 * j + 2]), "r"(hv[4 * j + 3]) : "memory");
        }
        fence_async_smem();
        named_bar(2, 128);
        STAMPIF(at == 0, 27);
        uint32_t mine = __ballot_sync(0xffffffffu, lane < 8 && (int)((~sel[lane & 7] & 2047u) >> 7) == chunk), tr;
        uint2 xr, xd;
        float gr, rs;
        auto skip = [&](int n) {
#pragma unroll 1
            for (int i = 0; i < n; i++) mine &= mine - 1;
            if (mine) {
                const uint32_t key = sel[__ffs(mine) - 1], kb = key >> 16;
                tr = ~key & 2047u;
                xr = __ldg(reinterpret_cast<const uint2*>(prm.x + (size_t)tr * D_ + dt * 128) + lane);
                rs = rbf(sigmoidf_(bf_lo((kb & 0x8000u) ? (kb & 0x7FFFu) : (~kb & 0xFFFFu))));
                gr = fabsf(__bfloat162float(reinterpret_cast<const __nv_bfloat16*>(smem + OFF_G)[tr & 127]));
                xd = lds64(sb + OFF_DK + 8 * lane);
            }
        };
        skip(w);
        down();
#pragma unroll
        for (int u = 0; u < 4; u++)
            st_relaxed(&prm.s->y[((2 * c + (u & 1)) * 8 + (cta >> 4)) * D_ + (cta & 15) * 64 + w * 16 + g + 8 * (u >> 1)], (__float_as_uint(facc[u]) & ~3u) | t2);
        STAMPIF(at == 0, 28);
        sleep_until(clk32() + TN(T_Y));
        while (mine) {
            const uint32_t* yp = &prm.s->y[(__ffs(mine) - 1) * 8 * D_ + dt * 128 + 4 * lane];
            float y[4];
            it = 0;
            while (true) {
                uint32_t bad = 0;
                y[0] = y[1] = y[2] = y[3] = 0.f;
#pragma unroll
                for (int ks = 0; ks < 8; ks++) {
                    const uint4 v = ld_relaxed4(yp + ks * D_);
                    bad |= v.x ^ t2;
                    y[0] += __uint_as_float(v.x); y[1] += __uint_as_float(v.y); y[2] += __uint_as_float(v.z); y[3] += __uint_as_float(v.w);
                }
                if (__all_sync(0xffffffffu, (bad & 3u) == 0)) break;
                if (++it > SPIN_LIMIT) __trap();
            }
            STAMPIF(lane == 0 && it, 62);
#pragma unroll
            for (int u = 0; u < 4; u++) {
                const uint32_t x2 = (u & 2) ? xr.y : xr.x, d2 = mul_bf2(x2, (u & 2) ? xd.y : xd.x);
                y[u] = fmaf(gr, (u & 1) ? bf_hi(d2) : bf_lo(d2), rbf(rbf(1.0f - gr) * rbf(((u & 1) ? bf_hi(x2) : bf_lo(x2)) + rbf(rbf(y[u]) * rs))));
            }
            STAMPIF(lane == 0, 50);
            mbar_wait(bar_stored);
            asm volatile("red.global.add.v4.f32 [%0], {%1, %2, %3, %4};" ::"l"(prm.out + (size_t)tr * D_ + dt * 128 + 4 * lane), "f"(y[0]), "f"(y[1]), "f"(y[2]), "f"(y[3]) : "memory");
            skip(4);
        }
        LSTAMP(lane == 0, 96 + 29);
    } else {
        asm volatile("setmaxnreg.dec.sync.aligned.u32 40;");
        if (warp != 12) sleep_until(cstart + (warp == 13 ? TN(T_SMALL) : TN(T_W3)));
        auto behind = [&](int e) {
            if (!mbar_test(empty + 8 * e, 0)) {
                mbar_wait(empty + 8 * e);
                if (TN(T_X0)) sleep_until(clk32() + TN(T_X0));
            }
        };
        if (warp == 15) {
            prefetch_map(&mXr);
            named_bar(0, 480);
#pragma unroll 1
            for (int i = 0; i < 4; i++) {
                const int u = i;
                if (lane == 0) mbar_expect_tx(ffull + 8 * u, TILE);
                sleep_until(cstart + (i == 0 ? TN(RT0) : i == 1 ? TN(RT1) : i == 2 ? TN(RT2) : TN(RT3)));
                if (elect_one()) tma3(sb + OFF_FT + u * TILE, &mXr, u * 256, rid * 16, ffull + 8 * u);
                STAMP(53 + u);
            }
            const CUtensorMap* mw = (cta & 1) ? &mWu : &mWg;
            if (sb & 1023) __trap();
            prefetch_map(mw);
            prefetch_map(&mWd);
            uint32_t slot = 4, par = 1;
#pragma unroll 1
            for (int j = 0; j < (has_gu && DBG != 1 ? 16 : 0); j++) {
                mbar_wait(fempty + 8 * slot, par);
                if (lane == 0) mbar_expect_tx(ffull + 8 * slot, TILE);
                behind(prm.fetch[j]);
                STAMPW(1, 176 + j);
                if (elect_one()) tma2(sb + OFF_FT + slot * TILE, mw, (fid >> 1) * 64, TN(WDBG) ? 0 : j * 64, ffull + 8 * slot);
                if (++slot == NFT) { slot = 0; par ^= 1; }
            }
            if (lane < 9) mbar_expect_tx(lane < 7 ? dfull + 8 * lane : bar_x + 8 * (lane - 7), lane < 7 ? TILE : 2 * TILE);
            if (!has_gu) mbar_wait(bar_g);
#pragma unroll 1
            for (int j = 0; j < (DBG != 1 ? 7 : 0); j++) {
                if (has_gu) mbar_wait(fempty + 8 * min(j, 4), 1);
                behind(prm.fetch[16 + j]);
                if (elect_one()) tma2(sb + OFF_FT + j * TILE, &mWd, (cta & 15) * 64, (cta >> 4) * 448 + (TN(WDBG) ? 0 : j * 64), dfull + 8 * j);
            }
            prefetch_map(&mXe);
#pragma unroll 1
            for (int u = 0; u < 4; u++) {
                if (u == 2) {
                    mbar_wait(bar_dfree + 16);
                    if (elect_one()) tma5(sb + tail_c(8), &mCim, c_col(63), dt * 8, full + 8 * (NBIG + 8));
                }
                mbar_wait(bar_dfree);
                behind(u < 2 ? TN(DN_E0) + u : NBIG + NSPL);
                if (elect_one())
                    asm volatile("cp.async.bulk.tensor.5d.shared::cluster.global.mbarrier::complete_tx::bytes [%0], [%1, {%3, %6, %6, %4, %5}], [%2];"
                                 ::"r"(sb + (u < 2 ? OFF_FT : tail_c(0)) + (u & 1) * TILE), "l"(&mXe), "r"(bar_x + 4 * (u & 2)), "r"(dt * 128 + (u & 1) * 64),
                                 "r"(u & 2), "r"(chunk * 4), "r"(0) : "memory");
                if (u < 2 && XPF) {
                    if (elect_one())
                        asm volatile("cp.async.bulk.prefetch.tensor.5d.L2.global [%0, {%1, %4, %4, %2, %3}];" ::"l"(&mXe), "r"(dt * 128 + u * 64), "r"(2), "r"(chunk * 4), "r"(0) : "memory");
                }
            }
        } else if (warp == 13) {
#pragma unroll
            for (int u = 0; u < 8; u++) {
                const int row = (u >> 2) * 4 + (lane >> 3);
                cp_async16(sb + OFF_XS + (u & 3) * 1024 + row * 128 + (((lane & 7) ^ row) << 4), (const char*)(u < 4 ? prm.w_r : prm.gate_w) + (u & 3) * 512 + lane * 16);
            }
            STAMP(57);
            const uint32_t tag = ld_relaxed(&prm.s->epoch[cta]) + 1;
            named_bar(1, 64);
            *reinterpret_cast<uint2*>(smem + OFF_EPOCH) = make_uint2(tag, tag % 3u + 1u);
            STAMPIF(tag, 58);
            asm volatile("cp.async.wait_all;" ::: "memory");
            STAMP(59);
            fence_async_smem();
            __syncwarp();
            if (lane == 0) {
                mbar_arrive(bar_epoch);
                prm.s->epoch[cta] = tag;
            }
            sleep_until(cstart + TN(T_BASE));
            {
                const uint2 st = ld_relaxed2(&prm.s->start[2 * lane]);
                const uint32_t d = st.x - cstart + 512u, age = gtime32() - st.y;
                const uint32_t m = __reduce_max_sync(0xffffffffu, d < 1024u && age < 4096u ? (d << 12) | age : 0u);
                const uint32_t late = (m & 4095u) - __reduce_min_sync(0xffffffffu, age);
                *reinterpret_cast<volatile uint32_t*>(smem + OFF_EPOCH + 8) = cstart + (m ? (m >> 12) - 512u + min(late, 256u) * TN(G_NS) / 4 : 0u);
                __syncwarp();
                if (lane == 0) mbar_arrive(bar_base);
                STAMP(60);
            }
            mbar_wait(bar_const);
            asm volatile("fence.acq_rel.gpu;" ::: "memory");
            if (lane < 4) st_relaxed2(&prm.s->armed[fid * 4 + lane], tag % 3u + 1u, 0u);
            prefetch_map(&mCre);
            prefetch_map(&mCim);
            const char* src = reinterpret_cast<const char*>(prm.s->h) + (size_t)chunk * 524288;
            uint32_t slot = 32 % NST, hpar = 0, rpar = 0;
#pragma unroll 1
            for (int i = 32; i < NBIG; i++) {
                mbar_wait(hfull + 8 * slot, hpar);
                STAMPIF(i == 32 || i == 33, 14 + (i & 1));
                rpar = check_tile<16>(sb, sb + slot * SLOT, probe, src, tag, bar_retry, rpar, TN(T_RETRY));
                if (lane == 0) mbar_expect_tx(full + 8 * i, 2 * TILE);
                STAMPIF(i == 32 || i == 33, 16 + (i & 1));
                src += 2 * TILE;
                slot = slot == NST - 1 ? 0 : slot + 1;
                hpar ^= slot == 32 % NST;
            }
        } else if (warp == 14) {
            prefetch_map(&mPB);
            auto pf_c = [&](int k) { if (!(NOPF & 4)) prefetch_slice(&mPC, 4 * (k >> 1), cta * 8 + (k & 1) * 4); };
            named_bar(0, 480);
            asm volatile("bar.arrive 1, 64;" ::: "memory");
            if (lane < 24) st_relaxed(lane < 8 ? &prm.s->key[cta * 8 + lane] : &prm.s->gate[rid * 16 + lane - 8], 0u);
#pragma unroll 1
            for (int k = TN(PF0) ? 0 : 1; k < 4; k++) {
                sleep_until(cstart + (k == 0 ? TN(PF0) : k == 1 ? TN(PF1) : k == 2 ? TN(PF2) : TN(PF3)));
                if (!(NOPF & 1)) { if (elect_one()) prefetch_slice(&mPB, 4 * k, cta * 4); }
            }
#pragma unroll 1
            for (int k = 0; k < 4; k++) {
                behind(TN(PB_E0) + TN(PB_STEP) * k);
                if (!(NOPF & 2)) { if (elect_one()) prefetch_slice(&mPB, 4 * k, 512 + cta * 4); }
            }
#pragma unroll 1
            for (int k = 0; k < TN(PC_N); k++) {
                behind(min(TN(PC_E0) + TN(PC_STEP) * k / 2, 25));
                if (elect_one()) pf_c(k);
            }
            int pk = TN(PC_N), pe = TN(PC_E1);
            auto own_part = [&](int e) {
                if (!mbar_test(bar_out + 8 * e, 0)) {
                    mbar_wait(bar_out + 8 * e);
                    sleep_until(clk32() + TN(T_OWN));
                    STAMP(11);
                }
            };
            const char* src = reinterpret_cast<const char*>(prm.s->h) + (size_t)chunk * 524288;
            uint32_t slot = 32 % NST;
#pragma unroll 1
            for (int i = 32; i < NBIG; i++) {
                if (!(i & 3)) own_part((i - 32) >> 2);
                mbar_wait(empty + 8 * (i - NST));
                PSTAMP(i);
                if (elect_one()) {
                    mbar_expect_tx(hfull + 8 * slot, 2 * TILE);
                    bulk_load(sb + slot * SLOT, src, 2 * TILE, hfull + 8 * slot);
                    tma5(sb + slot * SLOT + 2 * TILE, (i & 4) ? &mCim : &mCre, c_col(i), dt * 8, full + 8 * i);
                }
                if (i == pe && pk < 8) {
                    if (elect_one()) pf_c(pk);
                    pk++; pe += TN(PC_S1);
                }
                src += 2 * TILE;
                slot = slot == NST - 1 ? 0 : slot + 1;
            }
            src -= (NBIG - 32) * 2 * TILE;
#pragma unroll
            for (int k = 0; k < 2 * NSPL - 2; k++) {
                if (k == 0 || k == 2) own_part(6 + k / 2);
                mbar_wait(empty + 8 * (NBIG - NST + k));
                if (k >= 1 && k <= 4) {
                    if (elect_one()) {
#pragma unroll
                        for (int j = 2 * k - 2; j < 2 * k; j++)
                            tma5(sb + tail_c(j), ((NBIG + j) & 4) ? &mCim : &mCre, c_col(NBIG + j), dt * 8, full + 8 * (NBIG + j));
                    }
                }
                if (k == 4) continue;
                if (k == 2) mbar_wait(bar_dfree + 8);
                if (elect_one()) {
#pragma unroll
                    for (int n = k < 5 ? 2 * k : k + 2; n < (k < 3 ? 2 * k + 2 : k == 3 ? 7 : k + 3); n++) {
                        mbar_expect_tx(hfull + 8 * (NST + n % 7), TILE);
                        bulk_load(sb + tail_h(n), src + tail_src(n), TILE, hfull + 8 * (NST + n % 7));
                    }
                }
            }
        } else {
            if (elect_one()) {
#pragma unroll
                for (int i = 0; i < NST; i++) mbar_init(full + 8 * i, 1);
                fence_mbar_init();
            }
            __syncwarp();
            asm volatile("bar.arrive 5, 160;" ::: "memory");
#pragma unroll 1
            for (int i = 0; i < NST; i++) {
                if (elect_one()) {
                    mbar_expect_tx(full + 8 * i, SLOT);
                    tma5b(sb + i * SLOT, &mB, i * 64, dt * 4, full + 8 * i);
                    tma4(sb + i * SLOT + 2 * TILE, &mX, i * 64, chunk * 64, full + 8 * i);
                }
                STAMPIF(i == 0, 1);
            }
            STAMP(2);
            asm volatile("bar.arrive 0, 480;" ::: "memory");
            named_bar(6, 160);
            uint32_t dst = sb;
#pragma unroll 1
            for (int i = NST; i < 32; i++) {
                if (i == 2 * NST) mbar_wait(bar_base);
                if (lane == 0) mbar_expect_tx(full + 8 * i, SLOT);
                mbar_wait(empty + 8 * (i - NST));
                PSTAMP(i);
                if (elect_one()) {
                    tma5b(dst, &mB, (i & 15) * 64, (i >> 4) * 64 + dt * 4, full + 8 * i);
                    tma4(dst + 2 * TILE, &mX, (i & 15) * 64, chunk * 64, full + 8 * i);
                }
                dst = dst == sb + (NST - 1) * SLOT ? sb : dst + SLOT;
            }
        }
    }
}

typedef CUresult (*EncodeFn)(CUtensorMap*, CUtensorMapDataType, cuuint32_t, void*, const cuuint64_t*, const cuuint64_t*, const cuuint32_t*,
                             const cuuint32_t*, CUtensorMapInterleave, CUtensorMapSwizzle, CUtensorMapL2promotion, CUtensorMapFloatOOBfill);

bool encode(EncodeFn fn, CUtensorMap* m, const void* ptr, int rank, const cuuint64_t* dims, const cuuint64_t* strides, const cuuint32_t* box,
            CUtensorMapL2promotion promo = CU_TENSOR_MAP_L2_PROMOTION_NONE) {
    const cuuint32_t es[5] = {1, 1, 1, 1, 1};
    return fn(m, CU_TENSOR_MAP_DATA_TYPE_BFLOAT16, rank, const_cast<void*>(ptr), dims, strides, box, es, CU_TENSOR_MAP_INTERLEAVE_NONE,
              CU_TENSOR_MAP_SWIZZLE_128B, promo, CU_TENSOR_MAP_FLOAT_OOB_FILL_NONE) == CUDA_SUCCESS;
}

}

extern "C" void kernel_launch(void* const* d_in, const int* in_sizes, int n_in, void* d_out, int out_size) {
    (void)in_sizes; (void)n_in; (void)out_size;
    Params prm;
    prm.x = (const __nv_bfloat16*)d_in[0];
    prm.lam_re = (const __nv_bfloat16*)d_in[1];
    prm.lam_im = (const __nv_bfloat16*)d_in[2];
    prm.b_re = (const __nv_bfloat16*)d_in[3];
    prm.b_im = (const __nv_bfloat16*)d_in[4];
    prm.c_re = (const __nv_bfloat16*)d_in[5];
    prm.c_im = (const __nv_bfloat16*)d_in[6];
    prm.log_dt = (const __nv_bfloat16*)d_in[7];
    prm.dskip = (const __nv_bfloat16*)d_in[8];
    prm.w_r = (const __nv_bfloat16*)d_in[10];
    prm.gate_w = (const __nv_bfloat16*)d_in[14];
    prm.out = (float*)d_out;
    cudaGetSymbolAddress((void**)&prm.s, g_scratch);
    prm.swapped = prm.b_im < prm.b_re;

    void* fnp = nullptr;
    cudaDriverEntryPointQueryResult qr;
    cudaGetDriverEntryPoint("cuTensorMapEncodeTiled", &fnp, cudaEnableDefault, &qr);
    EncodeFn fn = (EncodeFn)fnp;
    cudaFuncSetAttribute(fused_kernel, cudaFuncAttributeMaxDynamicSharedMemorySize, SMEM_BYTES);

    CUtensorMap mX, mB, mCre, mCim, mWg, mWu, mWd, mXr, mPB, mPC, mXe;
    const cuuint64_t row = 2048;
    {
        const cuuint64_t dims[4] = {1024, 2, 4, 976}, st[3] = {row, 32 * row, 2 * row};
        const cuuint32_t box[4] = {64, 2, 4, 16};
        encode(fn, &mX, prm.x, 4, dims, st, box, PROMO);
    }
    {
        const char *lo = (const char*)(prm.swapped ? prm.b_im : prm.b_re), *hi = (const char*)(prm.swapped ? prm.b_re : prm.b_im);
        const cuuint64_t dims[5] = {1024, 8, 2, 96, 2}, st[4] = {row, (cuuint64_t)(hi - lo), 8 * row, 256 * row};
        const cuuint32_t box[5] = {64, 8, 2, 4, 2};
        encode(fn, &mB, lo, 5, dims, st, box, PROMO);
    }
    {
        const cuuint64_t dims[5] = {1024, 2, 4, 2, 64}, st[4] = {row, 4 * row, 2 * row, 16 * row};
        const cuuint32_t box[5] = {64, 2, 4, 2, 8};
        encode(fn, &mCre, prm.c_re, 5, dims, st, box);
        encode(fn, &mCim, prm.c_im, 5, dims, st, box);
    }
    {
        const cuuint64_t dims[2] = {F_, D_}, st[1] = {F_ * 2}, dimsd[2] = {D_, F_}, std_[1] = {row};
        const cuuint32_t box[2] = {64, 64};
        encode(fn, &mWg, d_in[11], 2, dims, st, box);
        encode(fn, &mWu, d_in[12], 2, dims, st, box);
        encode(fn, &mWd, d_in[13], 2, dimsd, std_, box);
    }
    for (int i = 0; i < 2; i++) {
        const char *p = (const char*)(i ? prm.c_re : prm.b_re), *q = (const char*)(i ? prm.c_im : prm.b_im);
        const cuuint64_t dims[4] = {64, 16, 1024, 2}, st[3] = {128, row, (cuuint64_t)(p < q ? q - p : p - q)};
        const cuuint32_t box[4] = {16, 4, 4, 2};
        encode(fn, i ? &mPC : &mPB, p < q ? p : q, 4, dims, st, box, CU_TENSOR_MAP_L2_PROMOTION_L2_128B);
    }
    {
        const cuuint64_t dims[3] = {D_ - 192, S_, 4}, st[2] = {row, 128};
        const cuuint32_t box[3] = {64, 16, 4};
        encode(fn, &mXr, prm.x, 3, dims, st, box);
    }
    {
        const cuuint64_t dims[5] = {1024, 2, 4, 4, S_ / 32}, st[4] = {4 * row, row, 8 * row, 32 * row};
        const cuuint32_t box[5] = {64, 2, 4, 2, 4};
        encode(fn, &mXe, prm.x, 5, dims, st, box);
    }
    for (int j = 0, e4 = 4 * TN(GC0); j < 23; j++) {
        prm.fetch[j] = j < NFT ? TN(GU_E0) + j * TN(W_NUM) / 4 : j < 16 ? 0 : TN(DL0) + (j - 16) * TN(DLS) / 4;
        prm.use[j] = j < 16 ? e4 / 4 : TN(DC0) + (j - 16) * TN(DCS) / 4;
        const int last = NBIG - 2;
        if (prm.fetch[j] > last) prm.fetch[j] = last;
        if (prm.use[j] > last) prm.use[j] = last;
        e4 += j < TN(N1) ? TN(GCS) : j < TN(N2) ? TN(GCS2) : j < 10 ? TN(GCS3) : TN(GCS4);
    }
    fused_kernel<<<NCTA, 512, SMEM_BYTES, cudaStreamPerThread>>>(prm, mX, mB, mCre, mCim, mWg, mWu, mWd, mXr, mPB, mPC, mXe);
}
```

```cpp
#include <cuda_runtime.h>
#include <cuda_bf16.h>
#include <cuda.h>
#include <stdint.h>

namespace {

constexpr int S_ = 2048, D_ = 1024, F_ = 3584;
constexpr int NCTA = 128;
constexpr int NSPL = 9, NBIG = 64 - NSPL, NENT = NBIG + 2 * NSPL;
constexpr int NST = 5;
constexpr int NFT = 5;
constexpr uint32_t SLOT = 32768, TILE = 8192;
constexpr uint32_t OFF_FT = NST * SLOT;
constexpr uint32_t OFF_XS = OFF_FT + NFT * TILE;
constexpr uint32_t OFF_LIST = OFF_XS + 8192;
constexpr uint32_t OFF_RED = OFF_XS + 4096;
constexpr uint32_t OFF_CONST = OFF_XS + 16384;
constexpr uint32_t OFF_M = OFF_CONST + 8192;
constexpr uint32_t OFF_HID = OFF_CONST;
constexpr uint32_t OFF_G = OFF_M + 512;
constexpr uint32_t OFF_DK = OFF_G + 256;
constexpr uint32_t OFF_FULL = OFF_DK + 256;
constexpr uint32_t OFF_EMPTY = OFF_FULL + 103 * 8;
constexpr uint32_t OFF_KEYS = OFF_EMPTY + 87 * 8;
constexpr uint32_t OFF_SEL = OFF_KEYS + 32;
constexpr uint32_t OFF_EPOCH = OFF_SEL + 32;
constexpr uint32_t OFF_PROF = OFF_EPOCH + 16;
constexpr uint32_t SMEM_BYTES = OFF_PROF + 432;
static_assert(SMEM_BYTES <= 232448, "smem");

static_assert(NBIG % NST == 0, "tail layout");
__host__ __device__ constexpr uint32_t tail_c(int j) { return j < 8 ? SLOT + j * 2 * TILE : OFF_FT + 5 * TILE; }
__host__ __device__ constexpr uint32_t tail_h(int n) { return n % 7 < 4 ? n % 7 * TILE : OFF_FT + (n % 7 - 2) * TILE; }
__host__ __device__ constexpr uint32_t tail_src(int n) { return (n % NSPL + NBIG - 32) * 2 * TILE + n / NSPL * TILE; }
__host__ __device__ constexpr int c_col(int i) { return ((i & 3) + ((i >> 1) & 12)) * 64; }

constexpr uint32_t SPIN_LIMIT = 1u << 18;

struct Scratch {
    uint2 carry[16 * 1024];
    uint2 hid[NCTA * 128];
    uint32_t y[8 * 8 * D_];
    uint32_t key[NCTA * 8];
    uint32_t gate[S_];
    uint2 armed[NCTA * 4];
    unsigned int epoch[256];
    uint4 start[32 * 2];
    uint4 h[16 * 32 * 1024];
};
__device__ __align__(1024) Scratch g_scratch;
#define STAMPW_(cond, w) do {} while (0)
#define GSTAMP(cond, w) do {} while (0)
#define LSTAMP(cond, w) STAMPW_(cond, w)
#define LT 0
#define STAMPW(cond, w) STAMPW_(cond, w)
#define STAMPIF(cond, i) STAMPW(cond, 96 + (i))
#define STAMP(i) STAMPW(1, 96 + (i))
#define KSTAMP(i) STAMPW((threadIdx.x & 127) == 0, i)
#define PSTAMP(i) STAMPW((i) < 56 && (i) >= 32, 160 + (i))

struct Params {
    const __nv_bfloat16 *x, *b_re, *b_im, *lam_re, *lam_im, *c_re, *c_im, *log_dt, *dskip, *w_r, *gate_w;
    float* out;
    Scratch* s;
    int fetch[23], use[23];
    int swapped;
};

__device__ __forceinline__ uint32_t smem_u32(const void* p) { return (uint32_t)__cvta_generic_to_shared(p); }
__device__ __forceinline__ void mbar_init(uint32_t bar, uint32_t cnt) { asm volatile("mbarrier.init.shared::cta.b64 [%0], %1;" ::"r"(bar), "r"(cnt) : "memory"); }
__device__ __forceinline__ void mbar_expect_tx(uint32_t bar, uint32_t bytes) { asm volatile("mbarrier.arrive.expect_tx.shared::cta.b64 _, [%0], %1;" ::"r"(bar), "r"(bytes) : "memory"); }
__device__ __forceinline__ void mbar_arrive(uint32_t bar) { asm volatile("mbarrier.arrive.shared::cta.b64 _, [%0];" ::"r"(bar) : "memory"); }
__device__ __forceinline__ bool mbar_try(uint32_t bar, uint32_t parity) {
    uint32_t ok;
    asm volatile("{ .reg .pred p; mbarrier.try_wait.parity.shared::cta.b64 p, [%1], %2; selp.u32 %0, 1, 0, p; }" : "=r"(ok) : "r"(bar), "r"(parity) : "memory");
    return ok;
}
__device__ __forceinline__ bool mbar_test(uint32_t bar, uint32_t parity) {
    uint32_t ok;
    asm volatile("{ .reg .pred p; mbarrier.test_wait.parity.shared::cta.b64 p, [%1], %2; selp.u32 %0, 1, 0, p; }" : "=r"(ok) : "r"(bar), "r"(parity) : "memory");
    return __all_sync(0xffffffffu, ok);
}
__device__ __forceinline__ void mbar_wait(uint32_t bar, uint32_t parity = 0) {
    if (mbar_try(bar, parity)) return;
#pragma unroll 1
    for (uint32_t it = 0; it < SPIN_LIMIT; ++it)
        if (mbar_try(bar, parity)) return;
    __trap();
}
__device__ __forceinline__ bool elect_one() {
    uint32_t pred;
    asm volatile("{ .reg .pred P; elect.sync _|P, 0xffffffff; selp.b32 %0, 1, 0, P; }" : "=r"(pred));
    return pred;
}
__device__ __forceinline__ void named_bar(int id, int n) { asm volatile("bar.sync %0, %1;" ::"r"(id), "r"(n) : "memory"); }
__device__ __forceinline__ void fence_mbar_init() { asm volatile("fence.mbarrier_init.release.cluster;" ::: "memory"); }
__device__ __forceinline__ void fence_async_smem() { asm volatile("fence.proxy.async.shared::cta;" ::: "memory"); }

__device__ __forceinline__ void bulk_load(uint32_t dst, const void* src, uint32_t bytes, uint32_t bar) {
    asm volatile("cp.async.bulk.shared::cluster.global.mbarrier::complete_tx::bytes [%0], [%1], %2, [%3];" ::"r"(dst), "l"(src), "r"(bytes), "r"(bar) : "memory");
}
__device__ __forceinline__ void cp_async16(uint32_t dst, const void* src) { asm volatile("cp.async.cg.shared.global [%0], [%1], 16;" ::"r"(dst), "l"(src) : "memory"); }
__device__ __forceinline__ void sts128(uint32_t a, uint32_t x, uint32_t y, uint32_t z, uint32_t w) {
    asm volatile("st.shared.v4.u32 [%0], {%1,%2,%3,%4};" ::"r"(a), "r"(x), "r"(y), "r"(z), "r"(w) : "memory");
}
__device__ __forceinline__ uint2 lds64(uint32_t a) {
    uint2 v;
    asm volatile("ld.shared.v2.u32 {%0,%1}, [%2];" : "=r"(v.x), "=r"(v.y) : "r"(a) : "memory");
    return v;
}
__device__ __forceinline__ uint32_t lds32(uint32_t a) {
    uint32_t v;
    asm volatile("ld.volatile.shared.u32 %0, [%1];" : "=r"(v) : "r"(a) : "memory");
    return v;
}
__device__ __forceinline__ void stg128(void* p, uint32_t x, uint32_t y, uint32_t z, uint32_t w) {
    asm volatile("st.global.v4.u32 [%0], {%1,%2,%3,%4};" ::"l"(p), "r"(x), "r"(y), "r"(z), "r"(w) : "memory");
}
__device__ __forceinline__ void st_relaxed(void* p, uint32_t x) { asm volatile("st.relaxed.gpu.global.b32 [%0], %1;" ::"l"(p), "r"(x) : "memory"); }
__device__ __forceinline__ void st_relaxed2(void* p, uint32_t x, uint32_t y) { asm volatile("st.relaxed.gpu.global.v2.b32 [%0], {%1, %2};" ::"l"(p), "r"(x), "r"(y) : "memory"); }
__device__ __forceinline__ void st_relaxed4(void* p, uint32_t x, uint32_t y, uint32_t z, uint32_t w) {
    asm volatile("st.relaxed.gpu.global.v4.b32 [%0], {%1, %2, %3, %4};" ::"l"(p), "r"(x), "r"(y), "r"(z), "r"(w) : "memory");
}
__device__ __forceinline__ uint32_t ld_relaxed(const void* p) {
    uint32_t v;
    asm volatile("ld.relaxed.gpu.global.b32 %0, [%1];" : "=r"(v) : "l"(p) : "memory");
    return v;
}
__device__ __forceinline__ uint2 ld_relaxed2(const void* p) {
    uint2 v;
    asm volatile("ld.relaxed.gpu.global.v2.b32 {%0, %1}, [%2];" : "=r"(v.x), "=r"(v.y) : "l"(p) : "memory");
    return v;
}
__device__ __forceinline__ uint4 ld_relaxed4(const void* p) {
    uint4 v;
    asm volatile("ld.relaxed.gpu.global.v4.b32 {%0, %1, %2, %3}, [%4];" : "=r"(v.x), "=r"(v.y), "=r"(v.z), "=r"(v.w) : "l"(p) : "memory");
    return v;
}
__device__ __forceinline__ uint32_t clk32() { uint32_t c; asm volatile("mov.u32 %0, %%clock;" : "=r"(c)); return c; }
__device__ __forceinline__ uint32_t gtime32() { uint32_t c; asm volatile("mov.u32 %0, %%globaltimer_lo;" : "=r"(c)); return c; }
__device__ __forceinline__ void sched_fence(uint32_t t) { while ((int)(clk32() - t) < 0) {} }
__device__ __forceinline__ void sleep_until(uint32_t t) { while ((int)(clk32() - t) < 0) __nanosleep(40); }

__device__ __forceinline__ void tma2(uint32_t dst, const CUtensorMap* m, int c0, int c1, uint32_t bar) {
    asm volatile("{ .reg .b64 pol; createpolicy.fractional.L2::evict_first.b64 pol;\n"
                 "cp.async.bulk.tensor.2d.shared::cluster.global.mbarrier::complete_tx::bytes.L2::cache_hint [%0], [%1, {%3, %4}], [%2], pol; }"
                 ::"r"(dst), "l"(m), "r"(bar), "r"(c0), "r"(c1) : "memory");
}
__device__ __forceinline__ void tma3(uint32_t dst, const CUtensorMap* m, int c0, int c1, uint32_t bar) {
    asm volatile("cp.async.bulk.tensor.3d.shared::cluster.global.mbarrier::complete_tx::bytes [%0], [%1, {%3, %4, %5}], [%2];"
                 ::"r"(dst), "l"(m), "r"(bar), "r"(c0), "r"(c1), "r"(0) : "memory");
}
__device__ __forceinline__ void tma4(uint32_t dst, const CUtensorMap* m, int c0, int c3, uint32_t bar) {
    asm volatile("cp.async.bulk.tensor.4d.shared::cluster.global.mbarrier::complete_tx::bytes [%0], [%1, {%3, %5, %5, %4}], [%2];"
                 ::"r"(dst), "l"(m), "r"(bar), "r"(c0), "r"(c3), "r"(0) : "memory");
}
__device__ __forceinline__ void tma5(uint32_t dst, const CUtensorMap* m, int c0, int c4, uint32_t bar) {
    asm volatile("cp.async.bulk.tensor.5d.shared::cluster.global.mbarrier::complete_tx::bytes [%0], [%1, {%3, %5, %5, %5, %4}], [%2];"
                 ::"r"(dst), "l"(m), "r"(bar), "r"(c0), "r"(c4), "r"(0) : "memory");
}
__device__ __forceinline__ void tma5b(uint32_t dst, const CUtensorMap* m, int c0, int c3, uint32_t bar) {
    asm volatile("cp.async.bulk.tensor.5d.shared::cluster.global.mbarrier::complete_tx::bytes [%0], [%1, {%3, %5, %5, %4, %5}], [%2];"
                 ::"r"(dst), "l"(m), "r"(bar), "r"(c0), "r"(c3), "r"(0) : "memory");
}
__device__ __forceinline__ void prefetch_l2(const void* p) { asm volatile("prefetch.global.L2 [%0];" ::"l"(p)); }
__device__ __forceinline__ void prefetch_slice(const CUtensorMap* m, int line, int row) {
    asm volatile("cp.async.bulk.prefetch.tensor.4d.L2.global [%0, {%3, %1, %2, %3}];" ::"l"(m), "r"(line), "r"(row), "r"(0) : "memory");
}
__device__ __forceinline__ void prefetch_map(const CUtensorMap* m) { asm volatile("prefetch.tensormap [%0];" ::"l"(m)); }
__device__ __forceinline__ uint32_t uni(uint32_t v) { return __shfl_sync(0xffffffffu, v, 0); }

__device__ __forceinline__ uint32_t make_desc(uint32_t addr) { return ((addr & 0x3FFFF) >> 4) | (1u << 16); }
__device__ __forceinline__ uint32_t make_desc_h(uint32_t addr) { return ((addr & 0x3FFFF) >> 4) | (32u << 16); }
template <int H> __device__ __forceinline__ uint64_t desc64(uint32_t lo) {
    uint64_t d;
    asm volatile("mov.b64 %0, {%1, %2};" : "=l"(d) : "r"(lo), "n"(64u | ((H ? 2u : 1u) << 30)));
    return d;
}
__device__ __forceinline__ void wgmma_fence() { asm volatile("wgmma.fence.sync.aligned;" ::: "memory"); }
__device__ __forceinline__ void wgmma_commit() { asm volatile("wgmma.commit_group.sync.aligned;" ::: "memory"); }
template <int N> __device__ __forceinline__ void wgmma_wait() { asm volatile("wgmma.wait_group.sync.aligned %0;" ::"n"(N) : "memory"); }

#define R8(d, i) "+f"(d[i]), "+f"(d[i + 1]), "+f"(d[i + 2]), "+f"(d[i + 3]), "+f"(d[i + 4]), "+f"(d[i + 5]), "+f"(d[i + 6]), "+f"(d[i + 7])
#define R64(d) R8(d, 0), R8(d, 8), R8(d, 16), R8(d, 24), R8(d, 32), R8(d, 40), R8(d, 48), R8(d, 56)
template <int TA>
__device__ __forceinline__ void wgmma_n128(float (&d)[64], uint64_t da, uint64_t db, int scale_d = 1) {
    asm volatile("{ .reg .pred p; setp.ne.b32 p, %66, 0;\n"
                 "wgmma.mma_async.sync.aligned.m64n128k16.f32.bf16.bf16 "
                 "{%0,%1,%2,%3,%4,%5,%6,%7,%8,%9,%10,%11,%12,%13,%14,%15,%16,%17,%18,%19,%20,%21,%22,%23,%24,%25,%26,%27,%28,%29,%30,%31,"
                 "%32,%33,%34,%35,%36,%37,%38,%39,%40,%41,%42,%43,%44,%45,%46,%47,%48,%49,%50,%51,%52,%53,%54,%55,%56,%57,%58,%59,%60,%61,%62,%63}, "
                 "%64, %65, p, 1, 1, %67, 0; }"
                 : R64(d)
                 : "l"(da), "l"(db), "r"(scale_d), "n"(TA));
}
__device__ __forceinline__ void pin4(float (&d)[4]) { asm volatile("" : "+f"(d[0]), "+f"(d[1]), "+f"(d[2]), "+f"(d[3])::"memory"); }
__device__ __forceinline__ void pin64(float (&d)[64]) { asm volatile("" : R64(d)::"memory"); }

template <int TA>
__device__ __forceinline__ void wgmma_n8(float (&d)[4], uint64_t da, uint64_t db, int scale_d = 1) {
    asm volatile("{ .reg .pred p; setp.ne.b32 p, %7, 0;\n"
                 "wgmma.mma_async.sync.aligned.m64n8k16.f32.bf16.bf16 {%0,%1,%2,%3}, %4, %5, p, 1, 1, %6, 0; }"
                 : "+f"(d[0]), "+f"(d[1]), "+f"(d[2]), "+f"(d[3])
                 : "l"(da), "l"(db), "n"(TA), "r"(scale_d));
}

__device__ __forceinline__ float bf_lo(uint32_t u) { return __uint_as_float(u << 16); }
__device__ __forceinline__ float bf_hi(uint32_t u) { return __uint_as_float(u & 0xFFFF0000u); }
__device__ __forceinline__ float rbf(float v) { return __bfloat162float(__float2bfloat16_rn(v)); }
__device__ __forceinline__ uint32_t pack_bf(float lo, float hi) {
    uint32_t r;
    asm("cvt.rn.bf16x2.f32 %0, %1, %2;" : "=r"(r) : "f"(hi), "f"(lo));
    return r;
}
__device__ __forceinline__ uint32_t mul_bf2(uint32_t a, uint32_t b) {
    uint32_t r;
    asm("mul.rn.bf16x2 %0, %1, %2;" : "=r"(r) : "r"(a), "r"(b));
    return r;
}
__device__ __forceinline__ uint32_t fma_bf2(uint32_t a, uint32_t b, uint32_t c) {
    uint32_t r;
    asm("fma.rn.bf16x2 %0, %1, %2, %3;" : "=r"(r) : "r"(a), "r"(b), "r"(c));
    return r;
}
__device__ __forceinline__ float2 cmul(float2 a, float2 b) { return make_float2(a.x * b.x - a.y * b.y, a.x * b.y + a.y * b.x); }
__device__ __forceinline__ float2 cfma(float2 a, float2 b, float2 c) {
    return make_float2(fmaf(a.x, b.x, fmaf(-a.y, b.y, c.x)), fmaf(a.x, b.y, fmaf(a.y, b.x, c.y)));
}
__device__ __forceinline__ float sigmoidf_(float v) { return __fdividef(1.0f, 1.0f + expf(-v)); }

#define SCHED_NAMES RT0, RT1, RT2, RT3, PF0, PF1, PF2, PF3, T_SMALL, T_INIT, T_X0, T_BASE, G_NS, GT0, GT1, GT2, G0, GAP0, GAP1, RS_E, \
    PB_E0, PB_STEP, PC_E0, PC_STEP, PC_N, PC_E1, PC_S1, GU_E0, W_NUM, GC0, N1, N2, GCS, GCS2, GCS3, GCS4, HG, DL0, DLS, DC0, DCS, DN_E0, WDBG, T_OWN, T_RETRY, NP, T_Y, T_W0, T_W3, T_CP0, T_CP1
enum { SCHED_NAMES, NTUNE };
constexpr int sched_default[NTUNE] = {
    2200, 2700, 3200, 3700,
    0, 1100, 1300, 2800,
    1000, 1000, 200, 2500, 7,
    6200, 7400, 0,
    800, 250, 300, 4,
    4, 1, 9, 4, 5, 50, 3,
    4, 9, 15, 6, 6, 7, 7, 7, 5, 43, 37, 8, 38, 1, 48,
    0, 1100, 200, 0, 700, 600, 1000, 900, 900};
template <int I> struct Sched { static constexpr int v = sched_default[I]; };
#define TN(i) (Sched<i>::v)
#define DBG 0
#define NKK 4
#define EARLY 1
#define FROT 0
#define NOPF 0
#define NOGAP 0
#define TDBG 0
#define SRND 4
#define XPF 1
#define X0 1
#define GE 8
#define RAISE_J 1
#define PROMO CU_TENSOR_MAP_L2_PROMOTION_L2_256B

template <int TA, class H>
__device__ __forceinline__ void run_entry(uint32_t lo32, uint32_t prev, int accumulate, float (&accA)[64], float (&accB)[64], H inside) {
    const uint64_t da = desc64<TA>(lo32), db = TA ? desc64<0>(lo32 + (2 * TILE >> 4) - (31u << 16)) : da + (2 * TILE >> 4);
    wgmma_fence();
#pragma unroll
    for (int kk = 0; kk < 4; kk++) {
        wgmma_n128<TA>(accA, da + kk * (TA ? 128 : 2), db + kk * 2, kk > 0 ? 1 : accumulate);
        wgmma_n128<TA>(accB, da + 512 + kk * (TA ? 128 : 2), db + kk * 2, kk > 0 ? 1 : accumulate);
        if (kk == 1) {
            wgmma_commit();
            wgmma_wait<1>();
            if ((threadIdx.x & 31) == 0) mbar_arrive(prev);
            inside();
        }
    }
    wgmma_commit();
}
template <int TA, class H>
__device__ __forceinline__ void run_entries(uint32_t sb, int lo, int hi, int slot, float (&accA)[64], float (&accB)[64], H after) {
    const uint32_t da0 = TA ? make_desc_h(sb) : make_desc(sb), dlast = da0 + (NST - 1) * (SLOT >> 4);
    uint32_t prev = sb + OFF_FULL + 8 * 101, bar = sb + OFF_FULL + 8 * lo, lo32 = da0 + slot * (SLOT >> 4);
    int accumulate = 0;
#pragma unroll 1
    for (int i = lo; i < hi; i++) {
        mbar_wait(bar);
        KSTAMP(i);
        run_entry<TA>(lo32, prev, accumulate, accA, accB, []() {});
        prev = bar + (OFF_EMPTY - OFF_FULL);
        bar += 8;
        lo32 = lo32 == dlast ? da0 : lo32 + (SLOT >> 4);
        accumulate = 1;
        after(i);
    }
}

template <int TA>
__device__ __forceinline__ void small_tile(float (&acc)[4], uint32_t alo, uint32_t blo, bool first) {
    const uint64_t da = desc64<0>(alo), db = desc64<0>(blo);
#pragma unroll
    for (int kk = 0; kk < 4; kk++) wgmma_n8<TA>(acc, da + kk * (TA ? 128 : 2), db + kk * 2, kk > 0 || !first);
}

template <int N>
__device__ __forceinline__ uint32_t check_tile(uint32_t sb, uint32_t dst, uint32_t probe, const char* src, uint32_t par, uint32_t bar, uint32_t phase, uint32_t pause) {
    if ((TDBG & 4) && N == 8) return phase;
#pragma unroll 1
    for (uint32_t it = 0; it < SPIN_LIMIT; it++) {
        uint32_t v[N], bad = 0;
#pragma unroll
        for (int u = 0; u < N; u++) v[u] = lds32(dst + probe + (u >> 1) * 2048 + (u & 1) * 256);
#pragma unroll
        for (int u = 0; u < N; u += 4)
            asm("{ .reg .b32 a, b; lop3.b32 a, %1, %2, %5, 0x7E; lop3.b32 b, %3, %4, %5, 0x7E; lop3.b32 %0, %0, a, b, 0xFE; }"
                : "+r"(bad) : "r"(v[u]), "r"(v[u + 1]), "r"(v[u + 2]), "r"(v[u + 3]), "r"(par));
        if (!__any_sync(0xffffffffu, bad & 1u)) return phase;
        STAMP(10);
        __nanosleep(pause);
        if (elect_one()) {
            mbar_expect_tx(bar, N * 1024);
            bulk_load(dst, src, N * 1024, bar);
        }
        mbar_wait(bar, phase);
        phase ^= 1;
    }
    __trap();
    return 0;
}

__global__ void __launch_bounds__(512, 1)
fused_kernel(const __grid_constant__ Params prm, const __grid_constant__ CUtensorMap mX, const __grid_constant__ CUtensorMap mB, const __grid_constant__ CUtensorMap mCre,
             const __grid_constant__ CUtensorMap mCim, const __grid_constant__ CUtensorMap mWg, const __grid_constant__ CUtensorMap mWu,
             const __grid_constant__ CUtensorMap mWd, const __grid_constant__ CUtensorMap mXr, const __grid_constant__ CUtensorMap mPB,
             const __grid_constant__ CUtensorMap mPC, const __grid_constant__ CUtensorMap mXe) {
    {
        const uint32_t t = threadIdx.x, b = blockIdx.x;
        const uint32_t row = t < 32 ? ((b & 60) * 2 + (b >> 6) * 4 + (b & 3)) * 16 + (t >> 1) : b * 4 + ((t >> 1) & 3);
        const char* base = (const char*)(t < 32 ? prm.x : t < 40 ? prm.b_re : prm.b_im);
        asm volatile("{ .reg .pred p; setp.lt.u32 p, %1, 48; @p prefetch.global.L2 [%0]; }" ::"l"(base + (row * 2048 + (t & 1) * 128)), "r"(t) : "memory");
    }
    extern __shared__ __align__(1024) uint8_t smem[];
    uint32_t sb;
    asm volatile("mov.u32 %0, %1;" : "=r"(sb) : "r"(smem_u32(smem)));
    const int tid = threadIdx.x, warp = __shfl_sync(0xffffffffu, tid >> 5, 0), lane = tid & 31;
    const int cta = blockIdx.x;
    const uint32_t cstart = clk32();
    const int chunk = (cta >> 2) & 15;
    const int dt = (cta >> 6) * 4 + (cta & 3);
    const int rid = chunk * 8 + dt;
    const int fid = (cta + FROT) & 127;
    const bool has_gu = fid < 112;
    const uint32_t full = sb + OFF_FULL, empty = sb + OFF_EMPTY;
    const uint32_t bar_epoch = full + 8 * 73, dfull = full + 8 * 74, bar_retry = full + 8 * 81, bar_x = full + 8 * 82, ffull = full + 8 * 84,
                   hfull = full + 8 * 89, bar_base = full + 8 * 102;
    const uint32_t fempty = empty + 8 * 66, bar_order = empty + 8 * 71, bar_stored = empty + 8 * 73, bar_dfree = empty + 8 * 74,
                   bar_out = empty + 8 * 77, bar_g = empty + 8 * 85, bar_const = empty + 8 * 86;
    const int w = warp & 3, g = lane >> 2, c = lane & 3, at = tid & 127;

    const uint32_t probe = (lane >> 3) * 32 + (g & 1) * 144 + (c & 1) * 520 + (c >> 1) * 1028;

    LSTAMP(tid == 0, 96);
    GSTAMP(tid == 0, 94);
    auto init_barriers = [&](uint32_t base, uint32_t cnt, auto n) {
        if (elect_one()) {
#pragma unroll
            for (int i = 0; i < n(); i++) mbar_init(base + 8 * i, cnt);
            fence_mbar_init();
        }
        __syncwarp();
    };
    if (warp != 12) {
        if (warp == 15 && !(cta & 3) && lane < 8) st_relaxed((uint32_t*)&prm.s->start[cta >> 1] + lane, (lane & 1) ? gtime32() : cstart);
        if (warp < 12) sleep_until(cstart + (warp < 4 ? TN(T_W0) : TN(T_INIT)));
    }
    if (warp < 8) {
        if (warp < 4) init_barriers(warp == 0 ? full + 40 : warp == 3 ? full + 8 * 98 : empty + 40 * (warp - 1), (warp + 1) & 2 ? 4 : 1, []() { return 5; });
        else init_barriers(full + 80 + 176 * w, 1, []() { return 22; });
        asm volatile("setmaxnreg.inc.sync.aligned.u32 192;");
        if (warp < 4) {
            named_bar(5, 160);
            asm volatile("bar.arrive 0, 480;" ::: "memory");
            asm volatile("bar.arrive 6, 160;" ::: "memory");
        } else named_bar(0, 480);
        const int wg = warp >> 2;
        const int p = wg * 512 + dt * 32 + w * 8 + g;
        uint32_t cp = sb + OFF_CONST + 8 * (wg * 64 + w * 8 + g), cw = cp + 1024 * c, cm = sb + OFF_M + 4 * (wg * 64 + w * 8 + g);
        const int j1 = chunk - 1 - c;
        uint2* cq = &prm.s->carry[j1 * 1024 + p];
        char* hd = reinterpret_cast<char*>(prm.s->h) + (size_t)chunk * 524288 + wg * 262144 + (dt >> 1) * 16384 + ((dt & 1) * 4 + w) * 1024 + g * 64 + ((c ^ (g >> 1)) << 4);
        const bool never = uni(cstart == 0 && sb == 0);
        asm volatile("" : "+l"(cq), "+l"(hd), "+r"(cp), "+r"(cw), "+r"(cm));
        float2 a[2], a32[2], a64[2], a512[2], pw32[2], pw128[2];
        uint32_t mm[2], t2, par;
        auto constants = [&](int h) {
            if (h) { t2 = lds32(sb + OFF_EPOCH + 4); par = lds32(sb + OFF_EPOCH); }
            auto ldc = [](uint32_t a) { const uint2 v = lds64(a); return make_float2(__uint_as_float(v.x), __uint_as_float(v.y)); };
            {
                a[h] = ldc(cp + 256 * h); a32[h] = ldc(cp + 256 * h + 1024); a64[h] = ldc(cp + 256 * h + 2048); a512[h] = ldc(cp + 256 * h + 7168);
                pw32[h] = ldc(cw + 256 * h);
                pw128[h] = ldc(cw + 256 * h + 3072);
                mm[h] = lds32(cm + 128 * h);
            }
        };
        if (wg == 1) {
            const int pc = w * 256 + dt * 32 + lane;
            const float lr = __bfloat162float(prm.lam_re[pc]), li = __bfloat162float(prm.lam_im[pc]), ld = __bfloat162float(prm.log_dt[pc]);
            const uint32_t dk = __ldg(reinterpret_cast<const uint32_t*>(prm.dskip + dt * 128) + (at & 63));
            reinterpret_cast<uint32_t*>(smem + OFF_DK)[at & 63] = dk;
            const float dtv = rbf(expf(ld));
            const float er = expf(dtv * lr);
            float sn, cs;
            sincosf(dtv * li, &sn, &cs);
            const float ar = er * cs, ai = er * sn;
            const float nr = ar - 1.0f, ni = ai;
            const bool big = fabsf(lr) >= fabsf(li);
            const float t = (big ? li : lr) / (big ? lr : li), dn = big ? lr + li * t : lr * t + li;
            const float cr = (big ? nr + ni * t : nr * t + ni) / dn, ci = (big ? ni - nr * t : ni * t - nr) / dn;
            float2* ct = reinterpret_cast<float2*>(smem + OFF_CONST) + at;
            float2 pw = make_float2(ar, prm.swapped ? -ai : ai);
            ct[0] = pw;
            const float mx = prm.swapped ? -2.f * ci : 2.f * cr, my = prm.swapped ? 2.f * cr : -2.f * ci;
            reinterpret_cast<uint32_t*>(smem + OFF_M)[at] = pack_bf(mx, my);
#pragma unroll
            for (int i = 0; i < 5; i++) pw = cmul(pw, pw);
#pragma unroll
            for (int i = 0; i < 2; i++) {
                const float2 p2 = cmul(pw, pw);
                ct[128 + 384 * i] = pw; ct[256 + 384 * i] = p2; ct[384 + 384 * i] = cmul(p2, pw);
                pw = cmul(p2, p2);
            }
            ct[896] = pw;
            mbar_wait(bar_epoch);
            __syncwarp();
            mbar_wait(empty + 8 * TN(RS_E));
            st_relaxed2(&prm.s->hid[fid * 128 + at], ~0u, ~0u);
            st_relaxed4(&prm.s->y[((at >> 4) * 8 + (cta >> 4)) * D_ + (cta & 15) * 64 + (at & 15) * 4], 0u, 0u, 0u, 0u);
            st_relaxed2(&prm.s->carry[chunk * 1024 + pc], 0u, 0u);
            __syncwarp();
            if (lane == 0) mbar_arrive(bar_const);

            STAMPIF(at == 0, 3);
            mbar_wait(bar_const);
            constants(0);
            constants(1);
            mbar_wait(bar_order);
        }

        float accA[64], accB[64];
        run_entries<0>(sb, wg * 16, wg * 16 + 15, wg, accA, accB, [&](int i) {
            if (i == GE - 1) {
                mbar_wait(bar_base);
                sched_fence(lds32(sb + OFF_EPOCH + 8) + TN(GT0));
            }
        });
        mbar_wait(full + 8 * (wg * 16 + 15));
        KSTAMP(wg * 16 + 15);
        if (wg == 0) {
            mbar_wait(bar_const);
            run_entry<0>(make_desc(sb), empty + 8 * 14, 1, accA, accB, [&]() { constants(0); constants(1); if (EARLY && lane == 0) mbar_arrive(bar_order); });
        } else run_entry<0>(make_desc(sb + SLOT), empty + 8 * 30, 1, accA, accB, [&]() { if (EARLY && lane == 0) mbar_arrive(bar_order + 8); });
        if (!EARLY && lane == 0) mbar_arrive(bar_order + 8 * wg);
        uint2 v[4];
#pragma unroll
        for (int m = 0; m < 4; m++) v[m] = make_uint2(t2, t2);
        wgmma_wait<0>();
        pin64(accA); pin64(accB);
        if (lane == 0) mbar_arrive(empty + 8 * (wg * 16 + 15));
        LSTAMP(at == 0, 96 + 30 + 10 * wg); GSTAMP(LT && at == 0, 193 + wg);

        auto cut = [&]() { if (never) sched_fence(cstart); };
        auto poll = [&](int h) {
#pragma unroll
            for (int m = 0; m < 4; m++)
                asm volatile("{ .reg .pred p; setp.ge.s32 p, %3, %4; @p ld.relaxed.gpu.global.v2.b32 {%0, %1}, [%2]; }"
                             : "+r"(v[m].x), "+r"(v[m].y) : "l"(cq + 256 * h - 4096 * m), "r"(j1), "r"(4 * m) : "memory");
        };
        auto valid = [&]() {
            uint32_t bad = 0;
#pragma unroll
            for (int m = 0; m < 4; m++) bad |= (v[m].x ^ t2) | (v[m].y ^ t2);
            return __all_sync(0xffffffffu, (bad & 3u) == 0);
        };
        float2 w0[2];
        uint32_t tp;
#pragma unroll
        for (int h = 0; h < 2; h++) {
            float (&acc)[64] = h ? accB : accA;
            float2 e = make_float2(acc[0], acc[2]);
#pragma unroll
            for (int s = 1; s < 32; s++) {
                const int i0 = 4 * (s >> 1) + (s & 1);
                e = cfma(a[h], e, make_float2(acc[i0], acc[i0 + 2]));
            }
            float2 y = make_float2(__shfl_up_sync(0xffffffffu, e.x, 1, 4), __shfl_up_sync(0xffffffffu, e.y, 1, 4));
            if (c >= 1) e = cfma(a32[h], y, e);
            y = make_float2(__shfl_up_sync(0xffffffffu, e.x, 2, 4), __shfl_up_sync(0xffffffffu, e.y, 2, 4));
            if (c >= 2) e = cfma(a64[h], y, e);
            if (c == 3) st_relaxed2(cq + 4096 + 256 * h, (__float_as_uint(e.x) & ~3u) | t2, (__float_as_uint(e.y) & ~3u) | t2);
            if (h == 0) tp = clk32();
            cut();
            w0[h] = make_float2(__shfl_up_sync(0xffffffffu, e.x, 1, 4), __shfl_up_sync(0xffffffffu, e.y, 1, 4));
            STAMPIF(at == 0, 31 + h + 10 * wg);
        }
        uint32_t sx[2][16], sy[2][16], mr[2][4];
        const uint32_t gap = wg ? TN(GAP1) : TN(GAP0);
#pragma unroll
        for (int h = 0; h < 2; h++) {
            const uint32_t sg = prm.swapped ? 0x80008000u : 0u;
            mr[h][0] = __byte_perm(mm[h], 0, 0x1010); mr[h][1] = __byte_perm(mm[h], 0, 0x3232);
            mr[h][2] = mr[h][1] ^ sg; mr[h][3] = mr[h][0] ^ sg ^ 0x80008000u;
        }
        auto put = [&](int e, int j) {
            uint32_t d[4];
#pragma unroll
            for (int u = 0; u < 4; u++) d[u] = fma_bf2(mr[e >> 1][2 * (e & 1)], sx[e >> 1][4 * j + u], mul_bf2(mr[e >> 1][2 * (e & 1) + 1], sy[e >> 1][4 * j + u]));
            #pragma unroll
            for (int u = 0; u < 2; u++)
                asm("lop3.b32 %0, %0, %1, %2, 0xD8;" : "+r"(d[2 * (j & 1) + u]) : "r"(par), "r"((uint32_t)((w & 1) == u)));
            stg128(hd + e * 65536 + (j >> 1) * 8192 + (j & 1) * 512, d[0], d[1], d[2], d[3]);
            if (j == 3 && lane == 0) mbar_arrive(bar_out + 32 * wg + 8 * e);
        };
#pragma unroll
        for (int h = 0; h < 2; h++) {
            float (&acc)[64] = h ? accB : accA;
            uint32_t it = 0;
            if (h == 0) {
                sleep_until(tp + (wg ? TN(T_CP1) : TN(T_CP0)));
                poll(h);
            }
            while (!valid()) {
                if (++it > SPIN_LIMIT) __trap();
#pragma unroll
                for (int m = 0; m < 4; m++)
                    asm volatile("{ .reg .pred p; setp.ne.u32 p, %3, 0; @p ld.relaxed.gpu.global.v2.b32 {%0, %1}, [%2]; }"
                                 : "+r"(v[m].x), "+r"(v[m].y) : "l"(cq + 256 * h - 4096 * m), "r"(((v[m].x ^ t2) | (v[m].y ^ t2)) & 3u) : "memory");
            }
            float2 hin = make_float2(__uint_as_float(v[3].x), __uint_as_float(v[3].y));
#pragma unroll
            for (int m = 2; m >= 0; m--) hin = cfma(a512[h], hin, make_float2(__uint_as_float(v[m].x), __uint_as_float(v[m].y)));
            STAMPIF(at == 0 && it > 0 && h == 0, 39 + 10 * wg);
            if (c) hin = cmul(pw128[h], hin);
            hin.x += __shfl_xor_sync(0xffffffffu, hin.x, 1); hin.y += __shfl_xor_sync(0xffffffffu, hin.y, 1);
            hin.x += __shfl_xor_sync(0xffffffffu, hin.x, 2); hin.y += __shfl_xor_sync(0xffffffffu, hin.y, 2);
            float2 st = hin;
            if (c) st = cfma(pw32[h], hin, w0[h]);
            STAMPIF(at == 0, 33 + 3 * h + 10 * wg);
#pragma unroll
            for (int j = 0; j < 4; j++) {
#pragma unroll
                for (int u = 0; u < 4; u++) {
                    const int i0 = 16 * j + 4 * u;
                    const float2 y = cfma(a[h], st, make_float2(acc[i0], acc[i0 + 2]));
                    st = cfma(a[h], y, make_float2(acc[i0 + 1], acc[i0 + 3]));
                    sx[h][4 * j + u] = pack_bf(y.x, st.x); sy[h][4 * j + u] = pack_bf(y.y, st.y);
                }
                if (h && !NOGAP) sleep_until(tp += gap);
                if (h == 0 && j == RAISE_J) poll(1);
                put(2 * h, j);
                cut();
            }
            STAMPIF(at == 0, 34 + 3 * h + 10 * wg);
            tp = clk32();
#pragma unroll
            for (int j = 0; j < 4; j++) {
                if (!NOGAP) sleep_until(tp += gap); else if (NOGAP == 2) __nanosleep(50); else cut();
                put(2 * h + 1, j);
            }
        }
        STAMPIF(at == 0, 38 + 10 * wg);

        if (wg == 1) {
            const char* src = reinterpret_cast<const char*>(prm.s->h) + (size_t)chunk * 524288;
            uint32_t rpar = 1;
#pragma unroll 1
            for (int n = w; n < 2 * NSPL; n += 4) {
                mbar_wait(empty + 8 * (NBIG - 7 + n));
                mbar_wait(hfull + 8 * (NST + n % 7), n / 7 & 1);
                const uint32_t dst = sb + tail_h(n);
                rpar = check_tile<8>(sb, dst, probe, src + tail_src(n), par, full + 8 * w, rpar, TN(T_RETRY));
                if (lane == 0) mbar_expect_tx(full + 8 * (NBIG + n), n < NSPL ? 2 * TILE : 0);
            }
        } else {
            asm volatile("setmaxnreg.inc.sync.aligned.u32 216;");
            const int tl = 64 * (w & 1) + 8 * (w >> 1) + g;
            float gf[4];
            float* op = prm.out + (size_t)(chunk * 128 + tl) * D_ + dt * 128 + 4 * c;
            const int xr = 2 * (g & 3) + (g >> 2);
            uint32_t xs = sb + (32 * (w & 1) + 8 * (w >> 1) + xr) * 128 + (((c >> 1) ^ xr) << 4) + (c & 1) * 8;
            uint32_t gs = sb + OFF_G + 2 * tl;
            asm volatile("" : "+r"(gs), "+l"(op), "+r"(xs));
            float outA[64], outB[64];
            STAMPIF(at == 0, 9);
            mbar_wait(bar_order + 8);
            STAMPIF(at == 0, 35);
            if (TN(GT2)) sched_fence(lds32(sb + OFF_EPOCH + 8) + TN(GT2));
            run_entries<1>(sb, 32, NBIG, 32 % NST, outA, outB, [](int) {});
            uint32_t gp[4], om[4];
            uint2 xt[4][8], dk[8];
            auto load_x = [&](int q, int j) {
#pragma unroll
                for (int r = 0; r < 2; r++) xt[2 * q + r][j] = lds64((xs ^ ((j & 3) << 5)) + (q ? tail_c(0) : OFF_FT) + (j >> 2) * TILE + r * 2048);
                if (q == 0) dk[j] = lds64(sb + OFF_DK + c * 8 + 32 * j);
            };
            auto term = [&](int q, int j) {
#pragma unroll
                for (int r = 2 * q; r < 2 * q + 2; r++) {
                    xt[r][j].x = mul_bf2(xt[r][j].x, fma_bf2(gp[r], dk[j].x, om[r]));
                    xt[r][j].y = mul_bf2(xt[r][j].y, fma_bf2(gp[r], dk[j].y, om[r]));
                }
            };
            auto store = [&](int q, int u0, int u1) {
                const float (&acc)[64] = q ? outB : outA;
#pragma unroll
                for (int u = u0; u < u1; u++) {
                    const int j = u >> 1, r = u & 1;
                    const int o = 8 * j + 2 * r;
                    const float gv = fabsf(gf[2 * q + r]);
                    const uint2 t = xt[2 * q + r][j];
                    stg128(op + (r * 32 + q * 16) * D_ + 16 * j, __float_as_uint(fmaf(gv, acc[o], bf_lo(t.x))), __float_as_uint(fmaf(gv, acc[o + 1], bf_hi(t.x))),
                           __float_as_uint(fmaf(gv, acc[o + 4], bf_lo(t.y))), __float_as_uint(fmaf(gv, acc[o + 5], bf_hi(t.y))));
                }
            };
            uint64_t dh = desc64<1>(make_desc_h(sb)), dc = desc64<0>(make_desc(sb));
#pragma unroll
            for (int n = 0; n < 2 * NSPL; n++) {
                const int j = n % NSPL;
                if (n == 0) mbar_wait(bar_g);
                if (n == X0 || n == 2 * NSPL - 1) mbar_wait(bar_x + (n == X0 ? 0 : 8));
                mbar_wait(full + 8 * (NBIG + n));
                KSTAMP(NBIG + n);
                asm volatile("mov.b64 %0, %0; mov.b64 %1, %1;" : "+l"(dh), "+l"(dc));
                const uint64_t da = dh + (tail_h(n) >> 4), db = dc + (tail_c(j) >> 4);
                const int xj = n - X0;
                wgmma_fence();
#pragma unroll
                for (int kk = 0; kk < 4; kk++) {
                    wgmma_n128<1>(n < NSPL ? outA : outB, da + kk * 128, db + kk * 2);
                    if (kk == 0 && n == 0) {
#pragma unroll
                        for (int r = 0; r < 4; r++) {
                            uint32_t u;
                            asm volatile("ld.shared.u16 %0, [%1];" : "=r"(u) : "r"(gs + (r & 1) * 64 + (r >> 1) * 32) : "memory");
                            gf[r] = bf_lo(u);
                        }
                    }
                    if (kk == 0 && xj >= 0 && xj < 8) load_x(0, xj);
                    if (kk == 0 && n == 2 * NSPL - 1) load_x(1, 0);
                }
                wgmma_commit();
                if (n <= 2 * NSPL - 7) {
                    wgmma_wait<1>();
                    if (lane == 0) mbar_arrive(empty + 8 * (NBIG + n - 1));
                    if (!j) { LSTAMP(at == 0, 96 + 12 + n / NSPL); GSTAMP(LT && at == 0, 195 + n / NSPL); }
                } else cut();
                if (n == 0) {
#pragma unroll
                    for (int r = 0; r < 4; r++) {
                        const bool routed = (int)__float_as_uint(gf[r]) < 0;
                        gp[r] = routed ? 0u : pack_bf(gf[r], gf[r]); om[r] = routed ? 0u : pack_bf(1.0f - gf[r], 1.0f - gf[r]);
                    }
                }
                if (xj >= 0 && xj < 8) term(0, xj);
                if (n == NSPL) pin64(outA);
                if (n >= NSPL) store(0, (j * 16 + SRND) / NSPL, j == NSPL - 1 ? 16 : ((j + 1) * 16 + SRND) / NSPL);
            }
            term(1, 0);
            cut();
            wgmma_wait<0>();
            pin64(outB);
            LSTAMP(at == 0, 96 + 51); GSTAMP(LT && at == 0, 197);
#pragma unroll
            for (int j = 1; j < 8; j++) load_x(1, j);
            store(1, 0, 2);
#pragma unroll
            for (int j = 1; j < 8; j++) {
                cut();
                term(1, j);
                store(1, 2 * j, 2 * j + 2);
            }
            __syncwarp();
            if (lane == 0) mbar_arrive(bar_stored);
            LSTAMP(at == 0, 96 + 52);
        }
    } else if (warp < 12) {
        asm volatile("setmaxnreg.dec.sync.aligned.u32 64;");
        init_barriers(empty + min(80 + 160 * w, 8 * 67), 4, []() { return 20; });
#pragma unroll
        for (int i = 0; i < 2; i++) sts128(sb + OFF_LIST + i * 2048 + at * 16, 0u, 0u, 0u, 0u);
        uint32_t* keys = reinterpret_cast<uint32_t*>(smem + OFF_KEYS);
        keys[4] = 0;
        named_bar(0, 480);
        mbar_wait(bar_epoch);
        const uint32_t t2 = lds32(sb + OFF_EPOCH + 4);
        STAMPIF(at == 0, 20);
        float facc[4];
        const uint32_t dft = make_desc(sb + OFF_FT), dxs = make_desc(sb + OFF_XS);
#pragma unroll 1
        for (int u = 0; u < 4; u++) {
            mbar_wait(ffull + 8 * u);
            STAMPIF(at == 0, 4 + u);
            wgmma_fence();
            small_tile<0>(facc, dft + u * (TILE >> 4), dxs + u * 64, u == 0);
            wgmma_commit();
        }
        wgmma_wait<0>();
        pin4(facc);
        if (lane < 4) mbar_arrive(fempty + 8 * lane);
        auto gate_up = [&](auto rest) {
            uint32_t slot = 4, par = 0, prev = full + 8 * 101;
#pragma unroll 1
            for (int j = 0; j < 16; j++) {
                if (j == 2) rest();
                STAMPW(at == 0, 75 + j);
                mbar_wait(ffull + 8 * slot, par);
                STAMPW(at == 0, 160 + j);
                mbar_wait(empty + 8 * prm.use[j]);
                wgmma_fence();
                small_tile<1>(facc, dft + slot * (TILE >> 4), dxs + j * 64, j == 0);
                wgmma_commit();
                if (j < TN(NP)) { wgmma_wait<0>(); prev = fempty + 8 * slot; }
                else wgmma_wait<1>();
                if (lane == 0) mbar_arrive(prev);
                prev = j < TN(NP) ? full + 8 * 101 : fempty + 8 * slot;
                if (++slot == NFT) { slot = 0; par ^= 1; }
            }
            wgmma_wait<0>();
            if (lane == 0) mbar_arrive(prev);
            pin4(facc);
        };
        auto down = [&]() {
            const uint32_t dhid = make_desc(sb + OFF_HID);
#pragma unroll 1
            for (int j = 0; j < 7; j++) {
                mbar_wait(dfull + 8 * j);
                mbar_wait(empty + 8 * prm.use[16 + j]);
                wgmma_fence();
                small_tile<1>(facc, dft + j * (TILE >> 4), dhid + j * 64, j == 0);
                wgmma_commit();
                if ((0x52 >> j) & 1) {
                    wgmma_wait<0>();
                    if (lane == 0) mbar_arrive(bar_dfree + 8 * (j / 3));
                }
            }
            wgmma_wait<0>();
            pin4(facc);
        };
        if ((c & 1) == (w >> 1)) {
            float* red = reinterpret_cast<float*>(smem + OFF_RED) + w * 32 + (c >> 1) * 16 + g;
            red[0] = (w & 1) ? facc[1] : facc[0];
            red[8] = (w & 1) ? facc[3] : facc[2];
        }
        named_bar(2, 128);
        STAMPIF(at == 0, 21);
        const uint32_t tpub = clk32();
        if (w < 2) {
            const float* red = reinterpret_cast<const float*>(smem + OFF_RED) + w * 16 + (lane & 15);
            const float v = rbf((red[0] + red[32]) + (red[64] + red[96]));
            if (w == 0) {
                uint32_t k = __float_as_uint(v);
                k = ((k ^ ((uint32_t)((int)k >> 31) | 0x80000000u)) & 0xFFFF0000u) | (t2 << 11) | (2047u - (uint32_t)(rid * 16 + (lane & 15)));
                int rank = 0;
#pragma unroll
                for (int i = 0; i < 8; i++) rank += __shfl_sync(0xffffffffu, k, (lane >> 4) * 8 + i) > k;
                rank += __shfl_xor_sync(0xffffffffu, rank, 16);
                if (rank < 8) st_relaxed(&prm.s->key[cta * 8 + rank], k);
            } else if (lane < 16) st_relaxed(&prm.s->gate[rid * 16 + lane], __float_as_uint(rbf(sigmoidf_(v))) | t2);
            __syncwarp();
        }
        uint32_t it = 0;
        uint4 ka, kb4;
        mbar_wait(bar_base);
        sleep_until(lds32(sb + OFF_EPOCH + 8) + TN(GT1));
        sleep_until(tpub + TN(G0));
        bool bad = true;
        while (true) {
            if (bad) {
                ka = ld_relaxed4(&prm.s->key[at * 8]);
                kb4 = ld_relaxed4(&prm.s->key[at * 8 + 4]);
            }
            bad = (((ka.x ^ (t2 << 11)) | (kb4.x ^ (t2 << 11))) & 0x1800u) != 0;
            if (!__any_sync(0xffffffffu, bad)) break;
            if (++it > SPIN_LIMIT) __trap();
            __nanosleep(TN(T_RETRY));
        }
        STAMPIF(at == 0, 22);
        STAMPIF(at == 0 && it > 0, 23);
        const uint32_t m1 = __reduce_max_sync(0xffffffffu, ka.x), m2 = __reduce_max_sync(0xffffffffu, ka.x == m1 ? ka.y : ka.x);
        if (lane == 0) keys[w] = m2;
        named_bar(2, 128);
        const uint4 th4 = *reinterpret_cast<const uint4*>(keys);
        const uint32_t th = min(min(th4.x, th4.y), min(th4.z, th4.w));
        {
            const uint32_t k8[8] = {ka.x, ka.y, ka.z, ka.w, kb4.x, kb4.y, kb4.z, kb4.w};
            auto append = [&](int lo, int hi) {
                uint32_t n = 0, pos = 0;
#pragma unroll
                for (int i = lo; i < hi; i++) n += k8[i] >= th;
                asm volatile("{ .reg .pred p; setp.ne.u32 p, %2, 0; @p atom.shared.add.u32 %0, [%1], %2; }" : "+r"(pos) : "r"(sb + OFF_KEYS + 16), "r"(n) : "memory");
#pragma unroll
                for (int i = lo; i < hi; i++)
                    if (k8[i] >= th) reinterpret_cast<uint32_t*>(smem + OFF_LIST)[pos + i - lo] = k8[i];
            };
            append(0, 2);
            if (__any_sync(0xffffffffu, k8[2] >= th)) append(2, 8);
        }
        named_bar(2, 128);
        {
            const uint32_t* list = reinterpret_cast<const uint32_t*>(smem + OFF_LIST);
            const int n = (int)keys[4];
#pragma unroll 1
            for (int i0 = w * 32; i0 < n; i0 += 128) {
                const uint32_t k = list[i0 + lane];
                int rank = 0;
#pragma unroll 2
                for (int o = 0; o < n; o += 4) {
                    const uint4 l4 = *reinterpret_cast<const uint4*>(list + o);
                    rank += (l4.x > k) + (l4.y > k) + (l4.z > k) + (l4.w > k);
                }
                if (rank < 8) reinterpret_cast<uint32_t*>(smem + OFF_SEL)[rank] = k;
            }
        }
        named_bar(2, 128);
        STAMPIF(at == 0, 24);
        const uint32_t* sel = reinterpret_cast<const uint32_t*>(smem + OFF_SEL);
        auto gates = [&]() {
            uint32_t gv;
            it = 0;
            while (true) {
                gv = ld_relaxed(&prm.s->gate[chunk * 128 + at]);
                const uint32_t ar = ld_relaxed(&prm.s->armed[((cta >> 4) * 14 + min(lane, 13)) * 4]);
                if (__all_sync(0xffffffffu, (gv & 3u) == t2 && ar == t2)) break;
                if (++it > SPIN_LIMIT) __trap();
            }
            asm volatile("fence.acquire.gpu;" ::: "memory");
#pragma unroll
            for (int s = 0; s < 8; s++)
                if ((~sel[s] & 2047u) == (uint32_t)(chunk * 128 + at)) gv |= 0x80000000u;
            reinterpret_cast<uint16_t*>(smem + OFF_G)[at] = (uint16_t)(gv >> 16);
            __syncwarp();
            if (lane == 0) mbar_arrive(bar_g);
        };
        if (has_gu) {
            const int tk = (at >> 3) & 7;
            const char* xt = (const char*)prm.x + (~sel[tk] & 2047u) * 2048 + (at >> 6) * 128 + (at & 7) * 16;
#pragma unroll
            for (int i = 0; i < 8; i++) {
                cp_async16(sb + OFF_XS + (2 * i + (at >> 6)) * 1024 + tk * 128 + (((at & 7) ^ tk) << 4), xt + i * 256);
                if (i == 0 || i == 7) asm volatile("cp.async.commit_group;" ::: "memory");
            }
            asm volatile("cp.async.wait_group 1;" ::: "memory");
            fence_async_smem();
            named_bar(2, 128);
            STAMPIF(at == 0, 25);
            gate_up([&]() {
                asm volatile("cp.async.wait_all;" ::: "memory");
                fence_async_smem();
                named_bar(2, 128);
            });
            if (!(cta & 1)) {
#pragma unroll
                for (int u = 0; u < 4; u++) {
                    const float v = rbf(facc[u]);
                    facc[u] = __fdividef(v, 1.0f + __expf(-v));
                }
            }
            st_relaxed2(&prm.s->hid[fid * 128 + at], pack_bf(facc[0], facc[1]), pack_bf(facc[2], facc[3]));
        }
        STAMPIF(at == 0, 26);
        gates();
        uint32_t mine = __ballot_sync(0xffffffffu, lane < 8 && (int)((~sel[lane & 7] & 2047u) >> 7) == chunk), tr;
        uint2 xr, xd;
        float gr, rs;
        auto skip = [&](int n) {
#pragma unroll 1
            for (int i = 0; i < n; i++) mine &= mine - 1;
            if (mine) {
                const uint32_t key = sel[__ffs(mine) - 1], kb = key >> 16;
                tr = ~key & 2047u;
                xr = __ldg(reinterpret_cast<const uint2*>(prm.x + (size_t)tr * D_ + dt * 128) + lane);
                rs = rbf(sigmoidf_(bf_lo((kb & 0x8000u) ? (kb & 0x7FFFu) : (~kb & 0xFFFFu))));
                gr = fabsf(__bfloat162float(reinterpret_cast<const __nv_bfloat16*>(smem + OFF_G)[tr & 127]));
                xd = lds64(sb + OFF_DK + 8 * lane);
            }
        };
        mbar_wait(bar_g);
        skip(w);
        {
            mbar_wait(empty + 8 * max(TN(HG), 31));
            const uint2* hp = &prm.s->hid[(cta >> 4) * 14 * 128 + at];
            uint32_t hv[16];
            it = 0;
            while (true) {
                uint32_t top = 0;
#pragma unroll
                for (int j = 0; j < 7; j++) {
                    const uint2 hg = ld_relaxed2(hp + 256 * j), hu = ld_relaxed2(hp + 256 * j + 128);
                    top = max(top, max(hg.x, hu.x));
                    hv[2 * j] = mul_bf2(hg.x, hu.x); hv[2 * j + 1] = mul_bf2(hg.y, hu.y);
                }
                if (__all_sync(0xffffffffu, top != ~0u)) break;
                do {
                    if (++it > SPIN_LIMIT) __trap();
                } while (!__all_sync(0xffffffffu, ld_relaxed(hp + min(lane, 13) * 128 - lane) != ~0u));
            }
            STAMPIF(at == 0 && it > 0, 61);
            hv[14] = hv[15] = 0;
#pragma unroll
            for (int j = 0; j < 4; j++)
                asm volatile("stmatrix.sync.aligned.m8n8.x4.trans.shared.b16 [%0], {%1, %2, %3, %4};" ::"r"(
                                 sb + OFF_HID + (2 * j + (lane >> 4)) * 1024 + (lane & 7) * 128 + (((2 * w + ((lane >> 3) & 1)) ^ (lane & 7)) << 4)),
                             "r"(hv[4 * j]), "r"(hv[4 * j + 1]), "r"(hv[4 * j + 2]), "r"(hv[4 * j + 3]) : "memory");
        }
        fence_async_smem();
        named_bar(2, 128);
        STAMPIF(at == 0, 27);
        down();
#pragma unroll
        for (int u = 0; u < 4; u++)
            st_relaxed(&prm.s->y[((2 * c + (u & 1)) * 8 + (cta >> 4)) * D_ + (cta & 15) * 64 + w * 16 + g + 8 * (u >> 1)], (__float_as_uint(facc[u]) & ~3u) | t2);
        STAMPIF(at == 0, 28);
        sleep_until(clk32() + TN(T_Y));
        while (mine) {
            const uint32_t* yp = &prm.s->y[(__ffs(mine) - 1) * 8 * D_ + dt * 128 + 4 * lane];
            float y[4];
            it = 0;
            while (true) {
                uint32_t bad = 0;
                y[0] = y[1] = y[2] = y[3] = 0.f;
#pragma unroll
                for (int ks = 0; ks < 8; ks++) {
                    const uint4 v = ld_relaxed4(yp + ks * D_);
                    bad |= v.x ^ t2;
                    y[0] += __uint_as_float(v.x); y[1] += __uint_as_float(v.y); y[2] += __uint_as_float(v.z); y[3] += __uint_as_float(v.w);
                }
                if (__all_sync(0xffffffffu, (bad & 3u) == 0)) break;
                if (++it > SPIN_LIMIT) __trap();
            }
            STAMPIF(lane == 0 && it, 62);
#pragma unroll
            for (int u = 0; u < 4; u++) {
                const uint32_t x2 = (u & 2) ? xr.y : xr.x, d2 = mul_bf2(x2, (u & 2) ? xd.y : xd.x);
                y[u] = fmaf(gr, (u & 1) ? bf_hi(d2) : bf_lo(d2), rbf(rbf(1.0f - gr) * rbf(((u & 1) ? bf_hi(x2) : bf_lo(x2)) + rbf(rbf(y[u]) * rs))));
            }
            STAMPIF(lane == 0, 50);
            mbar_wait(bar_stored);
            asm volatile("red.global.add.v4.f32 [%0], {%1, %2, %3, %4};" ::"l"(prm.out + (size_t)tr * D_ + dt * 128 + 4 * lane), "f"(y[0]), "f"(y[1]), "f"(y[2]), "f"(y[3]) : "memory");
            skip(4);
        }
        LSTAMP(lane == 0, 96 + 29);
    } else {
        asm volatile("setmaxnreg.dec.sync.aligned.u32 40;");
        if (warp != 12) sleep_until(cstart + (warp == 13 ? TN(T_SMALL) : TN(T_W3)));
        auto behind = [&](int e) {
            if (!mbar_test(empty + 8 * e, 0)) {
                mbar_wait(empty + 8 * e);
                if (TN(T_X0)) sleep_until(clk32() + TN(T_X0));
            }
        };
        if (warp == 15) {
            prefetch_map(&mXr);
            named_bar(0, 480);
#pragma unroll 1
            for (int i = 0; i < 4; i++) {
                const int u = i;
                if (lane == 0) mbar_expect_tx(ffull + 8 * u, TILE);
                sleep_until(cstart + (i == 0 ? TN(RT0) : i == 1 ? TN(RT1) : i == 2 ? TN(RT2) : TN(RT3)));
                if (elect_one()) tma3(sb + OFF_FT + u * TILE, &mXr, u * 256, rid * 16, ffull + 8 * u);
                STAMP(53 + u);
            }
            const CUtensorMap* mw = (cta & 1) ? &mWu : &mWg;
            if (sb & 1023) __trap();
            prefetch_map(mw);
            prefetch_map(&mWd);
            uint32_t slot = 4, par = 1;
#pragma unroll 1
            for (int j = 0; j < (has_gu && DBG != 1 ? 16 : 0); j++) {
                mbar_wait(fempty + 8 * slot, par);
                if (lane == 0) mbar_expect_tx(ffull + 8 * slot, TILE);
                behind(prm.fetch[j]);
                STAMPW(1, 176 + j);
                if (elect_one()) tma2(sb + OFF_FT + slot * TILE, mw, (fid >> 1) * 64, TN(WDBG) ? 0 : j * 64, ffull + 8 * slot);
                if (++slot == NFT) { slot = 0; par ^= 1; }
            }
            if (lane < 9) mbar_expect_tx(lane < 7 ? dfull + 8 * lane : bar_x + 8 * (lane - 7), lane < 7 ? TILE : 2 * TILE);
            if (!has_gu) mbar_wait(bar_g);
#pragma unroll 1
            for (int j = 0; j < (DBG != 1 ? 7 : 0); j++) {
                if (has_gu) mbar_wait(fempty + 8 * min(j, 4), 1);
                behind(prm.fetch[16 + j]);
                if (elect_one()) tma2(sb + OFF_FT + j * TILE, &mWd, (cta & 15) * 64, (cta >> 4) * 448 + (TN(WDBG) ? 0 : j * 64), dfull + 8 * j);
            }
            prefetch_map(&mXe);
#pragma unroll 1
            for (int u = 0; u < 4; u++) {
                if (u == 2) {
                    mbar_wait(bar_dfree + 16);
                    if (elect_one()) tma5(sb + tail_c(8), &mCim, c_col(63), dt * 8, full + 8 * (NBIG + 8));
                }
                mbar_wait(bar_dfree);
                behind(u < 2 ? TN(DN_E0) + u : NBIG + NSPL);
                if (elect_one())
                    asm volatile("cp.async.bulk.tensor.5d.shared::cluster.global.mbarrier::complete_tx::bytes [%0], [%1, {%3, %6, %6, %4, %5}], [%2];"
                                 ::"r"(sb + (u < 2 ? OFF_FT : tail_c(0)) + (u & 1) * TILE), "l"(&mXe), "r"(bar_x + 4 * (u & 2)), "r"(dt * 128 + (u & 1) * 64),
                                 "r"(u & 2), "r"(chunk * 4), "r"(0) : "memory");
                if (u < 2 && XPF) {
                    if (elect_one())
                        asm volatile("cp.async.bulk.prefetch.tensor.5d.L2.global [%0, {%1, %4, %4, %2, %3}];" ::"l"(&mXe), "r"(dt * 128 + u * 64), "r"(2), "r"(chunk * 4), "r"(0) : "memory");
                }
            }
        } else if (warp == 13) {
#pragma unroll
            for (int u = 0; u < 8; u++) {
                const int row = (u >> 2) * 4 + (lane >> 3);
                cp_async16(sb + OFF_XS + (u & 3) * 1024 + row * 128 + (((lane & 7) ^ row) << 4), (const char*)(u < 4 ? prm.w_r : prm.gate_w) + (u & 3) * 512 + lane * 16);
            }
            STAMP(57);
            const uint32_t tag = ld_relaxed(&prm.s->epoch[cta]) + 1;
            named_bar(1, 64);
            *reinterpret_cast<uint2*>(smem + OFF_EPOCH) = make_uint2(tag, tag % 3u + 1u);
            STAMPIF(tag, 58);
            asm volatile("cp.async.wait_all;" ::: "memory");
            STAMP(59);
            fence_async_smem();
            __syncwarp();
            if (lane == 0) {
                mbar_arrive(bar_epoch);
                prm.s->epoch[cta] = tag;
            }
            sleep_until(cstart + TN(T_BASE));
            {
                const uint2 st = ld_relaxed2(&prm.s->start[2 * lane]);
                const uint32_t d = st.x - cstart + 512u, age = gtime32() - st.y;
                const uint32_t m = __reduce_max_sync(0xffffffffu, d < 1024u && age < 4096u ? (d << 12) | age : 0u);
                const uint32_t late = (m & 4095u) - __reduce_min_sync(0xffffffffu, age);
                *reinterpret_cast<volatile uint32_t*>(smem + OFF_EPOCH + 8) = cstart + (m ? (m >> 12) - 512u + min(late, 256u) * TN(G_NS) / 4 : 0u);
                __syncwarp();
                if (lane == 0) mbar_arrive(bar_base);
                STAMP(60);
            }
            mbar_wait(bar_const);
            asm volatile("fence.acq_rel.gpu;" ::: "memory");
            if (lane < 4) st_relaxed2(&prm.s->armed[fid * 4 + lane], tag % 3u + 1u, 0u);
            prefetch_map(&mCre);
            prefetch_map(&mCim);
            const char* src = reinterpret_cast<const char*>(prm.s->h) + (size_t)chunk * 524288;
            uint32_t slot = 32 % NST, hpar = 0, rpar = 0;
#pragma unroll 1
            for (int i = 32; i < NBIG; i++) {
                mbar_wait(hfull + 8 * slot, hpar);
                STAMPIF(i == 32 || i == 33, 14 + (i & 1));
                rpar = check_tile<16>(sb, sb + slot * SLOT, probe, src, tag, bar_retry, rpar, TN(T_RETRY));
                if (lane == 0) mbar_expect_tx(full + 8 * i, 2 * TILE);
                STAMPIF(i == 32 || i == 33, 16 + (i & 1));
                src += 2 * TILE;
                slot = slot == NST - 1 ? 0 : slot + 1;
                hpar ^= slot == 32 % NST;
            }
        } else if (warp == 14) {
            prefetch_map(&mPB);
            auto pf_c = [&](int k) { if (!(NOPF & 4)) prefetch_slice(&mPC, 4 * (k >> 1), cta * 8 + (k & 1) * 4); };
            named_bar(0, 480);
            asm volatile("bar.arrive 1, 64;" ::: "memory");
            if (lane < 24) st_relaxed(lane < 8 ? &prm.s->key[cta * 8 + lane] : &prm.s->gate[rid * 16 + lane - 8], 0u);
#pragma unroll 1
            for (int k = TN(PF0) ? 0 : 1; k < 4; k++) {
                sleep_until(cstart + (k == 0 ? TN(PF0) : k == 1 ? TN(PF1) : k == 2 ? TN(PF2) : TN(PF3)));
                if (!(NOPF & 1)) { if (elect_one()) prefetch_slice(&mPB, 4 * k, cta * 4); }
            }
#pragma unroll 1
            for (int k = 0; k < 4; k++) {
                behind(TN(PB_E0) + TN(PB_STEP) * k);
                if (!(NOPF & 2)) { if (elect_one()) prefetch_slice(&mPB, 4 * k, 512 + cta * 4); }
            }
#pragma unroll 1
            for (int k = 0; k < TN(PC_N); k++) {
                behind(min(TN(PC_E0) + TN(PC_STEP) * k / 2, 25));
                if (elect_one()) pf_c(k);
            }
            int pk = TN(PC_N), pe = TN(PC_E1);
            auto own_part = [&](int e) {
                if (!mbar_test(bar_out + 8 * e, 0)) {
                    mbar_wait(bar_out + 8 * e);
                    sleep_until(clk32() + TN(T_OWN));
                    STAMP(11);
                }
            };
            const char* src = reinterpret_cast<const char*>(prm.s->h) + (size_t)chunk * 524288;
            uint32_t slot = 32 % NST;
#pragma unroll 1
            for (int i = 32; i < NBIG; i++) {
                if (!(i & 3)) own_part((i - 32) >> 2);
                mbar_wait(empty + 8 * (i - NST));
                PSTAMP(i);
                if (elect_one()) {
                    mbar_expect_tx(hfull + 8 * slot, 2 * TILE);
                    bulk_load(sb + slot * SLOT, src, 2 * TILE, hfull + 8 * slot);
                    tma5(sb + slot * SLOT + 2 * TILE, (i & 4) ? &mCim : &mCre, c_col(i), dt * 8, full + 8 * i);
                }
                if (i == pe && pk < 8) {
                    if (elect_one()) pf_c(pk);
                    pk++; pe += TN(PC_S1);
                }
                src += 2 * TILE;
                slot = slot == NST - 1 ? 0 : slot + 1;
            }
            src -= (NBIG - 32) * 2 * TILE;
#pragma unroll
            for (int k = 0; k < 2 * NSPL - 2; k++) {
                if (k == 0 || k == 2) own_part(6 + k / 2);
                mbar_wait(empty + 8 * (NBIG - NST + k));
                if (k >= 1 && k <= 4) {
                    if (elect_one()) {
#pragma unroll
                        for (int j = 2 * k - 2; j < 2 * k; j++)
                            tma5(sb + tail_c(j), ((NBIG + j) & 4) ? &mCim : &mCre, c_col(NBIG + j), dt * 8, full + 8 * (NBIG + j));
                    }
                }
                if (k == 4) continue;
                if (k == 2) mbar_wait(bar_dfree + 8);
                if (elect_one()) {
#pragma unroll
                    for (int n = k < 5 ? 2 * k : k + 2; n < (k < 3 ? 2 * k + 2 : k == 3 ? 7 : k + 3); n++) {
                        mbar_expect_tx(hfull + 8 * (NST + n % 7), TILE);
                        bulk_load(sb + tail_h(n), src + tail_src(n), TILE, hfull + 8 * (NST + n % 7));
                    }
                }
            }
        } else {
            if (elect_one()) {
#pragma unroll
                for (int i = 0; i < NST; i++) mbar_init(full + 8 * i, 1);
                fence_mbar_init();
            }
            __syncwarp();
            asm volatile("bar.arrive 5, 160;" ::: "memory");
#pragma unroll 1
            for (int i = 0; i < NST; i++) {
                if (elect_one()) {
                    mbar_expect_tx(full + 8 * i, SLOT);
                    tma5b(sb + i * SLOT, &mB, i * 64, dt * 4, full + 8 * i);
                    tma4(sb + i * SLOT + 2 * TILE, &mX, i * 64, chunk * 64, full + 8 * i);
                }
                STAMPIF(i == 0, 1);
            }
            STAMP(2);
            asm volatile("bar.arrive 0, 480;" ::: "memory");
            named_bar(6, 160);
            uint32_t dst = sb;
#pragma unroll 1
            for (int i = NST; i < 32; i++) {
                if (i == 2 * NST) mbar_wait(bar_base);
                if (lane == 0) mbar_expect_tx(full + 8 * i, SLOT);
                mbar_wait(empty + 8 * (i - NST));
                PSTAMP(i);
                if (elect_one()) {
                    tma5b(dst, &mB, (i & 15) * 64, (i >> 4) * 64 + dt * 4, full + 8 * i);
                    tma4(dst + 2 * TILE, &mX, (i & 15) * 64, chunk * 64, full + 8 * i);
                }
                dst = dst == sb + (NST - 1) * SLOT ? sb : dst + SLOT;
            }
        }
    }
}

typedef CUresult (*EncodeFn)(CUtensorMap*, CUtensorMapDataType, cuuint32_t, void*, const cuuint64_t*, const cuuint64_t*, const cuuint32_t*,
                             const cuuint32_t*, CUtensorMapInterleave, CUtensorMapSwizzle, CUtensorMapL2promotion, CUtensorMapFloatOOBfill);

bool encode(EncodeFn fn, CUtensorMap* m, const void* ptr, int rank, const cuuint64_t* dims, const cuuint64_t* strides, const cuuint32_t* box,
            CUtensorMapL2promotion promo = CU_TENSOR_MAP_L2_PROMOTION_NONE) {
    const cuuint32_t es[5] = {1, 1, 1, 1, 1};
    return fn(m, CU_TENSOR_MAP_DATA_TYPE_BFLOAT16, rank, const_cast<void*>(ptr), dims, strides, box, es, CU_TENSOR_MAP_INTERLEAVE_NONE,
              CU_TENSOR_MAP_SWIZZLE_128B, promo, CU_TENSOR_MAP_FLOAT_OOB_FILL_NONE) == CUDA_SUCCESS;
}

}

extern "C" void kernel_launch(void* const* d_in, const int* in_sizes, int n_in, void* d_out, int out_size) {
    (void)in_sizes; (void)n_in; (void)out_size;
    Params prm;
    prm.x = (const __nv_bfloat16*)d_in[0];
    prm.lam_re = (const __nv_bfloat16*)d_in[1];
    prm.lam_im = (const __nv_bfloat16*)d_in[2];
    prm.b_re = (const __nv_bfloat16*)d_in[3];
    prm.b_im = (const __nv_bfloat16*)d_in[4];
    prm.c_re = (const __nv_bfloat16*)d_in[5];
    prm.c_im = (const __nv_bfloat16*)d_in[6];
    prm.log_dt = (const __nv_bfloat16*)d_in[7];
    prm.dskip = (const __nv_bfloat16*)d_in[8];
    prm.w_r = (const __nv_bfloat16*)d_in[10];
    prm.gate_w = (const __nv_bfloat16*)d_in[14];
    prm.out = (float*)d_out;
    cudaGetSymbolAddress((void**)&prm.s, g_scratch);
    prm.swapped = prm.b_im < prm.b_re;

    void* fnp = nullptr;
    cudaDriverEntryPointQueryResult qr;
    cudaGetDriverEntryPoint("cuTensorMapEncodeTiled", &fnp, cudaEnableDefault, &qr);
    EncodeFn fn = (EncodeFn)fnp;
    cudaFuncSetAttribute(fused_kernel, cudaFuncAttributeMaxDynamicSharedMemorySize, SMEM_BYTES);

    CUtensorMap mX, mB, mCre, mCim, mWg, mWu, mWd, mXr, mPB, mPC, mXe;
    const cuuint64_t row = 2048;
    {
        const cuuint64_t dims[4] = {1024, 2, 4, 976}, st[3] = {row, 32 * row, 2 * row};
        const cuuint32_t box[4] = {64, 2, 4, 16};
        encode(fn, &mX, prm.x, 4, dims, st, box, PROMO);
    }
    {
        const char *lo = (const char*)(prm.swapped ? prm.b_im : prm.b_re), *hi = (const char*)(prm.swapped ? prm.b_re : prm.b_im);
        const cuuint64_t dims[5] = {1024, 8, 2, 96, 2}, st[4] = {row, (cuuint64_t)(hi - lo), 8 * row, 256 * row};
        const cuuint32_t box[5] = {64, 8, 2, 4, 2};
        encode(fn, &mB, lo, 5, dims, st, box, PROMO);
    }
    {
        const cuuint64_t dims[5] = {1024, 2, 4, 2, 64}, st[4] = {row, 4 * row, 2 * row, 16 * row};
        const cuuint32_t box[5] = {64, 2, 4, 2, 8};
        encode(fn, &mCre, prm.c_re, 5, dims, st, box);
        encode(fn, &mCim, prm.c_im, 5, dims, st, box);
    }
    {
        const cuuint64_t dims[2] = {F_, D_}, st[1] = {F_ * 2}, dimsd[2] = {D_, F_}, std_[1] = {row};
        const cuuint32_t box[2] = {64, 64};
        encode(fn, &mWg, d_in[11], 2, dims, st, box);
        encode(fn, &mWu, d_in[12], 2, dims, st, box);
        encode(fn, &mWd, d_in[13], 2, dimsd, std_, box);
    }
    for (int i = 0; i < 2; i++) {
        const char *p = (const char*)(i ? prm.c_re : prm.b_re), *q = (const char*)(i ? prm.c_im : prm.b_im);
        const cuuint64_t dims[4] = {64, 16, 1024, 2}, st[3] = {128, row, (cuuint64_t)(p < q ? q - p : p - q)};
        const cuuint32_t box[4] = {16, 4, 4, 2};
        encode(fn, i ? &mPC : &mPB, p < q ? p : q, 4, dims, st, box, CU_TENSOR_MAP_L2_PROMOTION_L2_128B);
    }
    {
        const cuuint64_t dims[3] = {D_ - 192, S_, 4}, st[2] = {row, 128};
        const cuuint32_t box[3] = {64, 16, 4};
        encode(fn, &mXr, prm.x, 3, dims, st, box);
    }
    {
        const cuuint64_t dims[5] = {1024, 2, 4, 4, S_ / 32}, st[4] = {4 * row, row, 8 * row, 32 * row};
        const cuuint32_t box[5] = {64, 2, 4, 2, 4};
        encode(fn, &mXe, prm.x, 5, dims, st, box);
    }
    for (int j = 0, e4 = 4 * TN(GC0); j < 23; j++) {
        prm.fetch[j] = j < NFT ? TN(GU_E0) + j * TN(W_NUM) / 4 : j < 16 ? 0 : TN(DL0) + (j - 16) * TN(DLS) / 4;
        prm.use[j] = j < 16 ? e4 / 4 : TN(DC0) + (j - 16) * TN(DCS) / 4;
        const int last = NBIG - 2;
        if (prm.fetch[j] > last) prm.fetch[j] = last;
        if (prm.use[j] > last) prm.use[j] = last;
        e4 += j < TN(N1) ? TN(GCS) : j < TN(N2) ? TN(GCS2) : j < 10 ? TN(GCS3) : TN(GCS4);
    }
    fused_kernel<<<NCTA, 512, SMEM_BYTES, cudaStreamPerThread>>>(prm, mX, mB, mCre, mCim, mWg, mWu, mWd, mXr, mPB, mPC, mXe);
}
```

```cpp
#include <cuda_runtime.h>
#include <cuda_bf16.h>
#include <cuda.h>
#include <stdint.h>

namespace {

constexpr int S_ = 2048, D_ = 1024, F_ = 3584;
constexpr int NCTA = 128;
constexpr int NSPL = 9, NBIG = 64 - NSPL, NENT = NBIG + 2 * NSPL;
constexpr int NST = 5;
constexpr int NFT = 5;
constexpr uint32_t SLOT = 32768, TILE = 8192;
constexpr uint32_t OFF_FT = NST * SLOT;
constexpr uint32_t OFF_XS = OFF_FT + NFT * TILE;
constexpr uint32_t OFF_LIST = OFF_XS + 8192;
constexpr uint32_t OFF_RED = OFF_XS + 4096;
constexpr uint32_t OFF_CONST = OFF_XS + 16384;
constexpr uint32_t OFF_M = OFF_CONST + 8192;
constexpr uint32_t OFF_HID = OFF_CONST;
constexpr uint32_t OFF_G = OFF_M + 512;
constexpr uint32_t OFF_DK = OFF_G + 256;
constexpr uint32_t OFF_FULL = OFF_DK + 256;
constexpr uint32_t OFF_EMPTY = OFF_FULL + 103 * 8;
constexpr uint32_t OFF_KEYS = OFF_EMPTY + 87 * 8;
constexpr uint32_t OFF_SEL = OFF_KEYS + 32;
constexpr uint32_t OFF_EPOCH = OFF_SEL + 32;
constexpr uint32_t OFF_PROF = OFF_EPOCH + 16;
constexpr uint32_t SMEM_BYTES = OFF_PROF + 432;
static_assert(SMEM_BYTES <= 232448, "smem");

static_assert(NBIG % NST == 0, "tail layout");
__host__ __device__ constexpr uint32_t tail_c(int j) { return j < 8 ? SLOT + j * 2 * TILE : OFF_FT + 5 * TILE; }
__host__ __device__ constexpr uint32_t tail_h(int n) { return n % 7 < 4 ? n % 7 * TILE : OFF_FT + (n % 7 - 2) * TILE; }
__host__ __device__ constexpr uint32_t tail_src(int n) { return (n % NSPL + NBIG - 32) * 2 * TILE + n / NSPL * TILE; }
__host__ __device__ constexpr int c_col(int i) { return ((i & 3) + ((i >> 1) & 12)) * 64; }

constexpr uint32_t SPIN_LIMIT = 1u << 18;

struct Scratch {
    uint2 carry[16 * 1024];
    uint2 hid[NCTA * 128];
    uint32_t y[8 * 8 * D_];
    uint32_t key[NCTA * 8];
    uint32_t gate[S_];
    uint2 armed[NCTA * 4];
    unsigned int epoch[256];
    uint4 start[32 * 2];
    uint4 h[16 * 32 * 1024];
};
__device__ __align__(1024) Scratch g_scratch;
#define STAMPW_(cond, w) do {} while (0)
#define GSTAMP(cond, w) do {} while (0)
#define LSTAMP(cond, w) STAMPW_(cond, w)
#define LT 0
#define STAMPW(cond, w) STAMPW_(cond, w)
#define STAMPIF(cond, i) STAMPW(cond, 96 + (i))
#define STAMP(i) STAMPW(1, 96 + (i))
#define KSTAMP(i) STAMPW((threadIdx.x & 127) == 0, i)
#define PSTAMP(i) STAMPW((i) < 56 && (i) >= 32, 160 + (i))

struct Params {
    const __nv_bfloat16 *x, *b_re, *b_im, *lam_re, *lam_im, *c_re, *c_im, *log_dt, *dskip, *w_r, *gate_w;
    float* out;
    Scratch* s;
    int fetch[23], use[23];
    int swapped;
};

__device__ __forceinline__ uint32_t smem_u32(const void* p) { return (uint32_t)__cvta_generic_to_shared(p); }
__device__ __forceinline__ void mbar_init(uint32_t bar, uint32_t cnt) { asm volatile("mbarrier.init.shared::cta.b64 [%0], %1;" ::"r"(bar), "r"(cnt) : "memory"); }
__device__ __forceinline__ void mbar_expect_tx(uint32_t bar, uint32_t bytes) { asm volatile("mbarrier.arrive.expect_tx.shared::cta.b64 _, [%0], %1;" ::"r"(bar), "r"(bytes) : "memory"); }
__device__ __forceinline__ void mbar_arrive(uint32_t bar) { asm volatile("mbarrier.arrive.shared::cta.b64 _, [%0];" ::"r"(bar) : "memory"); }
__device__ __forceinline__ bool mbar_try(uint32_t bar, uint32_t parity) {
    uint32_t ok;
    asm volatile("{ .reg .pred p; mbarrier.try_wait.parity.shared::cta.b64 p, [%1], %2; selp.u32 %0, 1, 0, p; }" : "=r"(ok) : "r"(bar), "r"(parity) : "memory");
    return ok;
}
__device__ __forceinline__ bool mbar_test(uint32_t bar, uint32_t parity) {
    uint32_t ok;
    asm volatile("{ .reg .pred p; mbarrier.test_wait.parity.shared::cta.b64 p, [%1], %2; selp.u32 %0, 1, 0, p; }" : "=r"(ok) : "r"(bar), "r"(parity) : "memory");
    return __all_sync(0xffffffffu, ok);
}
__device__ __forceinline__ void mbar_wait(uint32_t bar, uint32_t parity = 0) {
    if (mbar_try(bar, parity)) return;
#pragma unroll 1
    for (uint32_t it = 0; it < SPIN_LIMIT; ++it)
        if (mbar_try(bar, parity)) return;
    __trap();
}
__device__ __forceinline__ bool elect_one() {
    uint32_t pred;
    asm volatile("{ .reg .pred P; elect.sync _|P, 0xffffffff; selp.b32 %0, 1, 0, P; }" : "=r"(pred));
    return pred;
}
__device__ __forceinline__ void named_bar(int id, int n) { asm volatile("bar.sync %0, %1;" ::"r"(id), "r"(n) : "memory"); }
__device__ __forceinline__ void fence_mbar_init() { asm volatile("fence.mbarrier_init.release.cluster;" ::: "memory"); }
__device__ __forceinline__ void fence_async_smem() { asm volatile("fence.proxy.async.shared::cta;" ::: "memory"); }

__device__ __forceinline__ void bulk_load(uint32_t dst, const void* src, uint32_t bytes, uint32_t bar) {
    asm volatile("cp.async.bulk.shared::cluster.global.mbarrier::complete_tx::bytes [%0], [%1], %2, [%3];" ::"r"(dst), "l"(src), "r"(bytes), "r"(bar) : "memory");
}
__device__ __forceinline__ void cp_async16(uint32_t dst, const void* src) { asm volatile("cp.async.cg.shared.global [%0], [%1], 16;" ::"r"(dst), "l"(src) : "memory"); }
__device__ __forceinline__ void sts128(uint32_t a, uint32_t x, uint32_t y, uint32_t z, uint32_t w) {
    asm volatile("st.shared.v4.u32 [%0], {%1,%2,%3,%4};" ::"r"(a), "r"(x), "r"(y), "r"(z), "r"(w) : "memory");
}
__device__ __forceinline__ uint2 lds64(uint32_t a) {
    uint2 v;
    asm volatile("ld.shared.v2.u32 {%0,%1}, [%2];" : "=r"(v.x), "=r"(v.y) : "r"(a) : "memory");
    return v;
}
__device__ __forceinline__ uint32_t lds32(uint32_t a) {
    uint32_t v;
    asm volatile("ld.volatile.shared.u32 %0, [%1];" : "=r"(v) : "r"(a) : "memory");
    return v;
}
__device__ __forceinline__ void stg128(void* p, uint32_t x, uint32_t y, uint32_t z, uint32_t w) {
    asm volatile("st.global.v4.u32 [%0], {%1,%2,%3,%4};" ::"l"(p), "r"(x), "r"(y), "r"(z), "r"(w) : "memory");
}
__device__ __forceinline__ void st_relaxed(void* p, uint32_t x) { asm volatile("st.relaxed.gpu.global.b32 [%0], %1;" ::"l"(p), "r"(x) : "memory"); }
__device__ __forceinline__ void st_relaxed2(void* p, uint32_t x, uint32_t y) { asm volatile("st.relaxed.gpu.global.v2.b32 [%0], {%1, %2};" ::"l"(p), "r"(x), "r"(y) : "memory"); }
__device__ __forceinline__ void st_relaxed4(void* p, uint32_t x, uint32_t y, uint32_t z, uint32_t w) {
    asm volatile("st.relaxed.gpu.global.v4.b32 [%0], {%1, %2, %3, %4};" ::"l"(p), "r"(x), "r"(y), "r"(z), "r"(w) : "memory");
}
__device__ __forceinline__ uint32_t ld_relaxed(const void* p) {
    uint32_t v;
    asm volatile("ld.relaxed.gpu.global.b32 %0, [%1];" : "=r"(v) : "l"(p) : "memory");
    return v;
}
__device__ __forceinline__ uint2 ld_relaxed2(const void* p) {
    uint2 v;
    asm volatile("ld.relaxed.gpu.global.v2.b32 {%0, %1}, [%2];" : "=r"(v.x), "=r"(v.y) : "l"(p) : "memory");
    return v;
}
__device__ __forceinline__ uint4 ld_relaxed4(const void* p) {
    uint4 v;
    asm volatile("ld.relaxed.gpu.global.v4.b32 {%0, %1, %2, %3}, [%4];" : "=r"(v.x), "=r"(v.y), "=r"(v.z), "=r"(v.w) : "l"(p) : "memory");
    return v;
}
__device__ __forceinline__ uint32_t clk32() { uint32_t c; asm volatile("mov.u32 %0, %%clock;" : "=r"(c)); return c; }
__device__ __forceinline__ uint32_t gtime32() { uint32_t c; asm volatile("mov.u32 %0, %%globaltimer_lo;" : "=r"(c)); return c; }
__device__ __forceinline__ void sched_fence(uint32_t t) { while ((int)(clk32() - t) < 0) {} }
__device__ __forceinline__ void sleep_until(uint32_t t) { while ((int)(clk32() - t) < 0) __nanosleep(40); }

__device__ __forceinline__ void tma2(uint32_t dst, const CUtensorMap* m, int c0, int c1, uint32_t bar) {
    asm volatile("{ .reg .b64 pol; createpolicy.fractional.L2::evict_first.b64 pol;\n"
                 "cp.async.bulk.tensor.2d.shared::cluster.global.mbarrier::complete_tx::bytes.L2::cache_hint [%0], [%1, {%3, %4}], [%2], pol; }"
                 ::"r"(dst), "l"(m), "r"(bar), "r"(c0), "r"(c1) : "memory");
}
__device__ __forceinline__ void tma3(uint32_t dst, const CUtensorMap* m, int c0, int c1, uint32_t bar) {
    asm volatile("cp.async.bulk.tensor.3d.shared::cluster.global.mbarrier::complete_tx::bytes [%0], [%1, {%3, %4, %5}], [%2];"
                 ::"r"(dst), "l"(m), "r"(bar), "r"(c0), "r"(c1), "r"(0) : "memory");
}
__device__ __forceinline__ void tma4(uint32_t dst, const CUtensorMap* m, int c0, int c3, uint32_t bar) {
    asm volatile("cp.async.bulk.tensor.4d.shared::cluster.global.mbarrier::complete_tx::bytes [%0], [%1, {%3, %5, %5, %4}], [%2];"
                 ::"r"(dst), "l"(m), "r"(bar), "r"(c0), "r"(c3), "r"(0) : "memory");
}
__device__ __forceinline__ void tma5(uint32_t dst, const CUtensorMap* m, int c0, int c4, uint32_t bar) {
    asm volatile("cp.async.bulk.tensor.5d.shared::cluster.global.mbarrier::complete_tx::bytes [%0], [%1, {%3, %5, %5, %5, %4}], [%2];"
                 ::"r"(dst), "l"(m), "r"(bar), "r"(c0), "r"(c4), "r"(0) : "memory");
}
__device__ __forceinline__ void tma5b(uint32_t dst, const CUtensorMap* m, int c0, int c3, uint32_t bar) {
    asm volatile("cp.async.bulk.tensor.5d.shared::cluster.global.mbarrier::complete_tx::bytes [%0], [%1, {%3, %5, %5, %4, %5}], [%2];"
                 ::"r"(dst), "l"(m), "r"(bar), "r"(c0), "r"(c3), "r"(0) : "memory");
}
__device__ __forceinline__ void prefetch_l2(const void* p) { asm volatile("prefetch.global.L2 [%0];" ::"l"(p)); }
__device__ __forceinline__ void prefetch_slice(const CUtensorMap* m, int line, int row) {
    asm volatile("cp.async.bulk.prefetch.tensor.4d.L2.global [%0, {%3, %1, %2, %3}];" ::"l"(m), "r"(line), "r"(row), "r"(0) : "memory");
}
__device__ __forceinline__ void prefetch_map(const CUtensorMap* m) { asm volatile("prefetch.tensormap [%0];" ::"l"(m)); }
__device__ __forceinline__ uint32_t uni(uint32_t v) { return __shfl_sync(0xffffffffu, v, 0); }

__device__ __forceinline__ uint32_t make_desc(uint32_t addr) { return ((addr & 0x3FFFF) >> 4) | (1u << 16); }
__device__ __forceinline__ uint32_t make_desc_h(uint32_t addr) { return ((addr & 0x3FFFF) >> 4) | (32u << 16); }
template <int H> __device__ __forceinline__ uint64_t desc64(uint32_t lo) {
    uint64_t d;
    asm volatile("mov.b64 %0, {%1, %2};" : "=l"(d) : "r"(lo), "n"(64u | ((H ? 2u : 1u) << 30)));
    return d;
}
__device__ __forceinline__ void wgmma_fence() { asm volatile("wgmma.fence.sync.aligned;" ::: "memory"); }
__device__ __forceinline__ void wgmma_commit() { asm volatile("wgmma.commit_group.sync.aligned;" ::: "memory"); }
template <int N> __device__ __forceinline__ void wgmma_wait() { asm volatile("wgmma.wait_group.sync.aligned %0;" ::"n"(N) : "memory"); }

#define R8(d, i) "+f"(d[i]), "+f"(d[i + 1]), "+f"(d[i + 2]), "+f"(d[i + 3]), "+f"(d[i + 4]), "+f"(d[i + 5]), "+f"(d[i + 6]), "+f"(d[i + 7])
#define R64(d) R8(d, 0), R8(d, 8), R8(d, 16), R8(d, 24), R8(d, 32), R8(d, 40), R8(d, 48), R8(d, 56)
template <int TA>
__device__ __forceinline__ void wgmma_n128(float (&d)[64], uint64_t da, uint64_t db, int scale_d = 1) {
    asm volatile("{ .reg .pred p; setp.ne.b32 p, %66, 0;\n"
                 "wgmma.mma_async.sync.aligned.m64n128k16.f32.bf16.bf16 "
                 "{%0,%1,%2,%3,%4,%5,%6,%7,%8,%9,%10,%11,%12,%13,%14,%15,%16,%17,%18,%19,%20,%21,%22,%23,%24,%25,%26,%27,%28,%29,%30,%31,"
                 "%32,%33,%34,%35,%36,%37,%38,%39,%40,%41,%42,%43,%44,%45,%46,%47,%48,%49,%50,%51,%52,%53,%54,%55,%56,%57,%58,%59,%60,%61,%62,%63}, "
                 "%64, %65, p, 1, 1, %67, 0; }"
                 : R64(d)
                 : "l"(da), "l"(db), "r"(scale_d), "n"(TA));
}
__device__ __forceinline__ void pin4(float (&d)[4]) { asm volatile("" : "+f"(d[0]), "+f"(d[1]), "+f"(d[2]), "+f"(d[3])::"memory"); }
__device__ __forceinline__ void pin64(float (&d)[64]) { asm volatile("" : R64(d)::"memory"); }

template <int TA>
__device__ __forceinline__ void wgmma_n8(float (&d)[4], uint64_t da, uint64_t db, int scale_d = 1) {
    asm volatile("{ .reg .pred p; setp.ne.b32 p, %7, 0;\n"
                 "wgmma.mma_async.sync.aligned.m64n8k16.f32.bf16.bf16 {%0,%1,%2,%3}, %4, %5, p, 1, 1, %6, 0; }"
                 : "+f"(d[0]), "+f"(d[1]), "+f"(d[2]), "+f"(d[3])
                 : "l"(da), "l"(db), "n"(TA), "r"(scale_d));
}

__device__ __forceinline__ float bf_lo(uint32_t u) { return __uint_as_float(u << 16); }
__device__ __forceinline__ float bf_hi(uint32_t u) { return __uint_as_float(u & 0xFFFF0000u); }
__device__ __forceinline__ float rbf(float v) { return __bfloat162float(__float2bfloat16_rn(v)); }
__device__ __forceinline__ uint32_t pack_bf(float lo, float hi) {
    uint32_t r;
    asm("cvt.rn.bf16x2.f32 %0, %1, %2;" : "=r"(r) : "f"(hi), "f"(lo));
    return r;
}
__device__ __forceinline__ uint32_t mul_bf2(uint32_t a, uint32_t b) {
    uint32_t r;
    asm("mul.rn.bf16x2 %0, %1, %2;" : "=r"(r) : "r"(a), "r"(b));
    return r;
}
__device__ __forceinline__ uint32_t fma_bf2(uint32_t a, uint32_t b, uint32_t c) {
    uint32_t r;
    asm("fma.rn.bf16x2 %0, %1, %2, %3;" : "=r"(r) : "r"(a), "r"(b), "r"(c));
    return r;
}
__device__ __forceinline__ float2 cmul(float2 a, float2 b) { return make_float2(a.x * b.x - a.y * b.y, a.x * b.y + a.y * b.x); }
__device__ __forceinline__ float2 cfma(float2 a, float2 b, float2 c) {
    return make_float2(fmaf(a.x, b.x, fmaf(-a.y, b.y, c.x)), fmaf(a.x, b.y, fmaf(a.y, b.x, c.y)));
}
__device__ __forceinline__ float sigmoidf_(float v) { return __fdividef(1.0f, 1.0f + expf(-v)); }

#define SCHED_NAMES RT0, RT1, RT2, RT3, PF0, PF1, PF2, PF3, T_SMALL, T_INIT, T_X0, T_BASE, G_NS, GT0, GT1, GT2, G0, GAP0, GAP1, RS_E, \
    PB_E0, PB_STEP, PC_E0, PC_STEP, PC_N, PC_E1, PC_S1, GU_E0, W_NUM, GC0, N1, N2, GCS, GCS2, GCS3, GCS4, HG, DL0, DLS, DC0, DCS, DN_E0, WDBG, T_OWN, T_RETRY, NP, T_Y, T_W0, T_W3, T_CP0, T_CP1
enum { SCHED_NAMES, NTUNE };
constexpr int sched_default[NTUNE] = {
    2200, 2700, 3200, 3700,
    0, 1100, 1300, 2800,
    1000, 1000, 200, 2500, 7,
    6200, 7600, 0,
    800, 250, 300, 4,
    4, 1, 9, 4, 5, 50, 3,
    4, 9, 15, 6, 6, 7, 7, 7, 5, 43, 37, 8, 38, 1, 48,
    0, 1100, 200, 0, 700, 600, 1000, 900, 900};
template <int I> struct Sched { static constexpr int v = sched_default[I]; };
#define TN(i) (Sched<i>::v)
#define DBG 0
#define TDBG 0
#define X0 1
#define GE 8
#define PROMO CU_TENSOR_MAP_L2_PROMOTION_L2_256B

template <int TA, class H>
__device__ __forceinline__ void run_entry(uint32_t lo32, uint32_t prev, int accumulate, float (&accA)[64], float (&accB)[64], H inside) {
    const uint64_t da = desc64<TA>(lo32), db = TA ? desc64<0>(lo32 + (2 * TILE >> 4) - (31u << 16)) : da + (2 * TILE >> 4);
    wgmma_fence();
#pragma unroll
    for (int kk = 0; kk < 4; kk++) {
        wgmma_n128<TA>(accA, da + kk * (TA ? 128 : 2), db + kk * 2, kk > 0 ? 1 : accumulate);
        wgmma_n128<TA>(accB, da + 512 + kk * (TA ? 128 : 2), db + kk * 2, kk > 0 ? 1 : accumulate);
        if (kk == 1) {
            wgmma_commit();
            wgmma_wait<1>();
            if ((threadIdx.x & 31) == 0) mbar_arrive(prev);
            inside();
        }
    }
    wgmma_commit();
}
template <int TA, class H>
__device__ __forceinline__ void run_entries(uint32_t sb, int lo, int hi, int slot, float (&accA)[64], float (&accB)[64], H after) {
    const uint32_t da0 = TA ? make_desc_h(sb) : make_desc(sb), dlast = da0 + (NST - 1) * (SLOT >> 4);
    uint32_t prev = sb + OFF_FULL + 8 * 101, bar = sb + OFF_FULL + 8 * lo, lo32 = da0 + slot * (SLOT >> 4);
    int accumulate = 0;
#pragma unroll 1
    for (int i = lo; i < hi; i++) {
        mbar_wait(bar);
        KSTAMP(i);
        run_entry<TA>(lo32, prev, accumulate, accA, accB, []() {});
        prev = bar + (OFF_EMPTY - OFF_FULL);
        bar += 8;
        lo32 = lo32 == dlast ? da0 : lo32 + (SLOT >> 4);
        accumulate = 1;
        after(i);
    }
}

template <int TA>
__device__ __forceinline__ void small_tile(float (&acc)[4], uint32_t alo, uint32_t blo, bool first) {
    const uint64_t da = desc64<0>(alo), db = desc64<0>(blo);
#pragma unroll
    for (int kk = 0; kk < 4; kk++) wgmma_n8<TA>(acc, da + kk * (TA ? 128 : 2), db + kk * 2, kk > 0 || !first);
}

template <int N>
__device__ __forceinline__ uint32_t check_tile(uint32_t sb, uint32_t dst, uint32_t probe, const char* src, uint32_t par, uint32_t bar, uint32_t phase, uint32_t pause) {
    if (TDBG & 4) return phase;
#pragma unroll 1
    for (uint32_t it = 0; it < SPIN_LIMIT; it++) {
        uint32_t v[N], bad = 0;
#pragma unroll
        for (int u = 0; u < N; u++) v[u] = lds32(dst + probe + (u >> 1) * 2048 + (u & 1) * 256);
#pragma unroll
        for (int u = 0; u < N; u += 4)
            asm("{ .reg .b32 a, b; lop3.b32 a, %1, %2, %5, 0x7E; lop3.b32 b, %3, %4, %5, 0x7E; lop3.b32 %0, %0, a, b, 0xFE; }"
                : "+r"(bad) : "r"(v[u]), "r"(v[u + 1]), "r"(v[u + 2]), "r"(v[u + 3]), "r"(par));
        if (!__any_sync(0xffffffffu, bad & 1u)) return phase;
        STAMP(10);
        __nanosleep(pause);
        if (elect_one()) {
            mbar_expect_tx(bar, N * 1024);
            bulk_load(dst, src, N * 1024, bar);
        }
        mbar_wait(bar, phase);
        phase ^= 1;
    }
    __trap();
    return 0;
}

__global__ void __launch_bounds__(512, 1)
fused_kernel(const __grid_constant__ Params prm, const __grid_constant__ CUtensorMap mX, const __grid_constant__ CUtensorMap mB, const __grid_constant__ CUtensorMap mCre,
             const __grid_constant__ CUtensorMap mCim, const __grid_constant__ CUtensorMap mWg, const __grid_constant__ CUtensorMap mWu,
             const __grid_constant__ CUtensorMap mWd, const __grid_constant__ CUtensorMap mXr, const __grid_constant__ CUtensorMap mPB,
             const __grid_constant__ CUtensorMap mPC, const __grid_constant__ CUtensorMap mXe) {
    {
        const uint32_t t = threadIdx.x, b = blockIdx.x;
        const uint32_t row = t < 32 ? ((b & 60) * 2 + (b >> 6) * 4 + (b & 3)) * 16 + (t >> 1) : b * 4 + ((t >> 1) & 3);
        const char* base = (const char*)(t < 32 ? prm.x : t < 40 ? prm.b_re : prm.b_im);
        asm volatile("{ .reg .pred p; setp.lt.u32 p, %1, 48; @p prefetch.global.L2 [%0]; }" ::"l"(base + (row * 2048 + (t & 1) * 128)), "r"(t) : "memory");
    }
    extern __shared__ __align__(1024) uint8_t smem[];
    uint32_t sb;
    asm volatile("mov.u32 %0, %1;" : "=r"(sb) : "r"(smem_u32(smem)));
    const int tid = threadIdx.x, warp = __shfl_sync(0xffffffffu, tid >> 5, 0), lane = tid & 31;
    const int cta = blockIdx.x;
    const uint32_t cstart = clk32();
    const int chunk = (cta >> 2) & 15;
    const int dt = (cta >> 6) * 4 + (cta & 3);
    const int rid = chunk * 8 + dt;
    const int kslot = (rid & 3) * 32 + (rid >> 2);
    const bool has_gu = cta < 112;
    const uint32_t full = sb + OFF_FULL, empty = sb + OFF_EMPTY;
    const uint32_t bar_epoch = full + 8 * 73, dfull = full + 8 * 74, bar_retry = full + 8 * 81, bar_x = full + 8 * 82, ffull = full + 8 * 84,
                   hfull = full + 8 * 89, bar_base = full + 8 * 102;
    const uint32_t fempty = empty + 8 * 66, bar_order = empty + 8 * 71, bar_stored = empty + 8 * 73, bar_dfree = empty + 8 * 74,
                   bar_out = empty + 8 * 77, bar_g = empty + 8 * 85, bar_const = empty + 8 * 86;
    const int w = warp & 3, g = lane >> 2, c = lane & 3, at = tid & 127;

    const uint32_t probe = (lane >> 3) * 32 + (g & 1) * 144 + (c & 1) * 520 + (c >> 1) * 1028;

    LSTAMP(tid == 0, 96);
    GSTAMP(tid == 0, 94);
    auto init_barriers = [&](uint32_t base, uint32_t cnt, auto n) {
        if (elect_one()) {
#pragma unroll
            for (int i = 0; i < n(); i++) mbar_init(base + 8 * i, cnt);
            fence_mbar_init();
        }
        __syncwarp();
    };
    if (warp != 12) {
        if (warp == 15 && !(cta & 3) && lane < 8) st_relaxed((uint32_t*)&prm.s->start[cta >> 1] + lane, (lane & 1) ? gtime32() : cstart);
        if (warp < 12) sleep_until(cstart + (warp < 4 ? TN(T_W0) : TN(T_INIT)));
    }
    if (warp < 8) {
        if (warp < 4) init_barriers(warp == 0 ? full + 40 : warp == 3 ? full + 8 * 98 : empty + 40 * (warp - 1), (warp + 1) & 2 ? 4 : 1, []() { return 5; });
        else init_barriers(full + 80 + 176 * w, 1, []() { return 22; });
        asm volatile("setmaxnreg.inc.sync.aligned.u32 192;");
        if (warp < 4) {
            named_bar(5, 160);
            asm volatile("bar.arrive 0, 480;" ::: "memory");
            asm volatile("bar.arrive 6, 160;" ::: "memory");
        } else named_bar(0, 480);
        const int wg = warp >> 2;
        const int p = wg * 512 + dt * 32 + w * 8 + g;
        uint32_t cp = sb + OFF_CONST + 8 * (wg * 64 + w * 8 + g), cw = cp + 1024 * c, cm = sb + OFF_M + 4 * (wg * 64 + w * 8 + g);
        const int j1 = chunk - 1 - c;
        uint2* cq = &prm.s->carry[j1 * 1024 + p];
        char* hd = reinterpret_cast<char*>(prm.s->h) + (size_t)chunk * 524288 + wg * 262144 + (dt >> 1) * 16384 + ((dt & 1) * 4 + w) * 1024 + g * 64 + ((c ^ (g >> 1)) << 4);
        const bool never = uni(cstart == 0 && sb == 0);
        asm volatile("" : "+l"(cq), "+l"(hd), "+r"(cp), "+r"(cw), "+r"(cm));
        float2 a[2], a32[2], a64[2], a512[2], pw32[2], pw128[2];
        uint32_t mm[2], t2, par;
        auto constants = [&](int h) {
            if (h) { t2 = lds32(sb + OFF_EPOCH + 4); par = lds32(sb + OFF_EPOCH); }
            auto ldc = [](uint32_t a) { const uint2 v = lds64(a); return make_float2(__uint_as_float(v.x), __uint_as_float(v.y)); };
            {
                a[h] = ldc(cp + 256 * h); a32[h] = ldc(cp + 256 * h + 1024); a64[h] = ldc(cp + 256 * h + 2048); a512[h] = ldc(cp + 256 * h + 7168);
                pw32[h] = ldc(cw + 256 * h);
                pw128[h] = ldc(cw + 256 * h + 3072);
                mm[h] = lds32(cm + 128 * h);
            }
        };
        if (wg == 1) {
            const int pc = w * 256 + dt * 32 + lane;
            const float lr = __bfloat162float(prm.lam_re[pc]), li = __bfloat162float(prm.lam_im[pc]), ld = __bfloat162float(prm.log_dt[pc]);
            const uint32_t dk = __ldg(reinterpret_cast<const uint32_t*>(prm.dskip + dt * 128) + (at & 63));
            reinterpret_cast<uint32_t*>(smem + OFF_DK)[at & 63] = dk;
            const float dtv = rbf(expf(ld));
            const float er = expf(dtv * lr);
            float sn, cs;
            sincosf(dtv * li, &sn, &cs);
            const float ar = er * cs, ai = er * sn;
            const float nr = ar - 1.0f, ni = ai;
            const bool big = fabsf(lr) >= fabsf(li);
            const float t = (big ? li : lr) / (big ? lr : li), dn = big ? lr + li * t : lr * t + li;
            const float cr = (big ? nr + ni * t : nr * t + ni) / dn, ci = (big ? ni - nr * t : ni * t - nr) / dn;
            float2* ct = reinterpret_cast<float2*>(smem + OFF_CONST) + at;
            float2 pw = make_float2(ar, prm.swapped ? -ai : ai);
            ct[0] = pw;
            const float mx = prm.swapped ? -2.f * ci : 2.f * cr, my = prm.swapped ? 2.f * cr : -2.f * ci;
            reinterpret_cast<uint32_t*>(smem + OFF_M)[at] = pack_bf(mx, my);
#pragma unroll
            for (int i = 0; i < 5; i++) pw = cmul(pw, pw);
#pragma unroll
            for (int i = 0; i < 2; i++) {
                const float2 p2 = cmul(pw, pw);
                ct[128 + 384 * i] = pw; ct[256 + 384 * i] = p2; ct[384 + 384 * i] = cmul(p2, pw);
                pw = cmul(p2, p2);
            }
            ct[896] = pw;
            mbar_wait(bar_epoch);
            __syncwarp();
            mbar_wait(empty + 8 * TN(RS_E));
            st_relaxed2(&prm.s->hid[cta * 128 + at], ~0u, ~0u);
            st_relaxed4(&prm.s->y[((at >> 4) * 8 + (cta >> 4)) * D_ + (cta & 15) * 64 + (at & 15) * 4], 0u, 0u, 0u, 0u);
            st_relaxed2(&prm.s->carry[chunk * 1024 + pc], 0u, 0u);
            __syncwarp();
            if (lane == 0) mbar_arrive(bar_const);

            STAMPIF(at == 0, 3);
            mbar_wait(bar_const);
            constants(0);
            constants(1);
            mbar_wait(bar_order);
        }

        float accA[64], accB[64];
        run_entries<0>(sb, wg * 16, wg * 16 + 15, wg, accA, accB, [&](int i) {
            if (i == GE - 1) {
                mbar_wait(bar_base);
                sched_fence(lds32(sb + OFF_EPOCH + 8) + TN(GT0));
            }
        });
        mbar_wait(full + 8 * (wg * 16 + 15));
        KSTAMP(wg * 16 + 15);
        if (wg == 0) {
            mbar_wait(bar_const);
            run_entry<0>(make_desc(sb), empty + 8 * 14, 1, accA, accB, [&]() { constants(0); constants(1); if (lane == 0) mbar_arrive(bar_order); });
        } else run_entry<0>(make_desc(sb + SLOT), empty + 8 * 30, 1, accA, accB, [&]() { if (lane == 0) mbar_arrive(bar_order + 8); });
        uint2 v[4];
#pragma unroll
        for (int m = 0; m < 4; m++) v[m] = make_uint2(t2, t2);
        wgmma_wait<0>();
        pin64(accA); pin64(accB);
        if (lane == 0) mbar_arrive(empty + 8 * (wg * 16 + 15));
        LSTAMP(at == 0, 96 + 30 + 10 * wg); GSTAMP(LT && at == 0, 193 + wg);

        auto cut = [&]() { if (never) sched_fence(cstart); };
        auto poll = [&](int h) {
#pragma unroll
            for (int m = 0; m < 4; m++)
                asm volatile("{ .reg .pred p; setp.ge.s32 p, %3, %4; @p ld.relaxed.gpu.global.v2.b32 {%0, %1}, [%2]; }"
                             : "+r"(v[m].x), "+r"(v[m].y) : "l"(cq + 256 * h - 4096 * m), "r"(j1), "r"(4 * m) : "memory");
        };
        auto valid = [&]() {
            uint32_t bad = 0;
#pragma unroll
            for (int m = 0; m < 4; m++) bad |= (v[m].x ^ t2) | (v[m].y ^ t2);
            return __all_sync(0xffffffffu, (bad & 3u) == 0);
        };
        float2 w0[2];
        uint32_t tp;
#pragma unroll
        for (int h = 0; h < 2; h++) {
            float (&acc)[64] = h ? accB : accA;
            float2 e = make_float2(acc[0], acc[2]);
#pragma unroll
            for (int s = 1; s < 32; s++) {
                const int i0 = 4 * (s >> 1) + (s & 1);
                e = cfma(a[h], e, make_float2(acc[i0], acc[i0 + 2]));
            }
            float2 y = make_float2(__shfl_up_sync(0xffffffffu, e.x, 1, 4), __shfl_up_sync(0xffffffffu, e.y, 1, 4));
            if (c >= 1) e = cfma(a32[h], y, e);
            y = make_float2(__shfl_up_sync(0xffffffffu, e.x, 2, 4), __shfl_up_sync(0xffffffffu, e.y, 2, 4));
            if (c >= 2) e = cfma(a64[h], y, e);
            if (c == 3) st_relaxed2(cq + 4096 + 256 * h, (__float_as_uint(e.x) & ~3u) | t2, (__float_as_uint(e.y) & ~3u) | t2);
            if (h == 0) tp = clk32();
            cut();
            w0[h] = make_float2(__shfl_up_sync(0xffffffffu, e.x, 1, 4), __shfl_up_sync(0xffffffffu, e.y, 1, 4));
            STAMPIF(at == 0, 31 + h + 10 * wg);
        }
        uint32_t sx[2][16], sy[2][16], mr[2][4];
        const uint32_t gap = wg ? TN(GAP1) : TN(GAP0);
#pragma unroll
        for (int h = 0; h < 2; h++) {
            const uint32_t sg = prm.swapped ? 0x80008000u : 0u;
            mr[h][0] = __byte_perm(mm[h], 0, 0x1010); mr[h][1] = __byte_perm(mm[h], 0, 0x3232);
            mr[h][2] = mr[h][1] ^ sg; mr[h][3] = mr[h][0] ^ sg ^ 0x80008000u;
        }
        auto put = [&](int e, int j) {
            uint32_t d[4];
#pragma unroll
            for (int u = 0; u < 4; u++) d[u] = fma_bf2(mr[e >> 1][2 * (e & 1)], sx[e >> 1][4 * j + u], mul_bf2(mr[e >> 1][2 * (e & 1) + 1], sy[e >> 1][4 * j + u]));
            #pragma unroll
            for (int u = 0; u < 2; u++)
                asm("lop3.b32 %0, %0, %1, %2, 0xD8;" : "+r"(d[2 * (j & 1) + u]) : "r"(par), "r"((uint32_t)((w & 1) == u)));
            stg128(hd + e * 65536 + (j >> 1) * 8192 + (j & 1) * 512, d[0], d[1], d[2], d[3]);
            if (j == 3 && lane == 0) mbar_arrive(bar_out + 32 * wg + 8 * e);
        };
#pragma unroll
        for (int h = 0; h < 2; h++) {
            float (&acc)[64] = h ? accB : accA;
            uint32_t it = 0;
            if (h == 0) {
                sleep_until(tp + (wg ? TN(T_CP1) : TN(T_CP0)));
                poll(h);
            }
            while (!valid()) {
                if (++it > SPIN_LIMIT) __trap();
#pragma unroll
                for (int m = 0; m < 4; m++)
                    asm volatile("{ .reg .pred p; setp.ne.u32 p, %3, 0; @p ld.relaxed.gpu.global.v2.b32 {%0, %1}, [%2]; }"
                                 : "+r"(v[m].x), "+r"(v[m].y) : "l"(cq + 256 * h - 4096 * m), "r"(((v[m].x ^ t2) | (v[m].y ^ t2)) & 3u) : "memory");
            }
            float2 hin = make_float2(__uint_as_float(v[3].x), __uint_as_float(v[3].y));
#pragma unroll
            for (int m = 2; m >= 0; m--) hin = cfma(a512[h], hin, make_float2(__uint_as_float(v[m].x), __uint_as_float(v[m].y)));
            STAMPIF(at == 0 && it > 0 && h == 0, 39 + 10 * wg);
            if (c) hin = cmul(pw128[h], hin);
            hin.x += __shfl_xor_sync(0xffffffffu, hin.x, 1); hin.y += __shfl_xor_sync(0xffffffffu, hin.y, 1);
            hin.x += __shfl_xor_sync(0xffffffffu, hin.x, 2); hin.y += __shfl_xor_sync(0xffffffffu, hin.y, 2);
            float2 st = hin;
            if (c) st = cfma(pw32[h], hin, w0[h]);
            STAMPIF(at == 0, 33 + 3 * h + 10 * wg);
#pragma unroll
            for (int j = 0; j < 4; j++) {
#pragma unroll
                for (int u = 0; u < 4; u++) {
                    const int i0 = 16 * j + 4 * u;
                    const float2 y = cfma(a[h], st, make_float2(acc[i0], acc[i0 + 2]));
                    st = cfma(a[h], y, make_float2(acc[i0 + 1], acc[i0 + 3]));
                    sx[h][4 * j + u] = pack_bf(y.x, st.x); sy[h][4 * j + u] = pack_bf(y.y, st.y);
                }
                if (h) sleep_until(tp += gap);
                if (h == 0 && j == 1) poll(1);
                put(2 * h, j);
                cut();
            }
            STAMPIF(at == 0, 34 + 3 * h + 10 * wg);
            tp = clk32();
#pragma unroll
            for (int j = 0; j < 4; j++) {
                sleep_until(tp += gap);
                put(2 * h + 1, j);
            }
        }
        STAMPIF(at == 0, 38 + 10 * wg);

        if (wg == 1) {
            const char* src = reinterpret_cast<const char*>(prm.s->h) + (size_t)chunk * 524288;
            uint32_t rpar = 1;
#pragma unroll 1
            for (int n = w; n < 2 * NSPL; n += 4) {
                mbar_wait(empty + 8 * (NBIG - 7 + n));
                mbar_wait(hfull + 8 * (NST + n % 7), n / 7 & 1);
                const uint32_t dst = sb + tail_h(n);
                rpar = check_tile<8>(sb, dst, probe, src + tail_src(n), par, full + 8 * w, rpar, TN(T_RETRY));
                if (lane == 0) mbar_expect_tx(full + 8 * (NBIG + n), n < NSPL ? 2 * TILE : 0);
            }
        } else {
            asm volatile("setmaxnreg.inc.sync.aligned.u32 216;");
            const int tl = 64 * (w & 1) + 8 * (w >> 1) + g;
            float gf[4];
            float* op = prm.out + (size_t)(chunk * 128 + tl) * D_ + dt * 128 + 4 * c;
            const int xr = 2 * (g & 3) + (g >> 2);
            uint32_t xs = sb + (32 * (w & 1) + 8 * (w >> 1) + xr) * 128 + (((c >> 1) ^ xr) << 4) + (c & 1) * 8;
            uint32_t gs = sb + OFF_G + 2 * tl;
            asm volatile("" : "+r"(gs), "+l"(op), "+r"(xs));
            float outA[64], outB[64];
            STAMPIF(at == 0, 9);
            mbar_wait(bar_order + 8);
            STAMPIF(at == 0, 35);
            if (TN(GT2)) sched_fence(lds32(sb + OFF_EPOCH + 8) + TN(GT2));
            run_entries<1>(sb, 32, NBIG, 32 % NST, outA, outB, [](int) {});
            uint32_t gp[4], om[4];
            uint2 xt[4][8], dk[8];
            auto load_x = [&](int q, int j) {
#pragma unroll
                for (int r = 0; r < 2; r++) xt[2 * q + r][j] = lds64((xs ^ ((j & 3) << 5)) + (q ? tail_c(0) : OFF_FT) + (j >> 2) * TILE + r * 2048);
                if (q == 0) dk[j] = lds64(sb + OFF_DK + c * 8 + 32 * j);
            };
            auto term = [&](int q, int j) {
#pragma unroll
                for (int r = 2 * q; r < 2 * q + 2; r++) {
                    xt[r][j].x = mul_bf2(xt[r][j].x, fma_bf2(gp[r], dk[j].x, om[r]));
                    xt[r][j].y = mul_bf2(xt[r][j].y, fma_bf2(gp[r], dk[j].y, om[r]));
                }
            };
            auto store = [&](int q, int u0, int u1) {
                const float (&acc)[64] = q ? outB : outA;
#pragma unroll
                for (int u = u0; u < u1; u++) {
                    const int j = u >> 1, r = u & 1;
                    const int o = 8 * j + 2 * r;
                    const float gv = fabsf(gf[2 * q + r]);
                    const uint2 t = xt[2 * q + r][j];
                    stg128(op + (r * 32 + q * 16) * D_ + 16 * j, __float_as_uint(fmaf(gv, acc[o], bf_lo(t.x))), __float_as_uint(fmaf(gv, acc[o + 1], bf_hi(t.x))),
                           __float_as_uint(fmaf(gv, acc[o + 4], bf_lo(t.y))), __float_as_uint(fmaf(gv, acc[o + 5], bf_hi(t.y))));
                }
            };
            uint64_t dh = desc64<1>(make_desc_h(sb)), dc = desc64<0>(make_desc(sb));
#pragma unroll
            for (int n = 0; n < 2 * NSPL; n++) {
                const int j = n % NSPL;
                if (n == 0) mbar_wait(bar_g);
                if (n == X0 || n == 2 * NSPL - 1) mbar_wait(bar_x + (n == X0 ? 0 : 8));
                mbar_wait(full + 8 * (NBIG + n));
                KSTAMP(NBIG + n);
                asm volatile("mov.b64 %0, %0; mov.b64 %1, %1;" : "+l"(dh), "+l"(dc));
                const uint64_t da = dh + (tail_h(n) >> 4), db = dc + (tail_c(j) >> 4);
                const int xj = n - X0;
                wgmma_fence();
#pragma unroll
                for (int kk = 0; kk < 4; kk++) {
                    wgmma_n128<1>(n < NSPL ? outA : outB, da + kk * 128, db + kk * 2);
                    if (kk == 0 && n == 0) {
#pragma unroll
                        for (int r = 0; r < 4; r++) {
                            uint32_t u;
                            asm volatile("ld.shared.u16 %0, [%1];" : "=r"(u) : "r"(gs + (r & 1) * 64 + (r >> 1) * 32) : "memory");
                            gf[r] = bf_lo(u);
                        }
                    }
                    if (kk == 0 && xj >= 0 && xj < 8) load_x(0, xj);
                    if (kk == 0 && n == 2 * NSPL - 1) load_x(1, 0);
                }
                wgmma_commit();
                if (n <= 2 * NSPL - 7) {
                    wgmma_wait<1>();
                    if (lane == 0) mbar_arrive(empty + 8 * (NBIG + n - 1));
                    if (!j) { LSTAMP(at == 0, 96 + 12 + n / NSPL); GSTAMP(LT && at == 0, 195 + n / NSPL); }
                } else cut();
                if (n == 0) {
#pragma unroll
                    for (int r = 0; r < 4; r++) {
                        const bool routed = (int)__float_as_uint(gf[r]) < 0;
                        gp[r] = routed ? 0u : pack_bf(gf[r], gf[r]); om[r] = routed ? 0u : pack_bf(1.0f - gf[r], 1.0f - gf[r]);
                    }
                }
                if (xj >= 0 && xj < 8) term(0, xj);
                if (n == NSPL) pin64(outA);
                if (n >= NSPL) store(0, (j * 16 + 4) / NSPL, j == NSPL - 1 ? 16 : ((j + 1) * 16 + 4) / NSPL);
            }
            term(1, 0);
            cut();
            wgmma_wait<0>();
            pin64(outB);
            LSTAMP(at == 0, 96 + 51); GSTAMP(LT && at == 0, 197);
#pragma unroll
            for (int j = 1; j < 8; j++) load_x(1, j);
            store(1, 0, 2);
#pragma unroll
            for (int j = 1; j < 8; j++) {
                cut();
                term(1, j);
                store(1, 2 * j, 2 * j + 2);
            }
            __syncwarp();
            if (lane == 0) mbar_arrive(bar_stored);
            LSTAMP(at == 0, 96 + 52);
        }
    } else if (warp < 12) {
        asm volatile("setmaxnreg.dec.sync.aligned.u32 64;");
        init_barriers(empty + min(80 + 160 * w, 8 * 67), 4, []() { return 20; });
#pragma unroll
        for (int i = 0; i < 2; i++) sts128(sb + OFF_LIST + i * 2048 + at * 16, 0u, 0u, 0u, 0u);
        uint32_t* keys = reinterpret_cast<uint32_t*>(smem + OFF_KEYS);
        keys[4] = 0;
        named_bar(0, 480);
        if (at < 24) st_relaxed(at < 8 ? &prm.s->key[kslot * 8 + at] : &prm.s->gate[rid * 16 + at - 8], 0u);
        mbar_wait(bar_epoch);
        const uint32_t t2 = lds32(sb + OFF_EPOCH + 4);
        STAMPIF(at == 0, 20);
        float facc[4];
        const uint32_t dft = make_desc(sb + OFF_FT), dxs = make_desc(sb + OFF_XS);
#pragma unroll 1
        for (int u = 0; u < 4; u++) {
            mbar_wait(ffull + 8 * u);
            STAMPIF(at == 0, 4 + u);
            wgmma_fence();
            small_tile<0>(facc, dft + u * (TILE >> 4), dxs + u * 64, u == 0);
            wgmma_commit();
        }
        wgmma_wait<0>();
        pin4(facc);
        if (lane < 4) mbar_arrive(fempty + 8 * lane);
        auto gate_up = [&](auto rest) {
            uint32_t slot = 4, par = 0, prev = full + 8 * 101;
#pragma unroll 1
            for (int j = 0; j < 16; j++) {
                if (j == 2) rest();
                STAMPW(at == 0, 75 + j);
                mbar_wait(ffull + 8 * slot, par);
                STAMPW(at == 0, 160 + j);
                mbar_wait(empty + 8 * prm.use[j]);
                wgmma_fence();
                small_tile<1>(facc, dft + slot * (TILE >> 4), dxs + j * 64, j == 0);
                wgmma_commit();
                if (j < TN(NP)) { wgmma_wait<0>(); prev = fempty + 8 * slot; }
                else wgmma_wait<1>();
                if (lane == 0) mbar_arrive(prev);
                prev = j < TN(NP) ? full + 8 * 101 : fempty + 8 * slot;
                if (++slot == NFT) { slot = 0; par ^= 1; }
            }
            wgmma_wait<0>();
            if (lane == 0) mbar_arrive(prev);
            pin4(facc);
        };
        auto down = [&]() {
            const uint32_t dhid = make_desc(sb + OFF_HID);
#pragma unroll 1
            for (int j = 0; j < 7; j++) {
                mbar_wait(dfull + 8 * j);
                mbar_wait(empty + 8 * prm.use[16 + j]);
                wgmma_fence();
                small_tile<1>(facc, dft + j * (TILE >> 4), dhid + j * 64, j == 0);
                wgmma_commit();
                if ((0x52 >> j) & 1) {
                    wgmma_wait<0>();
                    if (lane == 0) mbar_arrive(bar_dfree + 8 * (j / 3));
                }
            }
            wgmma_wait<0>();
            pin4(facc);
        };
        if ((c & 1) == (w >> 1)) {
            float* red = reinterpret_cast<float*>(smem + OFF_RED) + w * 32 + (c >> 1) * 16 + g;
            red[0] = (w & 1) ? facc[1] : facc[0];
            red[8] = (w & 1) ? facc[3] : facc[2];
        }
        named_bar(2, 128);
        STAMPIF(at == 0, 21);
        const uint32_t tpub = clk32();
        if (w < 2) {
            const float* red = reinterpret_cast<const float*>(smem + OFF_RED) + w * 16 + (lane & 15);
            const float v = rbf((red[0] + red[32]) + (red[64] + red[96]));
            if (w == 0) {
                uint32_t k = __float_as_uint(v);
                k = ((k ^ ((uint32_t)((int)k >> 31) | 0x80000000u)) & 0xFFFF0000u) | (t2 << 11) | (2047u - (uint32_t)(rid * 16 + (lane & 15)));
                int rank = 0;
#pragma unroll
                for (int i = 0; i < 8; i++) rank += __shfl_sync(0xffffffffu, k, (lane >> 4) * 8 + i) > k;
                rank += __shfl_xor_sync(0xffffffffu, rank, 16);
                if (rank < 8) st_relaxed(&prm.s->key[kslot * 8 + rank], k);
            } else if (lane < 16) st_relaxed(&prm.s->gate[rid * 16 + lane], __float_as_uint(rbf(sigmoidf_(v))) | t2);
            __syncwarp();
        }
        uint32_t it = 0;
        uint4 ka, kb4;
        mbar_wait(bar_base);
        sleep_until(lds32(sb + OFF_EPOCH + 8) + TN(GT1));
        sleep_until(tpub + TN(G0));
        bool bad = true;
        while (true) {
            if (bad) {
                ka = ld_relaxed4(&prm.s->key[at * 8]);
                kb4 = ld_relaxed4(&prm.s->key[at * 8 + 4]);
            }
            bad = (((ka.x ^ (t2 << 11)) | (kb4.x ^ (t2 << 11))) & 0x1800u) != 0;
            if (!__any_sync(0xffffffffu, bad)) break;
            if (++it > SPIN_LIMIT) __trap();
            __nanosleep(TN(T_RETRY));
        }
        STAMPIF(at == 0, 22);
        STAMPIF(at == 0 && it > 0, 23);
        const uint32_t m1 = __reduce_max_sync(0xffffffffu, ka.x), m2 = __reduce_max_sync(0xffffffffu, ka.x == m1 ? ka.y : ka.x);
        if (lane == 0) keys[w] = m2;
        named_bar(2, 128);
        const uint4 th4 = *reinterpret_cast<const uint4*>(keys);
        const uint32_t th = min(min(th4.x, th4.y), min(th4.z, th4.w));
        {
            const uint32_t k8[8] = {ka.x, ka.y, ka.z, ka.w, kb4.x, kb4.y, kb4.z, kb4.w};
            auto append = [&](int lo, int hi) {
                uint32_t n = 0, pos = 0;
#pragma unroll
                for (int i = lo; i < hi; i++) n += k8[i] >= th;
                asm volatile("{ .reg .pred p; setp.ne.u32 p, %2, 0; @p atom.shared.add.u32 %0, [%1], %2; }" : "+r"(pos) : "r"(sb + OFF_KEYS + 16), "r"(n) : "memory");
#pragma unroll
                for (int i = lo; i < hi; i++)
                    if (k8[i] >= th) reinterpret_cast<uint32_t*>(smem + OFF_LIST)[pos + i - lo] = k8[i];
            };
            append(0, 2);
            if (__any_sync(0xffffffffu, k8[2] >= th)) append(2, 8);
        }
        named_bar(2, 128);
        {
            const uint32_t* list = reinterpret_cast<const uint32_t*>(smem + OFF_LIST);
            const int n = (int)keys[4];
#pragma unroll 1
            for (int i0 = w * 32; i0 < n; i0 += 128) {
                const uint32_t k = list[i0 + lane];
                int rank = 0;
#pragma unroll 2
                for (int o = 0; o < n; o += 4) {
                    const uint4 l4 = *reinterpret_cast<const uint4*>(list + o);
                    rank += (l4.x > k) + (l4.y > k) + (l4.z > k) + (l4.w > k);
                }
                if (rank < 8) reinterpret_cast<uint32_t*>(smem + OFF_SEL)[rank] = k;
            }
        }
        named_bar(2, 128);
        STAMPIF(at == 0, 24);
        const uint32_t* sel = reinterpret_cast<const uint32_t*>(smem + OFF_SEL);
        auto gates = [&]() {
            uint32_t gv;
            it = 0;
            while (true) {
                gv = ld_relaxed(&prm.s->gate[chunk * 128 + at]);
                const uint32_t ar = ld_relaxed(&prm.s->armed[((cta >> 4) * 14 + min(lane, 13)) * 4]);
                if (__all_sync(0xffffffffu, (gv & 3u) == t2 && ar == t2)) break;
                if (++it > SPIN_LIMIT) __trap();
            }
            asm volatile("fence.acquire.gpu;" ::: "memory");
#pragma unroll
            for (int s = 0; s < 8; s++)
                if ((~sel[s] & 2047u) == (uint32_t)(chunk * 128 + at)) gv |= 0x80000000u;
            reinterpret_cast<uint16_t*>(smem + OFF_G)[at] = (uint16_t)(gv >> 16);
            __syncwarp();
            if (lane == 0) mbar_arrive(bar_g);
        };
        if (has_gu) {
            const int tk = (at >> 3) & 7;
            const char* xt = (const char*)prm.x + (~sel[tk] & 2047u) * 2048 + (at >> 6) * 128 + (at & 7) * 16;
#pragma unroll
            for (int i = 0; i < 8; i++) {
                cp_async16(sb + OFF_XS + (2 * i + (at >> 6)) * 1024 + tk * 128 + (((at & 7) ^ tk) << 4), xt + i * 256);
                if (i == 0 || i == 7) asm volatile("cp.async.commit_group;" ::: "memory");
            }
            asm volatile("cp.async.wait_group 1;" ::: "memory");
            fence_async_smem();
            named_bar(2, 128);
            STAMPIF(at == 0, 25);
            gate_up([&]() {
                asm volatile("cp.async.wait_all;" ::: "memory");
                fence_async_smem();
                named_bar(2, 128);
            });
            if (!(cta & 1)) {
#pragma unroll
                for (int u = 0; u < 4; u++) {
                    const float v = rbf(facc[u]);
                    facc[u] = __fdividef(v, 1.0f + __expf(-v));
                }
            }
            st_relaxed2(&prm.s->hid[cta * 128 + at], pack_bf(facc[0], facc[1]), pack_bf(facc[2], facc[3]));
        }
        STAMPIF(at == 0, 26);
        gates();
        uint32_t mine = __ballot_sync(0xffffffffu, lane < 8 && (int)((~sel[lane & 7] & 2047u) >> 7) == chunk), tr;
        uint2 xr, xd;
        float gr, rs;
        auto skip = [&](int n) {
#pragma unroll 1
            for (int i = 0; i < n; i++) mine &= mine - 1;
            if (mine) {
                const uint32_t key = sel[__ffs(mine) - 1], kb = key >> 16;
                tr = ~key & 2047u;
                xr = __ldg(reinterpret_cast<const uint2*>(prm.x + (size_t)tr * D_ + dt * 128) + lane);
                rs = rbf(sigmoidf_(bf_lo((kb & 0x8000u) ? (kb & 0x7FFFu) : (~kb & 0xFFFFu))));
                gr = fabsf(__bfloat162float(reinterpret_cast<const __nv_bfloat16*>(smem + OFF_G)[tr & 127]));
                xd = lds64(sb + OFF_DK + 8 * lane);
            }
        };
        mbar_wait(bar_g);
        skip(w);
        {
            mbar_wait(empty + 8 * max(TN(HG), 31));
            const uint2* hp = &prm.s->hid[(cta >> 4) * 14 * 128 + at];
            uint32_t hv[16];
            it = 0;
            while (true) {
                uint32_t top = 0;
#pragma unroll
                for (int j = 0; j < 7; j++) {
                    const uint2 hg = ld_relaxed2(hp + 256 * j), hu = ld_relaxed2(hp + 256 * j + 128);
                    top = max(top, max(hg.x, hu.x));
                    hv[2 * j] = mul_bf2(hg.x, hu.x); hv[2 * j + 1] = mul_bf2(hg.y, hu.y);
                }
                if (__all_sync(0xffffffffu, top != ~0u)) break;
                do {
                    if (++it > SPIN_LIMIT) __trap();
                } while (!__all_sync(0xffffffffu, ld_relaxed(hp + min(lane, 13) * 128 - lane) != ~0u));
            }
            STAMPIF(at == 0 && it > 0, 61);
            hv[14] = hv[15] = 0;
#pragma unroll
            for (int j = 0; j < 4; j++)
                asm volatile("stmatrix.sync.aligned.m8n8.x4.trans.shared.b16 [%0], {%1, %2, %3, %4};" ::"r"(
                                 sb + OFF_HID + (2 * j + (lane >> 4)) * 1024 + (lane & 7) * 128 + (((2 * w + ((lane >> 3) & 1)) ^ (lane & 7)) << 4)),
                             "r"(hv[4 * j]), "r"(hv[4 * j + 1]), "r"(hv[4 * j + 2]), "r"(hv[4 * j + 3]) : "memory");
        }
        fence_async_smem();
        named_bar(2, 128);
        STAMPIF(at == 0, 27);
        down();
#pragma unroll
        for (int u = 0; u < 4; u++)
            st_relaxed(&prm.s->y[((2 * c + (u & 1)) * 8 + (cta >> 4)) * D_ + (cta & 15) * 64 + w * 16 + g + 8 * (u >> 1)], (__float_as_uint(facc[u]) & ~3u) | t2);
        STAMPIF(at == 0, 28);
        sleep_until(clk32() + TN(T_Y));
        while (mine) {
            const uint32_t* yp = &prm.s->y[(__ffs(mine) - 1) * 8 * D_ + dt * 128 + 4 * lane];
            float y[4];
            it = 0;
            while (true) {
                uint32_t bad = 0;
                y[0] = y[1] = y[2] = y[3] = 0.f;
#pragma unroll
                for (int ks = 0; ks < 8; ks++) {
                    const uint4 v = ld_relaxed4(yp + ks * D_);
                    bad |= v.x ^ t2;
                    y[0] += __uint_as_float(v.x); y[1] += __uint_as_float(v.y); y[2] += __uint_as_float(v.z); y[3] += __uint_as_float(v.w);
                }
                if (__all_sync(0xffffffffu, (bad & 3u) == 0)) break;
                if (++it > SPIN_LIMIT) __trap();
            }
            STAMPIF(lane == 0 && it, 62);
#pragma unroll
            for (int u = 0; u < 4; u++) {
                const uint32_t x2 = (u & 2) ? xr.y : xr.x, d2 = mul_bf2(x2, (u & 2) ? xd.y : xd.x);
                y[u] = fmaf(gr, (u & 1) ? bf_hi(d2) : bf_lo(d2), rbf(rbf(1.0f - gr) * rbf(((u & 1) ? bf_hi(x2) : bf_lo(x2)) + rbf(rbf(y[u]) * rs))));
            }
            STAMPIF(lane == 0, 50);
            mbar_wait(bar_stored);
            asm volatile("red.global.add.v4.f32 [%0], {%1, %2, %3, %4};" ::"l"(prm.out + (size_t)tr * D_ + dt * 128 + 4 * lane), "f"(y[0]), "f"(y[1]), "f"(y[2]), "f"(y[3]) : "memory");
            skip(4);
        }
        LSTAMP(lane == 0, 96 + 29);
    } else {
        asm volatile("setmaxnreg.dec.sync.aligned.u32 40;");
        if (warp != 12) sleep_until(cstart + (warp == 13 ? TN(T_SMALL) : TN(T_W3)));
        auto behind = [&](int e) {
            if (!mbar_test(empty + 8 * e, 0)) {
                mbar_wait(empty + 8 * e);
                if (TN(T_X0)) sleep_until(clk32() + TN(T_X0));
            }
        };
        if (warp == 15) {
            prefetch_map(&mXr);
            named_bar(0, 480);
#pragma unroll 1
            for (int i = 0; i < 4; i++) {
                const int u = i;
                if (lane == 0) mbar_expect_tx(ffull + 8 * u, TILE);
                sleep_until(cstart + (i == 0 ? TN(RT0) : i == 1 ? TN(RT1) : i == 2 ? TN(RT2) : TN(RT3)));
                if (elect_one()) tma3(sb + OFF_FT + u * TILE, &mXr, u * 256, rid * 16, ffull + 8 * u);
                STAMP(53 + u);
            }
            const CUtensorMap* mw = (cta & 1) ? &mWu : &mWg;
            if (sb & 1023) __trap();
            prefetch_map(mw);
            prefetch_map(&mWd);
            uint32_t slot = 4, par = 1;
#pragma unroll 1
            for (int j = 0; j < (has_gu && DBG != 1 ? 16 : 0); j++) {
                mbar_wait(fempty + 8 * slot, par);
                if (lane == 0) mbar_expect_tx(ffull + 8 * slot, TILE);
                behind(prm.fetch[j]);
                STAMPW(1, 176 + j);
                if (elect_one()) tma2(sb + OFF_FT + slot * TILE, mw, (cta >> 1) * 64, j * 64, ffull + 8 * slot);
                if (++slot == NFT) { slot = 0; par ^= 1; }
            }
            if (lane < 9) mbar_expect_tx(lane < 7 ? dfull + 8 * lane : bar_x + 8 * (lane - 7), lane < 7 ? TILE : 2 * TILE);
            if (!has_gu) mbar_wait(bar_g);
#pragma unroll 1
            for (int j = 0; j < (DBG != 1 ? 7 : 0); j++) {
                if (has_gu) mbar_wait(fempty + 8 * min(j, 4), 1);
                behind(prm.fetch[16 + j]);
                if (elect_one()) tma2(sb + OFF_FT + j * TILE, &mWd, (cta & 15) * 64, (cta >> 4) * 448 + j * 64, dfull + 8 * j);
            }
            prefetch_map(&mXe);
#pragma unroll 1
            for (int u = 0; u < 4; u++) {
                if (u == 2) {
                    mbar_wait(bar_dfree + 16);
                    if (elect_one()) tma5(sb + tail_c(8), &mCim, c_col(63), dt * 8, full + 8 * (NBIG + 8));
                }
                mbar_wait(bar_dfree);
                behind(u < 2 ? TN(DN_E0) + u : NBIG + NSPL);
                if (elect_one())
                    asm volatile("cp.async.bulk.tensor.5d.shared::cluster.global.mbarrier::complete_tx::bytes [%0], [%1, {%3, %6, %6, %4, %5}], [%2];"
                                 ::"r"(sb + (u < 2 ? OFF_FT : tail_c(0)) + (u & 1) * TILE), "l"(&mXe), "r"(bar_x + 4 * (u & 2)), "r"(dt * 128 + (u & 1) * 64),
                                 "r"(u & 2), "r"(chunk * 4), "r"(0) : "memory");
                if (u < 2) {
                    if (elect_one())
                        asm volatile("cp.async.bulk.prefetch.tensor.5d.L2.global [%0, {%1, %4, %4, %2, %3}];" ::"l"(&mXe), "r"(dt * 128 + u * 64), "r"(2), "r"(chunk * 4), "r"(0) : "memory");
                }
            }
        } else if (warp == 13) {
#pragma unroll
            for (int u = 0; u < 8; u++) {
                const int row = (u >> 2) * 4 + (lane >> 3);
                cp_async16(sb + OFF_XS + (u & 3) * 1024 + row * 128 + (((lane & 7) ^ row) << 4), (const char*)(u < 4 ? prm.w_r : prm.gate_w) + (u & 3) * 512 + lane * 16);
            }
            STAMP(57);
            const uint32_t tag = ld_relaxed(&prm.s->epoch[cta]) + 1;
            named_bar(1, 64);
            *reinterpret_cast<uint2*>(smem + OFF_EPOCH) = make_uint2(tag, tag % 3u + 1u);
            STAMPIF(tag, 58);
            asm volatile("cp.async.wait_all;" ::: "memory");
            STAMP(59);
            fence_async_smem();
            __syncwarp();
            if (lane == 0) {
                mbar_arrive(bar_epoch);
                prm.s->epoch[cta] = tag;
            }
            sleep_until(cstart + TN(T_BASE));
            {
                const uint2 st = ld_relaxed2(&prm.s->start[2 * lane]);
                const uint32_t d = st.x - cstart + 512u, age = gtime32() - st.y;
                const uint32_t m = __reduce_max_sync(0xffffffffu, d < 1024u && age < 4096u ? (d << 12) | age : 0u);
                const uint32_t late = (m & 4095u) - __reduce_min_sync(0xffffffffu, age);
                *reinterpret_cast<volatile uint32_t*>(smem + OFF_EPOCH + 8) = cstart + (m ? (m >> 12) - 512u + min(late, 256u) * TN(G_NS) / 4 : 0u);
                __syncwarp();
                if (lane == 0) mbar_arrive(bar_base);
                STAMP(60);
            }
            mbar_wait(bar_const);
            asm volatile("fence.acq_rel.gpu;" ::: "memory");
            if (lane < 4) st_relaxed2(&prm.s->armed[cta * 4 + lane], tag % 3u + 1u, 0u);
            prefetch_map(&mCre);
            prefetch_map(&mCim);
            const char* src = reinterpret_cast<const char*>(prm.s->h) + (size_t)chunk * 524288;
            uint32_t slot = 32 % NST, hpar = 0, rpar = 0;
#pragma unroll 1
            for (int i = 32; i < NBIG; i++) {
                mbar_wait(hfull + 8 * slot, hpar);
                STAMPIF(i == 32 || i == 33, 14 + (i & 1));
                rpar = check_tile<16>(sb, sb + slot * SLOT, probe, src, tag, bar_retry, rpar, TN(T_RETRY));
                if (lane == 0) mbar_expect_tx(full + 8 * i, 2 * TILE);
                STAMPIF(i == 32 || i == 33, 16 + (i & 1));
                src += 2 * TILE;
                slot = slot == NST - 1 ? 0 : slot + 1;
                hpar ^= slot == 32 % NST;
            }
        } else if (warp == 14) {
            prefetch_map(&mPB);
            auto pf_c = [&](int k) { prefetch_slice(&mPC, 4 * (k >> 1), cta * 8 + (k & 1) * 4); };
            named_bar(0, 480);
            asm volatile("bar.arrive 1, 64;" ::: "memory");
#pragma unroll 1
            for (int k = TN(PF0) ? 0 : 1; k < 4; k++) {
                sleep_until(cstart + (k == 0 ? TN(PF0) : k == 1 ? TN(PF1) : k == 2 ? TN(PF2) : TN(PF3)));
                if (elect_one()) prefetch_slice(&mPB, 4 * k, cta * 4);
            }
#pragma unroll 1
            for (int k = 0; k < 4; k++) {
                behind(TN(PB_E0) + TN(PB_STEP) * k);
                if (elect_one()) prefetch_slice(&mPB, 4 * k, 512 + cta * 4);
            }
#pragma unroll 1
            for (int k = 0; k < TN(PC_N); k++) {
                behind(min(TN(PC_E0) + TN(PC_STEP) * k / 2, 25));
                if (elect_one()) pf_c(k);
            }
            int pk = TN(PC_N), pe = TN(PC_E1);
            auto own_part = [&](int e) {
                if (!(TDBG & 16) && !mbar_test(bar_out + 8 * e, 0)) {
                    mbar_wait(bar_out + 8 * e);
                    sleep_until(clk32() + TN(T_OWN));
                    STAMP(11);
                }
            };
            const char* src = reinterpret_cast<const char*>(prm.s->h) + (size_t)chunk * 524288;
            uint32_t slot = 32 % NST;
#pragma unroll 1
            for (int i = 32; i < NBIG; i++) {
                if (!(i & 3)) own_part((i - 32) >> 2);
                mbar_wait(empty + 8 * (i - NST));
                PSTAMP(i);
                if (elect_one()) {
                    mbar_expect_tx(hfull + 8 * slot, 2 * TILE);
                    bulk_load(sb + slot * SLOT, src, 2 * TILE, hfull + 8 * slot);
                    tma5(sb + slot * SLOT + 2 * TILE, (i & 4) ? &mCim : &mCre, c_col(i), dt * 8, full + 8 * i);
                }
                if (i == pe && pk < 8) {
                    if (elect_one()) pf_c(pk);
                    pk++; pe += TN(PC_S1);
                }
                src += 2 * TILE;
                slot = slot == NST - 1 ? 0 : slot + 1;
            }
            src -= (NBIG - 32) * 2 * TILE;
#pragma unroll
            for (int k = 0; k < 2 * NSPL - 2; k++) {
                if (k == 0 || k == 2) own_part(6 + k / 2);
                mbar_wait(empty + 8 * (NBIG - NST + k));
                if (k >= 1 && k <= 4) {
                    if (elect_one()) {
#pragma unroll
                        for (int j = 2 * k - 2; j < 2 * k; j++)
                            tma5(sb + tail_c(j), ((NBIG + j) & 4) ? &mCim : &mCre, c_col(NBIG + j), dt * 8, full + 8 * (NBIG + j));
                    }
                }
                if (k == 4) continue;
                if (k == 2) mbar_wait(bar_dfree + 8);
                if (elect_one()) {
#pragma unroll
                    for (int n = k < 5 ? 2 * k : k + 2; n < (k < 3 ? 2 * k + 2 : k == 3 ? 7 : k + 3); n++) {
                        mbar_expect_tx(hfull + 8 * (NST + n % 7), TILE);
                        bulk_load(sb + tail_h(n), src + tail_src(n), TILE, hfull + 8 * (NST + n % 7));
                    }
                }
            }
        } else {
            if (elect_one()) {
#pragma unroll
                for (int i = 0; i < NST; i++) mbar_init(full + 8 * i, 1);
                fence_mbar_init();
            }
            __syncwarp();
            asm volatile("bar.arrive 5, 160;" ::: "memory");
#pragma unroll 1
            for (int i = 0; i < NST; i++) {
                if (elect_one()) {
                    mbar_expect_tx(full + 8 * i, SLOT);
                    tma5b(sb + i * SLOT, &mB, i * 64, dt * 4, full + 8 * i);
                    tma4(sb + i * SLOT + 2 * TILE, &mX, i * 64, chunk * 64, full + 8 * i);
                }
                STAMPIF(i == 0, 1);
            }
            STAMP(2);
            asm volatile("bar.arrive 0, 480;" ::: "memory");
            named_bar(6, 160);
            uint32_t dst = sb;
#pragma unroll 1
            for (int i = NST; i < 32; i++) {
                if (i == 2 * NST) mbar_wait(bar_base);
                if (lane == 0) mbar_expect_tx(full + 8 * i, SLOT);
                mbar_wait(empty + 8 * (i - NST));
                PSTAMP(i);
                if (elect_one()) {
                    tma5b(dst, &mB, (i & 15) * 64, (i >> 4) * 64 + dt * 4, full + 8 * i);
                    tma4(dst + 2 * TILE, &mX, (i & 15) * 64, chunk * 64, full + 8 * i);
                }
                dst = dst == sb + (NST - 1) * SLOT ? sb : dst + SLOT;
            }
        }
    }
}

typedef CUresult (*EncodeFn)(CUtensorMap*, CUtensorMapDataType, cuuint32_t, void*, const cuuint64_t*, const cuuint64_t*, const cuuint32_t*,
                             const cuuint32_t*, CUtensorMapInterleave, CUtensorMapSwizzle, CUtensorMapL2promotion, CUtensorMapFloatOOBfill);

bool encode(EncodeFn fn, CUtensorMap* m, const void* ptr, int rank, const cuuint64_t* dims, const cuuint64_t* strides, const cuuint32_t* box,
            CUtensorMapL2promotion promo = CU_TENSOR_MAP_L2_PROMOTION_NONE) {
    const cuuint32_t es[5] = {1, 1, 1, 1, 1};
    return fn(m, CU_TENSOR_MAP_DATA_TYPE_BFLOAT16, rank, const_cast<void*>(ptr), dims, strides, box, es, CU_TENSOR_MAP_INTERLEAVE_NONE,
              CU_TENSOR_MAP_SWIZZLE_128B, promo, CU_TENSOR_MAP_FLOAT_OOB_FILL_NONE) == CUDA_SUCCESS;
}

}

extern "C" void kernel_launch(void* const* d_in, const int* in_sizes, int n_in, void* d_out, int out_size) {
    (void)in_sizes; (void)n_in; (void)out_size;
    Params prm;
    prm.x = (const __nv_bfloat16*)d_in[0];
    prm.lam_re = (const __nv_bfloat16*)d_in[1];
    prm.lam_im = (const __nv_bfloat16*)d_in[2];
    prm.b_re = (const __nv_bfloat16*)d_in[3];
    prm.b_im = (const __nv_bfloat16*)d_in[4];
    prm.c_re = (const __nv_bfloat16*)d_in[5];
    prm.c_im = (const __nv_bfloat16*)d_in[6];
    prm.log_dt = (const __nv_bfloat16*)d_in[7];
    prm.dskip = (const __nv_bfloat16*)d_in[8];
    prm.w_r = (const __nv_bfloat16*)d_in[10];
    prm.gate_w = (const __nv_bfloat16*)d_in[14];
    prm.out = (float*)d_out;
    cudaGetSymbolAddress((void**)&prm.s, g_scratch);
    prm.swapped = prm.b_im < prm.b_re;

    void* fnp = nullptr;
    cudaDriverEntryPointQueryResult qr;
    cudaGetDriverEntryPoint("cuTensorMapEncodeTiled", &fnp, cudaEnableDefault, &qr);
    EncodeFn fn = (EncodeFn)fnp;
    cudaFuncSetAttribute(fused_kernel, cudaFuncAttributeMaxDynamicSharedMemorySize, SMEM_BYTES);

    CUtensorMap mX, mB, mCre, mCim, mWg, mWu, mWd, mXr, mPB, mPC, mXe;
    const cuuint64_t row = 2048;
    {
        const cuuint64_t dims[4] = {1024, 2, 4, 976}, st[3] = {row, 32 * row, 2 * row};
        const cuuint32_t box[4] = {64, 2, 4, 16};
        encode(fn, &mX, prm.x, 4, dims, st, box, PROMO);
    }
    {
        const char *lo = (const char*)(prm.swapped ? prm.b_im : prm.b_re), *hi = (const char*)(prm.swapped ? prm.b_re : prm.b_im);
        const cuuint64_t dims[5] = {1024, 8, 2, 96, 2}, st[4] = {row, (cuuint64_t)(hi - lo), 8 * row, 256 * row};
        const cuuint32_t box[5] = {64, 8, 2, 4, 2};
        encode(fn, &mB, lo, 5, dims, st, box, PROMO);
    }
    {
        const cuuint64_t dims[5] = {1024, 2, 4, 2, 64}, st[4] = {row, 4 * row, 2 * row, 16 * row};
        const cuuint32_t box[5] = {64, 2, 4, 2, 8};
        encode(fn, &mCre, prm.c_re, 5, dims, st, box);
        encode(fn, &mCim, prm.c_im, 5, dims, st, box);
    }
    {
        const cuuint64_t dims[2] = {F_, D_}, st[1] = {F_ * 2}, dimsd[2] = {D_, F_}, std_[1] = {row};
        const cuuint32_t box[2] = {64, 64};
        encode(fn, &mWg, d_in[11], 2, dims, st, box);
        encode(fn, &mWu, d_in[12], 2, dims, st, box);
        encode(fn, &mWd, d_in[13], 2, dimsd, std_, box);
    }
    for (int i = 0; i < 2; i++) {
        const char *p = (const char*)(i ? prm.c_re : prm.b_re), *q = (const char*)(i ? prm.c_im : prm.b_im);
        const cuuint64_t dims[4] = {64, 16, 1024, 2}, st[3] = {128, row, (cuuint64_t)(p < q ? q - p : p - q)};
        const cuuint32_t box[4] = {16, 4, 4, 2};
        encode(fn, i ? &mPC : &mPB, p < q ? p : q, 4, dims, st, box, CU_TENSOR_MAP_L2_PROMOTION_L2_128B);
    }
    {
        const cuuint64_t dims[3] = {D_ - 192, S_, 4}, st[2] = {row, 128};
        const cuuint32_t box[3] = {64, 16, 4};
        encode(fn, &mXr, prm.x, 3, dims, st, box);
    }
    {
        const cuuint64_t dims[5] = {1024, 2, 4, 4, S_ / 32}, st[4] = {4 * row, row, 8 * row, 32 * row};
        const cuuint32_t box[5] = {64, 2, 4, 2, 4};
        encode(fn, &mXe, prm.x, 5, dims, st, box);
    }
    for (int j = 0, e4 = 4 * TN(GC0); j < 23; j++) {
        prm.fetch[j] = j < NFT ? TN(GU_E0) + j * TN(W_NUM) / 4 : j < 16 ? 0 : TN(DL0) + (j - 16) * TN(DLS) / 4;
        prm.use[j] = j < 16 ? e4 / 4 : TN(DC0) + (j - 16) * TN(DCS) / 4;
        const int last = NBIG - 2;
        if (prm.fetch[j] > last) prm.fetch[j] = last;
        if (prm.use[j] > last) prm.use[j] = last;
        e4 += j < TN(N1) ? TN(GCS) : j < TN(N2) ? TN(GCS2) : j < 10 ? TN(GCS3) : TN(GCS4);
    }
    fused_kernel<<<NCTA, 512, SMEM_BYTES, cudaStreamPerThread>>>(prm, mX, mB, mCre, mCim, mWg, mWu, mWd, mXr, mPB, mPC, mXe);
}
```

```cpp
#include <cuda_runtime.h>
#include <cuda_bf16.h>
#include <cuda.h>
#include <stdint.h>

namespace {

constexpr int S_ = 2048, D_ = 1024, F_ = 3584;
constexpr int NCTA = 128;
constexpr int NSPL = 9, NBIG = 64 - NSPL, NENT = NBIG + 2 * NSPL;
constexpr int NST = 5;
constexpr int NFT = 5;
constexpr uint32_t SLOT = 32768, TILE = 8192;
constexpr uint32_t OFF_FT = NST * SLOT;
constexpr uint32_t OFF_XS = OFF_FT + NFT * TILE;
constexpr uint32_t OFF_LIST = OFF_XS + 8192;
constexpr uint32_t OFF_RED = OFF_XS + 4096;
constexpr uint32_t OFF_CONST = OFF_XS + 16384;
constexpr uint32_t OFF_M = OFF_CONST + 8192;
constexpr uint32_t OFF_HID = OFF_CONST;
constexpr uint32_t OFF_G = OFF_M + 512;
constexpr uint32_t OFF_DK = OFF_G + 256;
constexpr uint32_t OFF_FULL = OFF_DK + 256;
constexpr uint32_t OFF_EMPTY = OFF_FULL + 103 * 8;
constexpr uint32_t OFF_KEYS = OFF_EMPTY + 87 * 8;
constexpr uint32_t OFF_SEL = OFF_KEYS + 32;
constexpr uint32_t OFF_EPOCH = OFF_SEL + 32;
constexpr uint32_t OFF_PROF = OFF_EPOCH + 16;
constexpr uint32_t SMEM_BYTES = OFF_PROF + 432;
static_assert(SMEM_BYTES <= 232448, "smem");

static_assert(NBIG % NST == 0, "tail layout");
__host__ __device__ constexpr uint32_t tail_c(int j) { return j < 8 ? SLOT + j * 2 * TILE : OFF_FT + 5 * TILE; }
__host__ __device__ constexpr uint32_t tail_h(int n) { return n % 7 < 4 ? n % 7 * TILE : OFF_FT + (n % 7 - 2) * TILE; }
__host__ __device__ constexpr uint32_t tail_src(int n) { return (n % NSPL + NBIG - 32) * 2 * TILE + n / NSPL * TILE; }
__host__ __device__ constexpr int c_col(int i) { return ((i & 3) + ((i >> 1) & 12)) * 64; }

constexpr uint32_t SPIN_LIMIT = 1u << 18;

struct Scratch {
    uint2 carry[16 * 1024];
    uint2 hid[NCTA * 128];
    uint32_t y[8 * 8 * D_];
    uint32_t key[NCTA * 8];
    uint32_t gate[S_];
    uint2 armed[NCTA * 4];
    unsigned int epoch[256];
    uint4 start[32 * 2];
    uint4 h[16 * 32 * 1024];
};
__device__ __align__(1024) Scratch g_scratch;
#define STAMPW_(cond, w) do {} while (0)
#define GSTAMP(cond, w) do {} while (0)
#define LSTAMP(cond, w) STAMPW_(cond, w)
#define LT 0
#define STAMPW(cond, w) STAMPW_(cond, w)
#define STAMPIF(cond, i) STAMPW(cond, 96 + (i))
#define STAMP(i) STAMPW(1, 96 + (i))
#define KSTAMP(i) STAMPW((threadIdx.x & 127) == 0, i)
#define PSTAMP(i) STAMPW((i) < 56 && (i) >= 32, 160 + (i))

struct Params {
    const __nv_bfloat16 *x, *b_re, *b_im, *lam_re, *lam_im, *c_re, *c_im, *log_dt, *dskip, *w_r, *gate_w;
    float* out;
    Scratch* s;
    int swapped;
};

__device__ __forceinline__ uint32_t smem_u32(const void* p) { return (uint32_t)__cvta_generic_to_shared(p); }
__device__ __forceinline__ void mbar_init(uint32_t bar, uint32_t cnt) { asm volatile("mbarrier.init.shared::cta.b64 [%0], %1;" ::"r"(bar), "r"(cnt) : "memory"); }
__device__ __forceinline__ void mbar_expect_tx(uint32_t bar, uint32_t bytes) { asm volatile("mbarrier.arrive.expect_tx.shared::cta.b64 _, [%0], %1;" ::"r"(bar), "r"(bytes) : "memory"); }
__device__ __forceinline__ void mbar_arrive(uint32_t bar) { asm volatile("mbarrier.arrive.shared::cta.b64 _, [%0];" ::"r"(bar) : "memory"); }
__device__ __forceinline__ bool mbar_test(uint32_t bar, uint32_t parity) {
    uint32_t ok;
    asm volatile("{ .reg .pred p; mbarrier.test_wait.parity.shared::cta.b64 p, [%1], %2; selp.u32 %0, 1, 0, p; }" : "=r"(ok) : "r"(bar), "r"(parity) : "memory");
    return __all_sync(0xffffffffu, ok);
}
__device__ __forceinline__ void mbar_wait(uint32_t bar, uint32_t parity = 0) {
    asm volatile("{ .reg .pred p; .reg .u32 n; mov.u32 n, 0;\nW%=: mbarrier.try_wait.parity.shared::cta.b64 p, [%0], %1; @p bra D%=;\n"
                 "add.u32 n, n, 0x4000; setp.ne.u32 p, n, 0; @p bra W%=; trap;\nD%=: }" ::"r"(bar), "r"(parity) : "memory");
}
__device__ __forceinline__ bool elect_one() {
    uint32_t pred;
    asm volatile("{ .reg .pred P; elect.sync _|P, 0xffffffff; selp.b32 %0, 1, 0, P; }" : "=r"(pred));
    return pred;
}
__device__ __forceinline__ void named_bar(int id, int n) { asm volatile("bar.sync %0, %1;" ::"r"(id), "r"(n) : "memory"); }
__device__ __forceinline__ void fence_mbar_init() { asm volatile("fence.mbarrier_init.release.cluster;" ::: "memory"); }
__device__ __forceinline__ void fence_async_smem() { asm volatile("fence.proxy.async.shared::cta;" ::: "memory"); }

__device__ __forceinline__ void bulk_load(uint32_t dst, const void* src, uint32_t bytes, uint32_t bar) {
    asm volatile("cp.async.bulk.shared::cluster.global.mbarrier::complete_tx::bytes [%0], [%1], %2, [%3];" ::"r"(dst), "l"(src), "r"(bytes), "r"(bar) : "memory");
}
__device__ __forceinline__ void cp_async16(uint32_t dst, const void* src) { asm volatile("cp.async.cg.shared.global [%0], [%1], 16;" ::"r"(dst), "l"(src) : "memory"); }
__device__ __forceinline__ void sts128(uint32_t a, uint32_t x, uint32_t y, uint32_t z, uint32_t w) {
    asm volatile("st.shared.v4.u32 [%0], {%1,%2,%3,%4};" ::"r"(a), "r"(x), "r"(y), "r"(z), "r"(w) : "memory");
}
__device__ __forceinline__ uint2 lds64(uint32_t a) {
    uint2 v;
    asm volatile("ld.shared.v2.u32 {%0,%1}, [%2];" : "=r"(v.x), "=r"(v.y) : "r"(a) : "memory");
    return v;
}
__device__ __forceinline__ uint32_t lds32(uint32_t a) {
    uint32_t v;
    asm volatile("ld.volatile.shared.u32 %0, [%1];" : "=r"(v) : "r"(a) : "memory");
    return v;
}
__device__ __forceinline__ void stg128(void* p, uint32_t x, uint32_t y, uint32_t z, uint32_t w) {
    asm volatile("st.global.v4.u32 [%0], {%1,%2,%3,%4};" ::"l"(p), "r"(x), "r"(y), "r"(z), "r"(w) : "memory");
}
__device__ __forceinline__ void st_relaxed(void* p, uint32_t x) { asm volatile("st.relaxed.gpu.global.b32 [%0], %1;" ::"l"(p), "r"(x) : "memory"); }
__device__ __forceinline__ void st_relaxed2(void* p, uint32_t x, uint32_t y) { asm volatile("st.relaxed.gpu.global.v2.b32 [%0], {%1, %2};" ::"l"(p), "r"(x), "r"(y) : "memory"); }
__device__ __forceinline__ void st_relaxed4(void* p, uint32_t x, uint32_t y, uint32_t z, uint32_t w) {
    asm volatile("st.relaxed.gpu.global.v4.b32 [%0], {%1, %2, %3, %4};" ::"l"(p), "r"(x), "r"(y), "r"(z), "r"(w) : "memory");
}
__device__ __forceinline__ uint32_t ld_relaxed(const void* p) {
    uint32_t v;
    asm volatile("ld.relaxed.gpu.global.b32 %0, [%1];" : "=r"(v) : "l"(p) : "memory");
    return v;
}
__device__ __forceinline__ uint2 ld_relaxed2(const void* p) {
    uint2 v;
    asm volatile("ld.relaxed.gpu.global.v2.b32 {%0, %1}, [%2];" : "=r"(v.x), "=r"(v.y) : "l"(p) : "memory");
    return v;
}
__device__ __forceinline__ uint4 ld_relaxed4(const void* p) {
    uint4 v;
    asm volatile("ld.relaxed.gpu.global.v4.b32 {%0, %1, %2, %3}, [%4];" : "=r"(v.x), "=r"(v.y), "=r"(v.z), "=r"(v.w) : "l"(p) : "memory");
    return v;
}
__device__ __forceinline__ uint32_t clk32() { uint32_t c; asm volatile("mov.u32 %0, %%clock;" : "=r"(c)); return c; }
__device__ __forceinline__ uint32_t gtime32() { uint32_t c; asm volatile("mov.u32 %0, %%globaltimer_lo;" : "=r"(c)); return c; }
__device__ __forceinline__ void sched_fence(uint32_t t) { while ((int)(clk32() - t) < 0) {} }
__device__ __forceinline__ void sleep_until(uint32_t t) { while ((int)(clk32() - t) < 0) __nanosleep(40); }

__device__ __forceinline__ void tma2(uint32_t dst, const CUtensorMap* m, int c0, int c1, uint32_t bar) {
    asm volatile("{ .reg .b64 pol; createpolicy.fractional.L2::evict_first.b64 pol;\n"
                 "cp.async.bulk.tensor.2d.shared::cluster.global.mbarrier::complete_tx::bytes.L2::cache_hint [%0], [%1, {%3, %4}], [%2], pol; }"
                 ::"r"(dst), "l"(m), "r"(bar), "r"(c0), "r"(c1) : "memory");
}
__device__ __forceinline__ void tma3(uint32_t dst, const CUtensorMap* m, int c0, int c1, uint32_t bar) {
    asm volatile("cp.async.bulk.tensor.3d.shared::cluster.global.mbarrier::complete_tx::bytes [%0], [%1, {%3, %4, %5}], [%2];"
                 ::"r"(dst), "l"(m), "r"(bar), "r"(c0), "r"(c1), "r"(0) : "memory");
}
__device__ __forceinline__ void tma4(uint32_t dst, const CUtensorMap* m, int c0, int c3, uint32_t bar) {
    asm volatile("cp.async.bulk.tensor.4d.shared::cluster.global.mbarrier::complete_tx::bytes [%0], [%1, {%3, %5, %5, %4}], [%2];"
                 ::"r"(dst), "l"(m), "r"(bar), "r"(c0), "r"(c3), "r"(0) : "memory");
}
__device__ __forceinline__ void tma5(uint32_t dst, const CUtensorMap* m, int c0, int c4, uint32_t bar) {
    asm volatile("cp.async.bulk.tensor.5d.shared::cluster.global.mbarrier::complete_tx::bytes [%0], [%1, {%3, %5, %5, %5, %4}], [%2];"
                 ::"r"(dst), "l"(m), "r"(bar), "r"(c0), "r"(c4), "r"(0) : "memory");
}
__device__ __forceinline__ void tma5b(uint32_t dst, const CUtensorMap* m, int c0, int c3, uint32_t bar) {
    asm volatile("cp.async.bulk.tensor.5d.shared::cluster.global.mbarrier::complete_tx::bytes [%0], [%1, {%3, %5, %5, %4, %5}], [%2];"
                 ::"r"(dst), "l"(m), "r"(bar), "r"(c0), "r"(c3), "r"(0) : "memory");
}
__device__ __forceinline__ void prefetch_l2(const void* p) { asm volatile("prefetch.global.L2 [%0];" ::"l"(p)); }
__device__ __forceinline__ void prefetch_slice(const CUtensorMap* m, int line, int row) {
    asm volatile("cp.async.bulk.prefetch.tensor.4d.L2.global [%0, {%3, %1, %2, %3}];" ::"l"(m), "r"(line), "r"(row), "r"(0) : "memory");
}
__device__ __forceinline__ void prefetch_map(const CUtensorMap* m) { asm volatile("prefetch.tensormap [%0];" ::"l"(m)); }
__device__ __forceinline__ uint32_t uni(uint32_t v) { return __shfl_sync(0xffffffffu, v, 0); }

__device__ __forceinline__ uint32_t make_desc(uint32_t addr) { return ((addr & 0x3FFFF) >> 4) | (1u << 16); }
__device__ __forceinline__ uint32_t make_desc_h(uint32_t addr) { return ((addr & 0x3FFFF) >> 4) | (32u << 16); }
template <int H> __device__ __forceinline__ uint64_t desc64(uint32_t lo) {
    uint64_t d;
    asm volatile("mov.b64 %0, {%1, %2};" : "=l"(d) : "r"(lo), "n"(64u | ((H ? 2u : 1u) << 30)));
    return d;
}
__device__ __forceinline__ void wgmma_fence() { asm volatile("wgmma.fence.sync.aligned;" ::: "memory"); }
__device__ __forceinline__ void wgmma_commit() { asm volatile("wgmma.commit_group.sync.aligned;" ::: "memory"); }
template <int N> __device__ __forceinline__ void wgmma_wait() { asm volatile("wgmma.wait_group.sync.aligned %0;" ::"n"(N) : "memory"); }

#define R8(d, i) "+f"(d[i]), "+f"(d[i + 1]), "+f"(d[i + 2]), "+f"(d[i + 3]), "+f"(d[i + 4]), "+f"(d[i + 5]), "+f"(d[i + 6]), "+f"(d[i + 7])
#define R64(d) R8(d, 0), R8(d, 8), R8(d, 16), R8(d, 24), R8(d, 32), R8(d, 40), R8(d, 48), R8(d, 56)
template <int TA>
__device__ __forceinline__ void wgmma_n128(float (&d)[64], uint64_t da, uint64_t db, int scale_d = 1) {
    asm volatile("{ .reg .pred p; setp.ne.b32 p, %66, 0;\n"
                 "wgmma.mma_async.sync.aligned.m64n128k16.f32.bf16.bf16 "
                 "{%0,%1,%2,%3,%4,%5,%6,%7,%8,%9,%10,%11,%12,%13,%14,%15,%16,%17,%18,%19,%20,%21,%22,%23,%24,%25,%26,%27,%28,%29,%30,%31,"
                 "%32,%33,%34,%35,%36,%37,%38,%39,%40,%41,%42,%43,%44,%45,%46,%47,%48,%49,%50,%51,%52,%53,%54,%55,%56,%57,%58,%59,%60,%61,%62,%63}, "
                 "%64, %65, p, 1, 1, %67, 0; }"
                 : R64(d)
                 : "l"(da), "l"(db), "r"(scale_d), "n"(TA));
}
__device__ __forceinline__ void pin4(float (&d)[4]) { asm volatile("" : "+f"(d[0]), "+f"(d[1]), "+f"(d[2]), "+f"(d[3])::"memory"); }
__device__ __forceinline__ void pin64(float (&d)[64]) { asm volatile("" : R64(d)::"memory"); }

template <int TA>
__device__ __forceinline__ void wgmma_n8(float (&d)[4], uint64_t da, uint64_t db, int scale_d = 1) {
    asm volatile("{ .reg .pred p; setp.ne.b32 p, %7, 0;\n"
                 "wgmma.mma_async.sync.aligned.m64n8k16.f32.bf16.bf16 {%0,%1,%2,%3}, %4, %5, p, 1, 1, %6, 0; }"
                 : "+f"(d[0]), "+f"(d[1]), "+f"(d[2]), "+f"(d[3])
                 : "l"(da), "l"(db), "n"(TA), "r"(scale_d));
}

__device__ __forceinline__ float bf_lo(uint32_t u) { return __uint_as_float(u << 16); }
__device__ __forceinline__ float bf_hi(uint32_t u) { return __uint_as_float(u & 0xFFFF0000u); }
__device__ __forceinline__ float rbf(float v) { return __bfloat162float(__float2bfloat16_rn(v)); }
__device__ __forceinline__ uint32_t pack_bf(float lo, float hi) {
    uint32_t r;
    asm("cvt.rn.bf16x2.f32 %0, %1, %2;" : "=r"(r) : "f"(hi), "f"(lo));
    return r;
}
__device__ __forceinline__ uint32_t mul_bf2(uint32_t a, uint32_t b) {
    uint32_t r;
    asm("mul.rn.bf16x2 %0, %1, %2;" : "=r"(r) : "r"(a), "r"(b));
    return r;
}
__device__ __forceinline__ uint32_t fma_bf2(uint32_t a, uint32_t b, uint32_t c) {
    uint32_t r;
    asm("fma.rn.bf16x2 %0, %1, %2, %3;" : "=r"(r) : "r"(a), "r"(b), "r"(c));
    return r;
}
__device__ __forceinline__ float2 cmul(float2 a, float2 b) { return make_float2(a.x * b.x - a.y * b.y, a.x * b.y + a.y * b.x); }
__device__ __forceinline__ float2 cfma(float2 a, float2 b, float2 c) {
    return make_float2(fmaf(a.x, b.x, fmaf(-a.y, b.y, c.x)), fmaf(a.x, b.y, fmaf(a.y, b.x, c.y)));
}
__device__ __forceinline__ float sigmoidf_(float v) { return __fdividef(1.0f, 1.0f + expf(-v)); }

#define SCHED_NAMES T_W0, T_INIT, T_SMALL, T_W3, PF0, PF1, RT0, RT1, RT2, RT3, T_BASE, G_NS, GT0, GT1, G0, T_CP0, T_CP1, GAP0, GAP1, T_OWN, \
    T_RETRY, T_Y, T_X0, RS_E, PB_E0, PB_STEP, PC_E0, PC_STEP, PC_N, PC_E1, PC_S1, GU_E0, W_NUM, GC0, GCS, GCS4, HG, DL0, DLS, DN_E0
enum { SCHED_NAMES, NTUNE };
constexpr int sched_default[NTUNE] = {
    600, 1000, 1000, 1000,
    1100, 400,
    2200, 2700, 3200, 3700,
    2500, 7,
    6200, 7200,
    800, 900, 900,
    300, 300,
    1100, 200, 700, 200,
    4,
    4, 1, 9, 4, 5, 50, 3,
    4, 8, 14, 7, 5,
    43, 37, 8, 48};
template <int I> struct Sched { static constexpr int v = sched_default[I]; };
#define TN(i) (Sched<i>::v)
#define DBG 0
#define TDBG 0
#define X0 1
#define GE 8
#define PROMO CU_TENSOR_MAP_L2_PROMOTION_L2_256B

template <int TA, class H>
__device__ __forceinline__ void run_entry(uint32_t lo32, uint32_t prev, int accumulate, float (&accA)[64], float (&accB)[64], H inside) {
    const uint64_t da = desc64<TA>(lo32), db = TA ? desc64<0>(lo32 + (2 * TILE >> 4) - (31u << 16)) : da + (2 * TILE >> 4);
    wgmma_fence();
#pragma unroll
    for (int kk = 0; kk < 4; kk++) {
        wgmma_n128<TA>(accA, da + kk * (TA ? 128 : 2), db + kk * 2, kk > 0 ? 1 : accumulate);
        wgmma_n128<TA>(accB, da + 512 + kk * (TA ? 128 : 2), db + kk * 2, kk > 0 ? 1 : accumulate);
        if (kk == 1) {
            wgmma_commit();
            wgmma_wait<1>();
            if ((threadIdx.x & 31) == 0) mbar_arrive(prev);
            inside();
        }
    }
    wgmma_commit();
}
template <int TA, class H>
__device__ __forceinline__ void run_entries(uint32_t sb, int lo, int hi, int slot, float (&accA)[64], float (&accB)[64], H after) {
    const uint32_t da0 = TA ? make_desc_h(sb) : make_desc(sb), dlast = da0 + (NST - 1) * (SLOT >> 4);
    uint32_t prev = sb + OFF_FULL + 8 * 101, bar = sb + OFF_FULL + 8 * lo, lo32 = da0 + slot * (SLOT >> 4);
    int accumulate = 0;
#pragma unroll 1
    for (int i = lo; i < hi; i++) {
        mbar_wait(bar);
        KSTAMP(i);
        run_entry<TA>(lo32, prev, accumulate, accA, accB, []() {});
        prev = bar + (OFF_EMPTY - OFF_FULL);
        bar += 8;
        lo32 = lo32 == dlast ? da0 : lo32 + (SLOT >> 4);
        accumulate = 1;
        after(i);
    }
}

template <int TA>
__device__ __forceinline__ void small_tile(float (&acc)[4], uint32_t alo, uint32_t blo, bool first) {
    const uint64_t da = desc64<0>(alo), db = desc64<0>(blo);
#pragma unroll
    for (int kk = 0; kk < 4; kk++) wgmma_n8<TA>(acc, da + kk * (TA ? 128 : 2), db + kk * 2, kk > 0 || !first);
}

template <int N>
__device__ __forceinline__ uint32_t check_tile(uint32_t sb, uint32_t dst, uint32_t probe, const char* src, uint32_t par, uint32_t bar, uint32_t phase, uint32_t pause) {
    if (TDBG & 4) return phase;
#pragma unroll 1
    for (uint32_t it = 0; it < SPIN_LIMIT; it++) {
        uint32_t v[N], bad = 0;
#pragma unroll
        for (int u = 0; u < N; u++) v[u] = lds32(dst + probe + (u >> 1) * 2048 + (u & 1) * 256);
#pragma unroll
        for (int u = 0; u < N; u += 4)
            asm("{ .reg .b32 a, b; lop3.b32 a, %1, %2, %5, 0x7E; lop3.b32 b, %3, %4, %5, 0x7E; lop3.b32 %0, %0, a, b, 0xFE; }"
                : "+r"(bad) : "r"(v[u]), "r"(v[u + 1]), "r"(v[u + 2]), "r"(v[u + 3]), "r"(par));
        if (!__any_sync(0xffffffffu, bad & 1u)) return phase;
        STAMP(10);
        __nanosleep(pause);
        if (elect_one()) {
            mbar_expect_tx(bar, N * 1024);
            bulk_load(dst, src, N * 1024, bar);
        }
        mbar_wait(bar, phase);
        phase ^= 1;
    }
    __trap();
    return 0;
}

__global__ void __launch_bounds__(512, 1)
fused_kernel(const __grid_constant__ Params prm, const __grid_constant__ CUtensorMap mX, const __grid_constant__ CUtensorMap mB, const __grid_constant__ CUtensorMap mCre,
             const __grid_constant__ CUtensorMap mCim, const __grid_constant__ CUtensorMap mWg, const __grid_constant__ CUtensorMap mWu,
             const __grid_constant__ CUtensorMap mWd, const __grid_constant__ CUtensorMap mXr, const __grid_constant__ CUtensorMap mPB,
             const __grid_constant__ CUtensorMap mPC, const __grid_constant__ CUtensorMap mXe) {
    {
        const uint32_t t = threadIdx.x, b = blockIdx.x;
        const uint32_t row = t < 32 ? ((b & 60) * 2 + (b >> 6) * 4 + (b & 3)) * 16 + (t >> 1) : b * 4 + ((t >> 1) & 3);
        const char* base = (const char*)(t < 32 ? prm.x : t < 40 ? prm.b_re : prm.b_im);
        asm volatile("{ .reg .pred p; setp.lt.u32 p, %1, 48; @p prefetch.global.L2 [%0]; }" ::"l"(base + (row * 2048 + (t & 1) * 128)), "r"(t) : "memory");
    }
    extern __shared__ __align__(1024) uint8_t smem[];
    uint32_t sb;
    asm volatile("mov.u32 %0, %1;" : "=r"(sb) : "r"(smem_u32(smem)));
    const int tid = threadIdx.x, warp = __shfl_sync(0xffffffffu, tid >> 5, 0), lane = tid & 31;
    const int cta = blockIdx.x;
    const uint32_t cstart = clk32();
    const int chunk = (cta >> 2) & 15;
    const int dt = (cta >> 6) * 4 + (cta & 3);
    const int rid = chunk * 8 + dt;
    const int kslot = (rid & 3) * 32 + (rid >> 2);
    const bool has_gu = cta < 112;
    const uint32_t full = sb + OFF_FULL, empty = sb + OFF_EMPTY;
    const uint32_t bar_epoch = full + 8 * 73, dfull = full + 8 * 74, bar_retry = full + 8 * 81, bar_x = full + 8 * 82, ffull = full + 8 * 84,
                   hfull = full + 8 * 89, bar_base = full + 8 * 102;
    const uint32_t fempty = empty + 8 * 66, bar_order = empty + 8 * 71, bar_stored = empty + 8 * 73, bar_dfree = empty + 8 * 74,
                   bar_out = empty + 8 * 77, bar_g = empty + 8 * 85, bar_const = empty + 8 * 86;
    const int w = warp & 3, g = lane >> 2, c = lane & 3, at = tid & 127;

    const uint32_t probe = (lane >> 3) * 32 + (g & 1) * 144 + (c & 1) * 520 + (c >> 1) * 1028;

    LSTAMP(tid == 0, 96);
    GSTAMP(tid == 0, 94);
    auto init_barriers = [&](uint32_t base, uint32_t cnt, auto n) {
        if (elect_one()) {
#pragma unroll
            for (int i = 0; i < n(); i++) mbar_init(base + 8 * i, cnt);
            fence_mbar_init();
        }
        __syncwarp();
    };
    if (warp != 12) {
        if (warp == 15 && !(cta & 3) && lane < 8) st_relaxed((uint32_t*)&prm.s->start[cta >> 1] + lane, (lane & 1) ? gtime32() : cstart);
        if (warp < 12) sleep_until(cstart + (warp < 4 ? TN(T_W0) : TN(T_INIT)));
    }
    if (warp < 8) {
        if (warp < 4) init_barriers(warp == 0 ? full + 40 : warp == 3 ? full + 8 * 98 : empty + 40 * (warp - 1), (warp + 1) & 2 ? 4 : 1, []() { return 5; });
        else init_barriers(full + 80 + 176 * w, 1, []() { return 22; });
        asm volatile("setmaxnreg.inc.sync.aligned.u32 192;");
        if (warp < 4) {
            named_bar(5, 160);
            asm volatile("bar.arrive 0, 448;" ::: "memory");
            asm volatile("bar.arrive 6, 160;" ::: "memory");
            asm volatile("bar.arrive 7, 160;" ::: "memory");
        } else named_bar(0, 448);
        const int wg = warp >> 2;
        const int p = wg * 512 + dt * 32 + w * 8 + g;
        uint32_t cp = sb + OFF_CONST + 8 * (wg * 64 + w * 8 + g), cw = cp + 1024 * c, cm = sb + OFF_M + 4 * (wg * 64 + w * 8 + g);
        const int j1 = chunk - 1 - c;
        uint2* cq = &prm.s->carry[j1 * 1024 + p];
        char* hd = reinterpret_cast<char*>(prm.s->h) + (size_t)chunk * 524288 + wg * 262144 + (dt >> 1) * 16384 + ((dt & 1) * 4 + w) * 1024 + g * 64 + ((c ^ (g >> 1)) << 4);
        const bool never = uni(cstart == 0 && sb == 0);
        asm volatile("" : "+l"(cq), "+l"(hd), "+r"(cp), "+r"(cw), "+r"(cm));
        float2 a[2], a32[2], a64[2], a512[2], pw32[2], pw128[2];
        uint32_t mm[2], t2, par;
        auto constants = [&](int h) {
            if (h) { t2 = lds32(sb + OFF_EPOCH + 4); par = lds32(sb + OFF_EPOCH); }
            auto ldc = [](uint32_t a) { const uint2 v = lds64(a); return make_float2(__uint_as_float(v.x), __uint_as_float(v.y)); };
            {
                a[h] = ldc(cp + 256 * h); a32[h] = ldc(cp + 256 * h + 1024); a64[h] = ldc(cp + 256 * h + 2048); a512[h] = ldc(cp + 256 * h + 7168);
                pw32[h] = ldc(cw + 256 * h);
                pw128[h] = ldc(cw + 256 * h + 3072);
                mm[h] = lds32(cm + 128 * h);
            }
        };
        if (wg == 1) {
            const int pc = w * 256 + dt * 32 + lane;
            const float lr = __bfloat162float(prm.lam_re[pc]), li = __bfloat162float(prm.lam_im[pc]), ld = __bfloat162float(prm.log_dt[pc]);
            const uint32_t dk = __ldg(reinterpret_cast<const uint32_t*>(prm.dskip + dt * 128) + (at & 63));
            reinterpret_cast<uint32_t*>(smem + OFF_DK)[at & 63] = dk;
            const float dtv = rbf(expf(ld));
            const float er = expf(dtv * lr);
            float sn, cs;
            sincosf(dtv * li, &sn, &cs);
            const float ar = er * cs, ai = er * sn;
            const float nr = ar - 1.0f, ni = ai;
            const bool big = fabsf(lr) >= fabsf(li);
            const float t = (big ? li : lr) / (big ? lr : li), dn = big ? lr + li * t : lr * t + li;
            const float cr = (big ? nr + ni * t : nr * t + ni) / dn, ci = (big ? ni - nr * t : ni * t - nr) / dn;
            float2* ct = reinterpret_cast<float2*>(smem + OFF_CONST) + at;
            float2 pw = make_float2(ar, prm.swapped ? -ai : ai);
            ct[0] = pw;
            const float mx = prm.swapped ? -2.f * ci : 2.f * cr, my = prm.swapped ? 2.f * cr : -2.f * ci;
            reinterpret_cast<uint32_t*>(smem + OFF_M)[at] = pack_bf(mx, my);
#pragma unroll
            for (int i = 0; i < 5; i++) pw = cmul(pw, pw);
#pragma unroll
            for (int i = 0; i < 2; i++) {
                const float2 p2 = cmul(pw, pw);
                ct[128 + 384 * i] = pw; ct[256 + 384 * i] = p2; ct[384 + 384 * i] = cmul(p2, pw);
                pw = cmul(p2, p2);
            }
            ct[896] = pw;
            mbar_wait(bar_epoch);
            __syncwarp();
            mbar_wait(empty + 8 * TN(RS_E));
            st_relaxed2(&prm.s->hid[cta * 128 + at], ~0u, ~0u);
            st_relaxed4(&prm.s->y[((at >> 4) * 8 + (cta >> 4)) * D_ + (cta & 15) * 64 + (at & 15) * 4], 0u, 0u, 0u, 0u);
            st_relaxed2(&prm.s->carry[chunk * 1024 + pc], 0u, 0u);
            __syncwarp();
            if (lane == 0) mbar_arrive(bar_const);

            STAMPIF(at == 0, 3);
            mbar_wait(bar_const);
            constants(0);
            constants(1);
            mbar_wait(bar_order);
        }

        float accA[64], accB[64];
        run_entries<0>(sb, wg * 16, wg * 16 + 15, wg, accA, accB, [&](int i) {
            if (i == GE - 1) {
                mbar_wait(bar_base);
                sched_fence(lds32(sb + OFF_EPOCH + 8) + TN(GT0));
            }
        });
        mbar_wait(full + 8 * (wg * 16 + 15));
        KSTAMP(wg * 16 + 15);
        if (wg == 0) {
            mbar_wait(bar_const);
            run_entry<0>(make_desc(sb), empty + 8 * 14, 1, accA, accB, [&]() { constants(0); constants(1); });
            if (lane == 0) mbar_arrive(bar_order);
        } else run_entry<0>(make_desc(sb + SLOT), empty + 8 * 30, 1, accA, accB, [&]() { if (lane == 0) mbar_arrive(bar_order + 8); });
        uint2 v[4];
#pragma unroll
        for (int m = 0; m < 4; m++) v[m] = make_uint2(t2, t2);
        wgmma_wait<0>();
        pin64(accA); pin64(accB);
        if (lane == 0) mbar_arrive(empty + 8 * (wg * 16 + 15));
        LSTAMP(at == 0, 96 + 30 + 10 * wg); GSTAMP(LT && at == 0, 193 + wg);

        auto cut = [&]() { if (never) sched_fence(cstart); };
        auto poll = [&](int h) {
#pragma unroll
            for (int m = 0; m < 4; m++)
                asm volatile("{ .reg .pred p; setp.ge.s32 p, %3, %4; @p ld.relaxed.gpu.global.v2.b32 {%0, %1}, [%2]; }"
                             : "+r"(v[m].x), "+r"(v[m].y) : "l"(cq + 256 * h - 4096 * m), "r"(j1), "r"(4 * m) : "memory");
        };
        auto valid = [&]() {
            uint32_t bad = 0;
#pragma unroll
            for (int m = 0; m < 4; m++) bad |= (v[m].x ^ t2) | (v[m].y ^ t2);
            return __all_sync(0xffffffffu, (bad & 3u) == 0);
        };
        float2 w0[2];
        uint32_t tp;
#pragma unroll
        for (int h = 0; h < 2; h++) {
            float (&acc)[64] = h ? accB : accA;
            float2 e = make_float2(acc[0], acc[2]);
#pragma unroll
            for (int s = 1; s < 32; s++) {
                const int i0 = 4 * (s >> 1) + (s & 1);
                e = cfma(a[h], e, make_float2(acc[i0], acc[i0 + 2]));
            }
            float2 y = make_float2(__shfl_up_sync(0xffffffffu, e.x, 1, 4), __shfl_up_sync(0xffffffffu, e.y, 1, 4));
            if (c >= 1) e = cfma(a32[h], y, e);
            y = make_float2(__shfl_up_sync(0xffffffffu, e.x, 2, 4), __shfl_up_sync(0xffffffffu, e.y, 2, 4));
            if (c >= 2) e = cfma(a64[h], y, e);
            if (c == 3) st_relaxed2(cq + 4096 + 256 * h, (__float_as_uint(e.x) & ~3u) | t2, (__float_as_uint(e.y) & ~3u) | t2);
            if (h == 0) tp = clk32();
            cut();
            w0[h] = make_float2(__shfl_up_sync(0xffffffffu, e.x, 1, 4), __shfl_up_sync(0xffffffffu, e.y, 1, 4));
            STAMPIF(at == 0, 31 + h + 10 * wg);
        }
        uint32_t sx[2][16], sy[2][16], mr[2][4];
        const uint32_t gap = wg ? TN(GAP1) : TN(GAP0);
#pragma unroll
        for (int h = 0; h < 2; h++) {
            const uint32_t sg = prm.swapped ? 0x80008000u : 0u;
            mr[h][0] = __byte_perm(mm[h], 0, 0x1010); mr[h][1] = __byte_perm(mm[h], 0, 0x3232);
            mr[h][2] = mr[h][1] ^ sg; mr[h][3] = mr[h][0] ^ sg ^ 0x80008000u;
        }
        auto put = [&](int e, int j) {
            uint32_t d[4];
#pragma unroll
            for (int u = 0; u < 4; u++) d[u] = fma_bf2(mr[e >> 1][2 * (e & 1)], sx[e >> 1][4 * j + u], mul_bf2(mr[e >> 1][2 * (e & 1) + 1], sy[e >> 1][4 * j + u]));
            #pragma unroll
            for (int u = 0; u < 2; u++)
                asm("lop3.b32 %0, %0, %1, %2, 0xD8;" : "+r"(d[2 * (j & 1) + u]) : "r"(par), "r"((uint32_t)((w & 1) == u)));
            stg128(hd + e * 65536 + (j >> 1) * 8192 + (j & 1) * 512, d[0], d[1], d[2], d[3]);
            if (j == 3 && lane == 0) mbar_arrive(bar_out + 32 * wg + 8 * e);
        };
#pragma unroll
        for (int h = 0; h < 2; h++) {
            float (&acc)[64] = h ? accB : accA;
            uint32_t it = 0;
            if (h == 0) {
                sleep_until(tp + (wg ? TN(T_CP1) : TN(T_CP0)));
                poll(h);
            }
            while (!valid()) {
                if (++it > SPIN_LIMIT) __trap();
#pragma unroll
                for (int m = 0; m < 4; m++)
                    asm volatile("{ .reg .pred p; setp.ne.u32 p, %3, 0; @p ld.relaxed.gpu.global.v2.b32 {%0, %1}, [%2]; }"
                                 : "+r"(v[m].x), "+r"(v[m].y) : "l"(cq + 256 * h - 4096 * m), "r"(((v[m].x ^ t2) | (v[m].y ^ t2)) & 3u) : "memory");
            }
            float2 hin = make_float2(__uint_as_float(v[3].x), __uint_as_float(v[3].y));
#pragma unroll
            for (int m = 2; m >= 0; m--) hin = cfma(a512[h], hin, make_float2(__uint_as_float(v[m].x), __uint_as_float(v[m].y)));
            STAMPIF(at == 0 && it > 0 && h == 0, 39 + 10 * wg);
            if (c) hin = cmul(pw128[h], hin);
            hin.x += __shfl_xor_sync(0xffffffffu, hin.x, 1); hin.y += __shfl_xor_sync(0xffffffffu, hin.y, 1);
            hin.x += __shfl_xor_sync(0xffffffffu, hin.x, 2); hin.y += __shfl_xor_sync(0xffffffffu, hin.y, 2);
            float2 st = hin;
            if (c) st = cfma(pw32[h], hin, w0[h]);
            STAMPIF(at == 0, 33 + 3 * h + 10 * wg);
#pragma unroll
            for (int j = 0; j < 4; j++) {
#pragma unroll
                for (int u = 0; u < 4; u++) {
                    const int i0 = 16 * j + 4 * u;
                    const float2 y = cfma(a[h], st, make_float2(acc[i0], acc[i0 + 2]));
                    st = cfma(a[h], y, make_float2(acc[i0 + 1], acc[i0 + 3]));
                    sx[h][4 * j + u] = pack_bf(y.x, st.x); sy[h][4 * j + u] = pack_bf(y.y, st.y);
                }
                if (h) sleep_until(tp += gap);
                if (h == 0 && j == 1) poll(1);
                put(2 * h, j);
                cut();
            }
            STAMPIF(at == 0, 34 + 3 * h + 10 * wg);
            tp = clk32();
#pragma unroll
            for (int j = 0; j < 4; j++) {
                sleep_until(tp += gap);
                put(2 * h + 1, j);
            }
        }
        STAMPIF(at == 0, 38 + 10 * wg);

        if (wg == 1) {
            const char* src = reinterpret_cast<const char*>(prm.s->h) + (size_t)chunk * 524288;
            uint32_t rpar = 1;
#pragma unroll 1
            for (int n = w; n < 2 * NSPL; n += 4) {
                mbar_wait(empty + 8 * (NBIG - 7 + n));
                mbar_wait(hfull + 8 * (NST + n % 7), n / 7 & 1);
                const uint32_t dst = sb + tail_h(n);
                rpar = check_tile<8>(sb, dst, probe, src + tail_src(n), par, full + 8 * w, rpar, TN(T_RETRY));
                if (lane == 0) mbar_expect_tx(full + 8 * (NBIG + n), n < NSPL ? 2 * TILE : 0);
            }
        } else {
            asm volatile("setmaxnreg.inc.sync.aligned.u32 216;");
            const int tl = 64 * (w & 1) + 8 * (w >> 1) + g;
            float gf[4];
            float* op = prm.out + (size_t)(chunk * 128 + tl) * D_ + dt * 128 + 4 * c;
            const int xr = 2 * (g & 3) + (g >> 2);
            uint32_t xs = sb + (32 * (w & 1) + 8 * (w >> 1) + xr) * 128 + (((c >> 1) ^ xr) << 4) + (c & 1) * 8;
            uint32_t gs = sb + OFF_G + 2 * tl;
            asm volatile("" : "+r"(gs), "+l"(op), "+r"(xs));
            float outA[64], outB[64];
            STAMPIF(at == 0, 9);
            mbar_wait(bar_order + 8);
            STAMPIF(at == 0, 35);
            run_entries<1>(sb, 32, NBIG, 32 % NST, outA, outB, [](int) {});
            uint32_t gp[4], om[4];
            uint2 xt[4][8], dk[8];
            auto load_x = [&](int q, int j) {
#pragma unroll
                for (int r = 0; r < 2; r++) xt[2 * q + r][j] = lds64((xs ^ ((j & 3) << 5)) + (q ? tail_c(0) : OFF_FT) + (j >> 2) * TILE + r * 2048);
                if (q == 0) dk[j] = lds64(sb + OFF_DK + c * 8 + 32 * j);
            };
            auto term = [&](int q, int j) {
#pragma unroll
                for (int r = 2 * q; r < 2 * q + 2; r++) {
                    xt[r][j].x = mul_bf2(xt[r][j].x, fma_bf2(gp[r], dk[j].x, om[r]));
                    xt[r][j].y = mul_bf2(xt[r][j].y, fma_bf2(gp[r], dk[j].y, om[r]));
                }
            };
            auto store = [&](int q, int u0, int u1) {
                const float (&acc)[64] = q ? outB : outA;
#pragma unroll
                for (int u = u0; u < u1; u++) {
                    const int j = u >> 1, r = u & 1;
                    const int o = 8 * j + 2 * r;
                    const float gv = fabsf(gf[2 * q + r]);
                    const uint2 t = xt[2 * q + r][j];
                    stg128(op + (r * 32 + q * 16) * D_ + 16 * j, __float_as_uint(fmaf(gv, acc[o], bf_lo(t.x))), __float_as_uint(fmaf(gv, acc[o + 1], bf_hi(t.x))),
                           __float_as_uint(fmaf(gv, acc[o + 4], bf_lo(t.y))), __float_as_uint(fmaf(gv, acc[o + 5], bf_hi(t.y))));
                }
            };
            uint64_t dh = desc64<1>(make_desc_h(sb)), dc = desc64<0>(make_desc(sb));
#pragma unroll
            for (int n = 0; n < 2 * NSPL; n++) {
                const int j = n % NSPL;
                if (n == 0) mbar_wait(bar_g);
                if (n == X0 || n == 2 * NSPL - 1) mbar_wait(bar_x + (n == X0 ? 0 : 8));
                mbar_wait(full + 8 * (NBIG + n));
                KSTAMP(NBIG + n);
                asm volatile("mov.b64 %0, %0; mov.b64 %1, %1;" : "+l"(dh), "+l"(dc));
                const uint64_t da = dh + (tail_h(n) >> 4), db = dc + (tail_c(j) >> 4);
                const int xj = n - X0;
                wgmma_fence();
#pragma unroll
                for (int kk = 0; kk < 4; kk++) {
                    wgmma_n128<1>(n < NSPL ? outA : outB, da + kk * 128, db + kk * 2);
                    if (kk == 0 && n == 0) {
#pragma unroll
                        for (int r = 0; r < 4; r++) {
                            uint32_t u;
                            asm volatile("ld.shared.u16 %0, [%1];" : "=r"(u) : "r"(gs + (r & 1) * 64 + (r >> 1) * 32) : "memory");
                            gf[r] = bf_lo(u);
                        }
                    }
                    if (kk == 0 && xj >= 0 && xj < 8) load_x(0, xj);
                    if (kk == 0 && n == 2 * NSPL - 1) load_x(1, 0);
                }
                wgmma_commit();
                if (n <= 2 * NSPL - 7) {
                    wgmma_wait<1>();
                    if (lane == 0) mbar_arrive(empty + 8 * (NBIG + n - 1));
                    if (!j) { LSTAMP(at == 0, 96 + 12 + n / NSPL); GSTAMP(LT && at == 0, 195 + n / NSPL); }
                } else cut();
                if (n == 0) {
#pragma unroll
                    for (int r = 0; r < 4; r++) {
                        const bool routed = (int)__float_as_uint(gf[r]) < 0;
                        gp[r] = routed ? 0u : pack_bf(gf[r], gf[r]); om[r] = routed ? 0u : pack_bf(1.0f - gf[r], 1.0f - gf[r]);
                    }
                }
                if (xj >= 0 && xj < 8) term(0, xj);
                if (n == NSPL) pin64(outA);
                if (n >= NSPL) store(0, (j * 16 + 4) / NSPL, j == NSPL - 1 ? 16 : ((j + 1) * 16 + 4) / NSPL);
            }
            term(1, 0);
            cut();
            wgmma_wait<0>();
            pin64(outB);
            LSTAMP(at == 0, 96 + 51); GSTAMP(LT && at == 0, 197);
#pragma unroll
            for (int j = 1; j < 8; j++) load_x(1, j);
            store(1, 0, 2);
#pragma unroll
            for (int j = 1; j < 8; j++) {
                cut();
                term(1, j);
                store(1, 2 * j, 2 * j + 2);
            }
            __syncwarp();
            if (lane == 0) mbar_arrive(bar_stored);
            LSTAMP(at == 0, 96 + 52);
        }
    } else if (warp < 12) {
        asm volatile("setmaxnreg.dec.sync.aligned.u32 64;");
        init_barriers(empty + min(80 + 160 * w, 8 * 67), 4, []() { return 20; });
#pragma unroll
        for (int i = 0; i < 2; i++) sts128(sb + OFF_LIST + i * 2048 + at * 16, 0u, 0u, 0u, 0u);
        uint32_t* keys = reinterpret_cast<uint32_t*>(smem + OFF_KEYS);
        keys[4] = 0;
        named_bar(0, 448);
        if (at < 24) st_relaxed(at < 8 ? &prm.s->key[kslot * 8 + at] : &prm.s->gate[rid * 16 + at - 8], 0u);
        mbar_wait(bar_epoch);
        const uint32_t t2 = lds32(sb + OFF_EPOCH + 4);
        STAMPIF(at == 0, 20);
        float facc[4];
        const uint32_t dft = make_desc(sb + OFF_FT), dxs = make_desc(sb + OFF_XS);
#pragma unroll 1
        for (int u = 0; u < 4; u++) {
            mbar_wait(ffull + 8 * u);
            STAMPIF(at == 0, 4 + u);
            wgmma_fence();
            small_tile<0>(facc, dft + u * (TILE >> 4), dxs + u * 64, u == 0);
            wgmma_commit();
        }
        wgmma_wait<0>();
        pin4(facc);
        if (lane < 4) mbar_arrive(fempty + 8 * lane);
        auto gate_up = [&](auto rest) {
            uint32_t slot = 4, par = 0, prev = full + 8 * 101, e4 = 4 * TN(GC0);
#pragma unroll 1
            for (int j = 0; j < 16; j++) {
                if (j == 2) rest();
                STAMPW(at == 0, 75 + j);
                mbar_wait(ffull + 8 * slot, par);
                STAMPW(at == 0, 160 + j);
                mbar_wait(empty + 8 * (e4 >> 2));
                e4 += j < 10 ? TN(GCS) : TN(GCS4);
                wgmma_fence();
                small_tile<1>(facc, dft + slot * (TILE >> 4), dxs + j * 64, j == 0);
                wgmma_commit();
                wgmma_wait<1>();
                if (lane == 0) mbar_arrive(prev);
                prev = fempty + 8 * slot;
                if (++slot == NFT) { slot = 0; par ^= 1; }
            }
            wgmma_wait<0>();
            if (lane == 0) mbar_arrive(prev);
            pin4(facc);
        };
        auto down = [&]() {
            const uint32_t dhid = make_desc(sb + OFF_HID);
#pragma unroll 1
            for (int j = 0; j < 7; j++) {
                mbar_wait(dfull + 8 * j);
                wgmma_fence();
                small_tile<1>(facc, dft + j * (TILE >> 4), dhid + j * 64, j == 0);
                wgmma_commit();
                if ((0x52 >> j) & 1) {
                    wgmma_wait<0>();
                    if (lane == 0) mbar_arrive(bar_dfree + 8 * (j / 3));
                }
            }
            wgmma_wait<0>();
            pin4(facc);
        };
        if ((c & 1) == (w >> 1)) {
            float* red = reinterpret_cast<float*>(smem + OFF_RED) + w * 32 + (c >> 1) * 16 + g;
            red[0] = (w & 1) ? facc[1] : facc[0];
            red[8] = (w & 1) ? facc[3] : facc[2];
        }
        named_bar(2, 128);
        STAMPIF(at == 0, 21);
        const uint32_t tpub = clk32();
        if (w < 2) {
            const float* red = reinterpret_cast<const float*>(smem + OFF_RED) + w * 16 + (lane & 15);
            const float v = rbf((red[0] + red[32]) + (red[64] + red[96]));
            if (w == 0) {
                uint32_t k = __float_as_uint(v);
                k = ((k ^ ((uint32_t)((int)k >> 31) | 0x80000000u)) & 0xFFFF0000u) | (t2 << 11) | (2047u - (uint32_t)(rid * 16 + (lane & 15)));
                int rank = 0;
#pragma unroll
                for (int i = 0; i < 8; i++) rank += __shfl_sync(0xffffffffu, k, (lane >> 4) * 8 + i) > k;
                rank += __shfl_xor_sync(0xffffffffu, rank, 16);
                if (rank < 8) st_relaxed(&prm.s->key[kslot * 8 + rank], k);
            } else if (lane < 16) st_relaxed(&prm.s->gate[rid * 16 + lane], __float_as_uint(rbf(sigmoidf_(v))) | t2);
            __syncwarp();
        }
        uint32_t it = 0;
        uint4 ka, kb4;
        mbar_wait(bar_base);
        sleep_until(lds32(sb + OFF_EPOCH + 8) + TN(GT1));
        sleep_until(tpub + TN(G0));
        bool bad = true;
        while (true) {
            if (bad) {
                ka = ld_relaxed4(&prm.s->key[at * 8]);
                kb4 = ld_relaxed4(&prm.s->key[at * 8 + 4]);
            }
            bad = (((ka.x ^ (t2 << 11)) | (kb4.x ^ (t2 << 11))) & 0x1800u) != 0;
            if (!__any_sync(0xffffffffu, bad)) break;
            if (++it > SPIN_LIMIT) __trap();
            __nanosleep(TN(T_RETRY));
        }
        STAMPIF(at == 0, 22);
        STAMPIF(at == 0 && it > 0, 23);
        const uint32_t m1 = __reduce_max_sync(0xffffffffu, ka.x), m2 = __reduce_max_sync(0xffffffffu, ka.x == m1 ? ka.y : ka.x);
        if (lane == 0) keys[w] = m2;
        named_bar(2, 128);
        const uint4 th4 = *reinterpret_cast<const uint4*>(keys);
        const uint32_t th = min(min(th4.x, th4.y), min(th4.z, th4.w));
        {
            const uint32_t k8[8] = {ka.x, ka.y, ka.z, ka.w, kb4.x, kb4.y, kb4.z, kb4.w};
            auto append = [&](int lo, int hi) {
                uint32_t n = 0, pos = 0;
#pragma unroll
                for (int i = lo; i < hi; i++) n += k8[i] >= th;
                asm volatile("{ .reg .pred p; setp.ne.u32 p, %2, 0; @p atom.shared.add.u32 %0, [%1], %2; }" : "+r"(pos) : "r"(sb + OFF_KEYS + 16), "r"(n) : "memory");
#pragma unroll
                for (int i = lo; i < hi; i++)
                    if (k8[i] >= th) reinterpret_cast<uint32_t*>(smem + OFF_LIST)[pos + i - lo] = k8[i];
            };
            append(0, 2);
            if (__any_sync(0xffffffffu, k8[2] >= th)) append(2, 8);
        }
        named_bar(2, 128);
        {
            const uint32_t* list = reinterpret_cast<const uint32_t*>(smem + OFF_LIST);
            const int n = (int)keys[4];
#pragma unroll 1
            for (int i0 = w * 32; i0 < n; i0 += 128) {
                const uint32_t k = list[i0 + lane];
                int rank = 0;
#pragma unroll 2
                for (int o = 0; o < n; o += 4) {
                    const uint4 l4 = *reinterpret_cast<const uint4*>(list + o);
                    rank += (l4.x > k) + (l4.y > k) + (l4.z > k) + (l4.w > k);
                }
                if (rank < 8) reinterpret_cast<uint32_t*>(smem + OFF_SEL)[rank] = k;
            }
        }
        named_bar(2, 128);
        STAMPIF(at == 0, 24);
        const uint32_t* sel = reinterpret_cast<const uint32_t*>(smem + OFF_SEL);
        auto gates = [&]() {
            uint32_t gv;
            it = 0;
            while (true) {
                gv = ld_relaxed(&prm.s->gate[chunk * 128 + at]);
                const uint32_t ar = ld_relaxed(&prm.s->armed[((cta >> 4) * 14 + min(lane, 13)) * 4]);
                if (__all_sync(0xffffffffu, (gv & 3u) == t2 && ar == t2)) break;
                if (++it > SPIN_LIMIT) __trap();
            }
            asm volatile("fence.acquire.gpu;" ::: "memory");
#pragma unroll
            for (int s = 0; s < 8; s++)
                if ((~sel[s] & 2047u) == (uint32_t)(chunk * 128 + at)) gv |= 0x80000000u;
            reinterpret_cast<uint16_t*>(smem + OFF_G)[at] = (uint16_t)(gv >> 16);
            __syncwarp();
            if (lane == 0) mbar_arrive(bar_g);
        };
        if (has_gu) {
            const int tk = (at >> 3) & 7;
            const char* xt = (const char*)prm.x + (~sel[tk] & 2047u) * 2048 + (at >> 6) * 128 + (at & 7) * 16;
#pragma unroll
            for (int i = 0; i < 8; i++) {
                cp_async16(sb + OFF_XS + (2 * i + (at >> 6)) * 1024 + tk * 128 + (((at & 7) ^ tk) << 4), xt + i * 256);
                if (i == 0 || i == 7) asm volatile("cp.async.commit_group;" ::: "memory");
            }
            asm volatile("cp.async.wait_group 1;" ::: "memory");
            fence_async_smem();
            named_bar(2, 128);
            STAMPIF(at == 0, 25);
            gate_up([&]() {
                asm volatile("cp.async.wait_all;" ::: "memory");
                fence_async_smem();
                named_bar(2, 128);
            });
            if (!(cta & 1)) {
#pragma unroll
                for (int u = 0; u < 4; u++) {
                    const float v = rbf(facc[u]);
                    facc[u] = __fdividef(v, 1.0f + __expf(-v));
                }
            }
            st_relaxed2(&prm.s->hid[cta * 128 + at], pack_bf(facc[0], facc[1]), pack_bf(facc[2], facc[3]));
        }
        STAMPIF(at == 0, 26);
        gates();
        uint32_t mine = __ballot_sync(0xffffffffu, lane < 8 && (int)((~sel[lane & 7] & 2047u) >> 7) == chunk), tr;
        uint2 xr, xd;
        float gr, rs;
        auto skip = [&](int n) {
#pragma unroll 1
            for (int i = 0; i < n; i++) mine &= mine - 1;
            if (mine) {
                const uint32_t key = sel[__ffs(mine) - 1], kb = key >> 16;
                tr = ~key & 2047u;
                xr = __ldg(reinterpret_cast<const uint2*>(prm.x + (size_t)tr * D_ + dt * 128) + lane);
                rs = rbf(sigmoidf_(bf_lo((kb & 0x8000u) ? (kb & 0x7FFFu) : (~kb & 0xFFFFu))));
                gr = fabsf(__bfloat162float(reinterpret_cast<const __nv_bfloat16*>(smem + OFF_G)[tr & 127]));
                xd = lds64(sb + OFF_DK + 8 * lane);
            }
        };
        mbar_wait(bar_g);
        skip(w);
        {
            mbar_wait(empty + 8 * max(TN(HG), 31));
            const uint2* hp = &prm.s->hid[(cta >> 4) * 14 * 128 + at];
            uint32_t hv[16];
            it = 0;
            while (true) {
                uint32_t top = 0;
#pragma unroll
                for (int j = 0; j < 7; j++) {
                    const uint2 hg = ld_relaxed2(hp + 256 * j), hu = ld_relaxed2(hp + 256 * j + 128);
                    top = max(top, max(hg.x, hu.x));
                    hv[2 * j] = mul_bf2(hg.x, hu.x); hv[2 * j + 1] = mul_bf2(hg.y, hu.y);
                }
                if (__all_sync(0xffffffffu, top != ~0u)) break;
                do {
                    if (++it > SPIN_LIMIT) __trap();
                } while (!__all_sync(0xffffffffu, ld_relaxed(hp + min(lane, 13) * 128 - lane) != ~0u));
            }
            STAMPIF(at == 0 && it > 0, 61);
            hv[14] = hv[15] = 0;
#pragma unroll
            for (int j = 0; j < 4; j++)
                asm volatile("stmatrix.sync.aligned.m8n8.x4.trans.shared.b16 [%0], {%1, %2, %3, %4};" ::"r"(
                                 sb + OFF_HID + (2 * j + (lane >> 4)) * 1024 + (lane & 7) * 128 + (((2 * w + ((lane >> 3) & 1)) ^ (lane & 7)) << 4)),
                             "r"(hv[4 * j]), "r"(hv[4 * j + 1]), "r"(hv[4 * j + 2]), "r"(hv[4 * j + 3]) : "memory");
        }
        fence_async_smem();
        named_bar(2, 128);
        STAMPIF(at == 0, 27);
        down();
#pragma unroll
        for (int u = 0; u < 4; u++)
            st_relaxed(&prm.s->y[((2 * c + (u & 1)) * 8 + (cta >> 4)) * D_ + (cta & 15) * 64 + w * 16 + g + 8 * (u >> 1)], (__float_as_uint(facc[u]) & ~3u) | t2);
        STAMPIF(at == 0, 28);
        sleep_until(clk32() + TN(T_Y));
        while (mine) {
            const uint32_t* yp = &prm.s->y[(__ffs(mine) - 1) * 8 * D_ + dt * 128 + 4 * lane];
            float y[4];
            it = 0;
            while (true) {
                uint32_t bad = 0;
                y[0] = y[1] = y[2] = y[3] = 0.f;
#pragma unroll
                for (int ks = 0; ks < 8; ks++) {
                    const uint4 v = ld_relaxed4(yp + ks * D_);
                    bad |= v.x ^ t2;
                    y[0] += __uint_as_float(v.x); y[1] += __uint_as_float(v.y); y[2] += __uint_as_float(v.z); y[3] += __uint_as_float(v.w);
                }
                if (__all_sync(0xffffffffu, (bad & 3u) == 0)) break;
                if (++it > SPIN_LIMIT) __trap();
            }
            STAMPIF(lane == 0 && it, 62);
#pragma unroll
            for (int u = 0; u < 4; u++) {
                const uint32_t x2 = (u & 2) ? xr.y : xr.x, d2 = mul_bf2(x2, (u & 2) ? xd.y : xd.x);
                y[u] = fmaf(gr, (u & 1) ? bf_hi(d2) : bf_lo(d2), rbf(rbf(1.0f - gr) * rbf(((u & 1) ? bf_hi(x2) : bf_lo(x2)) + rbf(rbf(y[u]) * rs))));
            }
            STAMPIF(lane == 0, 50);
            mbar_wait(bar_stored);
            asm volatile("red.global.add.v4.f32 [%0], {%1, %2, %3, %4};" ::"l"(prm.out + (size_t)tr * D_ + dt * 128 + 4 * lane), "f"(y[0]), "f"(y[1]), "f"(y[2]), "f"(y[3]) : "memory");
            skip(4);
        }
        LSTAMP(lane == 0, 96 + 29);
    } else {
        asm volatile("setmaxnreg.dec.sync.aligned.u32 40;");
        if (warp != 12) sleep_until(cstart + (warp == 13 ? TN(T_SMALL) : warp == 14 ? TN(PF0) - 250 : TN(T_W3)));
        auto behind = [&](int e) {
            if (!mbar_test(empty + 8 * e, 0)) {
                mbar_wait(empty + 8 * e);
                if (TN(T_X0)) sleep_until(clk32() + TN(T_X0));
            }
        };
        if (warp == 15) {
            prefetch_map(&mXr);
            named_bar(0, 448);
            asm volatile("bar.arrive 1, 64;" ::: "memory");
#pragma unroll 1
            for (int i = 0; i < 4; i++) {
                const int u = i;
                if (lane == 0) mbar_expect_tx(ffull + 8 * u, TILE);
                sleep_until(cstart + (i == 0 ? TN(RT0) : i == 1 ? TN(RT1) : i == 2 ? TN(RT2) : TN(RT3)));
                if (elect_one()) tma3(sb + OFF_FT + u * TILE, &mXr, u * 256, rid * 16, ffull + 8 * u);
                STAMP(53 + u);
            }
            const CUtensorMap* mw = (cta & 1) ? &mWu : &mWg;
            if (sb & 1023) __trap();
            prefetch_map(mw);
            prefetch_map(&mWd);
            uint32_t slot = 4, par = 1;
#pragma unroll 1
            for (int j = 0; j < (has_gu && DBG != 1 ? 16 : 0); j++) {
                mbar_wait(fempty + 8 * slot, par);
                if (lane == 0) mbar_expect_tx(ffull + 8 * slot, TILE);
                if (j < NFT) behind(TN(GU_E0) + j * TN(W_NUM) / 4);
                STAMPW(1, 176 + j);
                if (elect_one()) tma2(sb + OFF_FT + slot * TILE, mw, (cta >> 1) * 64, j * 64, ffull + 8 * slot);
                if (++slot == NFT) { slot = 0; par ^= 1; }
            }
            if (lane < 9) mbar_expect_tx(lane < 7 ? dfull + 8 * lane : bar_x + 8 * (lane - 7), lane < 7 ? TILE : 2 * TILE);
            if (!has_gu) mbar_wait(bar_g);
#pragma unroll 1
            for (int j = 0; j < (DBG != 1 ? 7 : 0); j++) {
                if (has_gu) mbar_wait(fempty + 8 * min(j, 4), 1);
                behind(min(TN(DL0) + j * TN(DLS) / 4, NBIG - 2));
                if (elect_one()) tma2(sb + OFF_FT + j * TILE, &mWd, (cta & 15) * 64, (cta >> 4) * 448 + j * 64, dfull + 8 * j);
            }
            prefetch_map(&mXe);
#pragma unroll 1
            for (int u = 0; u < 4; u++) {
                if (u == 2) {
                    mbar_wait(bar_dfree + 16);
                    if (elect_one()) tma5(sb + tail_c(8), &mCim, c_col(63), dt * 8, full + 8 * (NBIG + 8));
                }
                mbar_wait(bar_dfree);
                behind(u < 2 ? TN(DN_E0) + u : NBIG + NSPL);
                if (elect_one())
                    asm volatile("cp.async.bulk.tensor.5d.shared::cluster.global.mbarrier::complete_tx::bytes [%0], [%1, {%3, %6, %6, %4, %5}], [%2];"
                                 ::"r"(sb + (u < 2 ? OFF_FT : tail_c(0)) + (u & 1) * TILE), "l"(&mXe), "r"(bar_x + 4 * (u & 2)), "r"(dt * 128 + (u & 1) * 64),
                                 "r"(u & 2), "r"(chunk * 4), "r"(0) : "memory");
                if (u < 2) {
                    if (elect_one())
                        asm volatile("cp.async.bulk.prefetch.tensor.5d.L2.global [%0, {%1, %4, %4, %2, %3}];" ::"l"(&mXe), "r"(dt * 128 + u * 64), "r"(2), "r"(chunk * 4), "r"(0) : "memory");
                }
            }
        } else if (warp == 13) {
#pragma unroll
            for (int u = 0; u < 8; u++) {
                const int row = (u >> 2) * 4 + (lane >> 3);
                cp_async16(sb + OFF_XS + (u & 3) * 1024 + row * 128 + (((lane & 7) ^ row) << 4), (const char*)(u < 4 ? prm.w_r : prm.gate_w) + (u & 3) * 512 + lane * 16);
            }
            STAMP(57);
            const uint32_t tag = ld_relaxed(&prm.s->epoch[cta]) + 1;
            named_bar(1, 64);
            *reinterpret_cast<uint2*>(smem + OFF_EPOCH) = make_uint2(tag, tag % 3u + 1u);
            STAMPIF(tag, 58);
            asm volatile("cp.async.wait_all;" ::: "memory");
            STAMP(59);
            fence_async_smem();
            __syncwarp();
            if (lane == 0) {
                mbar_arrive(bar_epoch);
                prm.s->epoch[cta] = tag;
            }
            sleep_until(cstart + TN(T_BASE));
            {
                const uint2 st = ld_relaxed2(&prm.s->start[2 * lane]);
                const uint32_t d = st.x - cstart + 512u, age = gtime32() - st.y;
                const uint32_t m = __reduce_max_sync(0xffffffffu, d < 1024u && age < 4096u ? (d << 12) | age : 0u);
                const uint32_t late = (m & 4095u) - __reduce_min_sync(0xffffffffu, age);
                *reinterpret_cast<volatile uint32_t*>(smem + OFF_EPOCH + 8) = cstart + (m ? (m >> 12) - 512u + min(late, 256u) * TN(G_NS) / 4 : 0u);
                __syncwarp();
                if (lane == 0) mbar_arrive(bar_base);
                STAMP(60);
            }
            mbar_wait(bar_const);
            asm volatile("fence.acq_rel.gpu;" ::: "memory");
            if (lane < 4) st_relaxed2(&prm.s->armed[cta * 4 + lane], tag % 3u + 1u, 0u);
            prefetch_map(&mCre);
            prefetch_map(&mCim);
            const char* src = reinterpret_cast<const char*>(prm.s->h) + (size_t)chunk * 524288;
            uint32_t slot = 32 % NST, hpar = 0, rpar = 0;
#pragma unroll 1
            for (int i = 32; i < NBIG; i++) {
                mbar_wait(hfull + 8 * slot, hpar);
                STAMPIF(i == 32 || i == 33, 14 + (i & 1));
                rpar = check_tile<16>(sb, sb + slot * SLOT, probe, src, tag, bar_retry, rpar, TN(T_RETRY));
                if (lane == 0) mbar_expect_tx(full + 8 * i, 2 * TILE);
                STAMPIF(i == 32 || i == 33, 16 + (i & 1));
                src += 2 * TILE;
                slot = slot == NST - 1 ? 0 : slot + 1;
                hpar ^= slot == 32 % NST;
            }
        } else if (warp == 14) {
            prefetch_map(&mPB);
            auto pf_c = [&](int k) { prefetch_slice(&mPC, 4 * (k >> 1), cta * 8 + (k & 1) * 4); };
            {
                const char* px = (const char*)prm.x + (rid * 16 + (lane >> 1)) * 2048 + (lane & 1) * 128;
                const char* pb = (const char*)((lane & 8) ? prm.b_im : prm.b_re) + (cta * 4 + ((lane >> 1) & 3)) * 2048 + (lane & 1) * 128;
#pragma unroll 1
                for (int k = 1; k < 8; k++) {
                    sleep_until(cstart + TN(PF0) + (k - 1) * TN(PF1));
                    prefetch_l2(px + k * 256);
                    if (lane < 16) prefetch_l2(pb + k * 256);
                }
            }
            named_bar(7, 160);
            mbar_wait(bar_base);
#pragma unroll 1
            for (int k = 0; k < 4; k++) {
                behind(TN(PB_E0) + TN(PB_STEP) * k);
                if (elect_one()) prefetch_slice(&mPB, 4 * k, 512 + cta * 4);
            }
#pragma unroll 1
            for (int k = 0; k < TN(PC_N); k++) {
                behind(min(TN(PC_E0) + TN(PC_STEP) * k / 2, 25));
                if (elect_one()) pf_c(k);
            }
            int pk = TN(PC_N), pe = TN(PC_E1);
            auto own_part = [&](int e) {
                if (!(TDBG & 16) && !mbar_test(bar_out + 8 * e, 0)) {
                    mbar_wait(bar_out + 8 * e);
                    sleep_until(clk32() + TN(T_OWN));
                    STAMP(11);
                }
            };
            const char* src = reinterpret_cast<const char*>(prm.s->h) + (size_t)chunk * 524288;
            uint32_t slot = 32 % NST;
#pragma unroll 1
            for (int i = 32; i < NBIG; i++) {
                if (!(i & 3)) own_part((i - 32) >> 2);
                mbar_wait(empty + 8 * (i - NST));
                PSTAMP(i);
                if (elect_one()) {
                    mbar_expect_tx(hfull + 8 * slot, 2 * TILE);
                    bulk_load(sb + slot * SLOT, src, 2 * TILE, hfull + 8 * slot);
                    tma5(sb + slot * SLOT + 2 * TILE, (i & 4) ? &mCim : &mCre, c_col(i), dt * 8, full + 8 * i);
                }
                if (i == pe && pk < 8) {
                    if (elect_one()) pf_c(pk);
                    pk++; pe += TN(PC_S1);
                }
                src += 2 * TILE;
                slot = slot == NST - 1 ? 0 : slot + 1;
            }
            src -= (NBIG - 32) * 2 * TILE;
#pragma unroll
            for (int k = 0; k < 2 * NSPL - 2; k++) {
                if (k == 0 || k == 2) own_part(6 + k / 2);
                mbar_wait(empty + 8 * (NBIG - NST + k));
                if (k >= 1 && k <= 4) {
                    if (elect_one()) {
#pragma unroll
                        for (int j = 2 * k - 2; j < 2 * k; j++)
                            tma5(sb + tail_c(j), ((NBIG + j) & 4) ? &mCim : &mCre, c_col(NBIG + j), dt * 8, full + 8 * (NBIG + j));
                    }
                }
                if (k == 4) continue;
                if (k == 2) mbar_wait(bar_dfree + 8);
                if (elect_one()) {
#pragma unroll
                    for (int n = k < 5 ? 2 * k : k + 2; n < (k < 3 ? 2 * k + 2 : k == 3 ? 7 : k + 3); n++) {
                        mbar_expect_tx(hfull + 8 * (NST + n % 7), TILE);
                        bulk_load(sb + tail_h(n), src + tail_src(n), TILE, hfull + 8 * (NST + n % 7));
                    }
                }
            }
        } else {
            if (elect_one()) {
#pragma unroll
                for (int i = 0; i < NST; i++) mbar_init(full + 8 * i, 1);
                fence_mbar_init();
            }
            __syncwarp();
            asm volatile("bar.arrive 5, 160;" ::: "memory");
#pragma unroll 1
            for (int i = 0; i < NST; i++) {
                if (elect_one()) {
                    mbar_expect_tx(full + 8 * i, SLOT);
                    tma5b(sb + i * SLOT, &mB, i * 64, dt * 4, full + 8 * i);
                    tma4(sb + i * SLOT + 2 * TILE, &mX, i * 64, chunk * 64, full + 8 * i);
                }
                STAMPIF(i == 0, 1);
            }
            STAMP(2);
            asm volatile("bar.arrive 0, 448;" ::: "memory");
            named_bar(6, 160);
            uint32_t dst = sb;
#pragma unroll 1
            for (int i = NST; i < 32; i++) {
                if (i == 2 * NST) mbar_wait(bar_base);
                if (lane == 0) mbar_expect_tx(full + 8 * i, SLOT);
                mbar_wait(empty + 8 * (i - NST));
                PSTAMP(i);
                if (elect_one()) {
                    tma5b(dst, &mB, (i & 15) * 64, (i >> 4) * 64 + dt * 4, full + 8 * i);
                    tma4(dst + 2 * TILE, &mX, (i & 15) * 64, chunk * 64, full + 8 * i);
                }
                dst = dst == sb + (NST - 1) * SLOT ? sb : dst + SLOT;
            }
        }
    }
}

typedef CUresult (*EncodeFn)(CUtensorMap*, CUtensorMapDataType, cuuint32_t, void*, const cuuint64_t*, const cuuint64_t*, const cuuint32_t*,
                             const cuuint32_t*, CUtensorMapInterleave, CUtensorMapSwizzle, CUtensorMapL2promotion, CUtensorMapFloatOOBfill);

bool encode(EncodeFn fn, CUtensorMap* m, const void* ptr, int rank, const cuuint64_t* dims, const cuuint64_t* strides, const cuuint32_t* box,
            CUtensorMapL2promotion promo = CU_TENSOR_MAP_L2_PROMOTION_NONE) {
    const cuuint32_t es[5] = {1, 1, 1, 1, 1};
    return fn(m, CU_TENSOR_MAP_DATA_TYPE_BFLOAT16, rank, const_cast<void*>(ptr), dims, strides, box, es, CU_TENSOR_MAP_INTERLEAVE_NONE,
              CU_TENSOR_MAP_SWIZZLE_128B, promo, CU_TENSOR_MAP_FLOAT_OOB_FILL_NONE) == CUDA_SUCCESS;
}

}

extern "C" void kernel_launch(void* const* d_in, const int* in_sizes, int n_in, void* d_out, int out_size) {
    (void)in_sizes; (void)n_in; (void)out_size;
    Params prm;
    prm.x = (const __nv_bfloat16*)d_in[0];
    prm.lam_re = (const __nv_bfloat16*)d_in[1];
    prm.lam_im = (const __nv_bfloat16*)d_in[2];
    prm.b_re = (const __nv_bfloat16*)d_in[3];
    prm.b_im = (const __nv_bfloat16*)d_in[4];
    prm.c_re = (const __nv_bfloat16*)d_in[5];
    prm.c_im = (const __nv_bfloat16*)d_in[6];
    prm.log_dt = (const __nv_bfloat16*)d_in[7];
    prm.dskip = (const __nv_bfloat16*)d_in[8];
    prm.w_r = (const __nv_bfloat16*)d_in[10];
    prm.gate_w = (const __nv_bfloat16*)d_in[14];
    prm.out = (float*)d_out;
    cudaGetSymbolAddress((void**)&prm.s, g_scratch);
    prm.swapped = prm.b_im < prm.b_re;

    void* fnp = nullptr;
    cudaDriverEntryPointQueryResult qr;
    cudaGetDriverEntryPoint("cuTensorMapEncodeTiled", &fnp, cudaEnableDefault, &qr);
    EncodeFn fn = (EncodeFn)fnp;
    cudaFuncSetAttribute(fused_kernel, cudaFuncAttributeMaxDynamicSharedMemorySize, SMEM_BYTES);

    CUtensorMap mX, mB, mCre, mCim, mWg, mWu, mWd, mXr, mPB, mPC, mXe;
    const cuuint64_t row = 2048;
    {
        const cuuint64_t dims[4] = {1024, 2, 4, 976}, st[3] = {row, 32 * row, 2 * row};
        const cuuint32_t box[4] = {64, 2, 4, 16};
        encode(fn, &mX, prm.x, 4, dims, st, box, PROMO);
    }
    {
        const char *lo = (const char*)(prm.swapped ? prm.b_im : prm.b_re), *hi = (const char*)(prm.swapped ? prm.b_re : prm.b_im);
        const cuuint64_t dims[5] = {1024, 8, 2, 96, 2}, st[4] = {row, (cuuint64_t)(hi - lo), 8 * row, 256 * row};
        const cuuint32_t box[5] = {64, 8, 2, 4, 2};
        encode(fn, &mB, lo, 5, dims, st, box, PROMO);
    }
    {
        const cuuint64_t dims[5] = {1024, 2, 4, 2, 64}, st[4] = {row, 4 * row, 2 * row, 16 * row};
        const cuuint32_t box[5] = {64, 2, 4, 2, 8};
        encode(fn, &mCre, prm.c_re, 5, dims, st, box);
        encode(fn, &mCim, prm.c_im, 5, dims, st, box);
    }
    {
        const cuuint64_t dims[2] = {F_, D_}, st[1] = {F_ * 2}, dimsd[2] = {D_, F_}, std_[1] = {row};
        const cuuint32_t box[2] = {64, 64};
        encode(fn, &mWg, d_in[11], 2, dims, st, box);
        encode(fn, &mWu, d_in[12], 2, dims, st, box);
        encode(fn, &mWd, d_in[13], 2, dimsd, std_, box);
    }
    for (int i = 0; i < 2; i++) {
        const char *p = (const char*)(i ? prm.c_re : prm.b_re), *q = (const char*)(i ? prm.c_im : prm.b_im);
        const cuuint64_t dims[4] = {64, 16, 1024, 2}, st[3] = {128, row, (cuuint64_t)(p < q ? q - p : p - q)};
        const cuuint32_t box[4] = {16, 4, 4, 2};
        encode(fn, i ? &mPC : &mPB, p < q ? p : q, 4, dims, st, box, CU_TENSOR_MAP_L2_PROMOTION_L2_128B);
    }
    {
        const cuuint64_t dims[3] = {D_ - 192, S_, 4}, st[2] = {row, 128};
        const cuuint32_t box[3] = {64, 16, 4};
        encode(fn, &mXr, prm.x, 3, dims, st, box);
    }
    {
        const cuuint64_t dims[5] = {1024, 2, 4, 4, S_ / 32}, st[4] = {4 * row, row, 8 * row, 32 * row};
        const cuuint32_t box[5] = {64, 2, 4, 2, 4};
        encode(fn, &mXe, prm.x, 5, dims, st, box);
    }
    fused_kernel<<<NCTA, 512, SMEM_BYTES, cudaStreamPerThread>>>(prm, mX, mB, mCre, mCim, mWg, mWu, mWd, mXr, mPB, mPC, mXe);
}
```

```cpp
#include <cuda_runtime.h>
#include <cuda_bf16.h>
#include <cuda.h>
#include <stdint.h>

namespace {

constexpr int S_ = 2048, D_ = 1024, F_ = 3584;
constexpr int NCTA = 128;
constexpr int NSPL = 9, NBIG = 64 - NSPL, NENT = NBIG + 2 * NSPL;
constexpr int NST = 5;
constexpr int NFT = 5;
constexpr uint32_t SLOT = 32768, TILE = 8192;
constexpr uint32_t OFF_FT = NST * SLOT;
constexpr uint32_t OFF_XS = OFF_FT + NFT * TILE;
constexpr uint32_t OFF_LIST = OFF_XS + 8192;
constexpr uint32_t OFF_RED = OFF_XS + 4096;
constexpr uint32_t OFF_CONST = OFF_XS + 16384;
constexpr uint32_t OFF_M = OFF_CONST + 8192;
constexpr uint32_t OFF_HID = OFF_CONST;
constexpr uint32_t OFF_G = OFF_M + 512;
constexpr uint32_t OFF_DK = OFF_G + 256;
constexpr uint32_t OFF_FULL = OFF_DK + 256;
constexpr uint32_t OFF_EMPTY = OFF_FULL + 103 * 8;
constexpr uint32_t OFF_KEYS = OFF_EMPTY + 87 * 8;
constexpr uint32_t OFF_SEL = OFF_KEYS + 32;
constexpr uint32_t OFF_EPOCH = OFF_SEL + 32;
constexpr uint32_t OFF_PROF = OFF_EPOCH + 16;
constexpr uint32_t SMEM_BYTES = OFF_PROF + 432;
static_assert(SMEM_BYTES <= 232448, "smem");

static_assert(NBIG % NST == 0, "tail layout");
__host__ __device__ constexpr uint32_t tail_c(int j) { return j < 8 ? SLOT + j * 2 * TILE : OFF_FT + 5 * TILE; }
__host__ __device__ constexpr uint32_t tail_h(int n) { return n % 7 < 4 ? n % 7 * TILE : OFF_FT + (n % 7 - 2) * TILE; }
__host__ __device__ constexpr uint32_t tail_src(int n) { return (n % NSPL + NBIG - 32) * 2 * TILE + n / NSPL * TILE; }
__host__ __device__ constexpr int c_col(int i) { return ((i & 3) + ((i >> 1) & 12)) * 64; }

constexpr uint32_t SPIN_LIMIT = 1u << 18;

struct Scratch {
    uint2 carry[16 * 1024];
    uint2 hid[NCTA * 128];
    uint32_t y[8 * 8 * D_];
    uint32_t key[NCTA * 8];
    uint32_t gate[S_];
    uint2 armed[NCTA * 4];
    unsigned int epoch[256];
    uint4 start[32 * 2];
    uint4 h[16 * 32 * 1024];
};
__device__ __align__(1024) Scratch g_scratch;
#define STAMPW_(cond, w) do {} while (0)
#define GSTAMP(cond, w) do {} while (0)
#define LSTAMP(cond, w) STAMPW_(cond, w)
#define LT 0
#define STAMPW(cond, w) STAMPW_(cond, w)
#define STAMPIF(cond, i) STAMPW(cond, 96 + (i))
#define STAMP(i) STAMPW(1, 96 + (i))
#define KSTAMP(i) STAMPW((threadIdx.x & 127) == 0, i)
#define PSTAMP(i) STAMPW((i) < 56 && (i) >= 32, 160 + (i))

struct Params {
    const __nv_bfloat16 *x, *b_re, *b_im, *lam_re, *lam_im, *c_re, *c_im, *log_dt, *dskip, *w_r, *gate_w;
    float* out;
    Scratch* s;
    int swapped;
};

__device__ __forceinline__ uint32_t smem_u32(const void* p) { return (uint32_t)__cvta_generic_to_shared(p); }
__device__ __forceinline__ void mbar_init(uint32_t bar, uint32_t cnt) { asm volatile("mbarrier.init.shared::cta.b64 [%0], %1;" ::"r"(bar), "r"(cnt) : "memory"); }
__device__ __forceinline__ void mbar_expect_tx(uint32_t bar, uint32_t bytes) { asm volatile("mbarrier.arrive.expect_tx.shared::cta.b64 _, [%0], %1;" ::"r"(bar), "r"(bytes) : "memory"); }
__device__ __forceinline__ void mbar_arrive(uint32_t bar) { asm volatile("mbarrier.arrive.shared::cta.b64 _, [%0];" ::"r"(bar) : "memory"); }
__device__ __forceinline__ bool mbar_test(uint32_t bar, uint32_t parity) {
    uint32_t ok;
    asm volatile("{ .reg .pred p; mbarrier.test_wait.parity.shared::cta.b64 p, [%1], %2; selp.u32 %0, 1, 0, p; }" : "=r"(ok) : "r"(bar), "r"(parity) : "memory");
    return __all_sync(0xffffffffu, ok);
}
__device__ __forceinline__ void mbar_wait(uint32_t bar, uint32_t parity = 0) {
    asm volatile("{ .reg .pred p; .reg .u32 n; mov.u32 n, 0;\nW%=: mbarrier.try_wait.parity.shared::cta.b64 p, [%0], %1; @p bra D%=;\n"
                 "add.u32 n, n, 0x4000; setp.ne.u32 p, n, 0; @p bra W%=; trap;\nD%=: }" ::"r"(bar), "r"(parity) : "memory");
}
__device__ __forceinline__ bool elect_one() {
    uint32_t pred;
    asm volatile("{ .reg .pred P; elect.sync _|P, 0xffffffff; selp.b32 %0, 1, 0, P; }" : "=r"(pred));
    return pred;
}
__device__ __forceinline__ void named_bar(int id, int n) { asm volatile("bar.sync %0, %1;" ::"r"(id), "r"(n) : "memory"); }
__device__ __forceinline__ void fence_mbar_init() { asm volatile("fence.mbarrier_init.release.cluster;" ::: "memory"); }
__device__ __forceinline__ void fence_async_smem() { asm volatile("fence.proxy.async.shared::cta;" ::: "memory"); }

__device__ __forceinline__ void bulk_load(uint32_t dst, const void* src, uint32_t bytes, uint32_t bar) {
    asm volatile("cp.async.bulk.shared::cluster.global.mbarrier::complete_tx::bytes [%0], [%1], %2, [%3];" ::"r"(dst), "l"(src), "r"(bytes), "r"(bar) : "memory");
}
__device__ __forceinline__ void cp_async16(uint32_t dst, const void* src) { asm volatile("cp.async.cg.shared.global [%0], [%1], 16;" ::"r"(dst), "l"(src) : "memory"); }
__device__ __forceinline__ void sts128(uint32_t a, uint32_t x, uint32_t y, uint32_t z, uint32_t w) {
    asm volatile("st.shared.v4.u32 [%0], {%1,%2,%3,%4};" ::"r"(a), "r"(x), "r"(y), "r"(z), "r"(w) : "memory");
}
__device__ __forceinline__ uint2 lds64(uint32_t a) {
    uint2 v;
    asm volatile("ld.shared.v2.u32 {%0,%1}, [%2];" : "=r"(v.x), "=r"(v.y) : "r"(a) : "memory");
    return v;
}
__device__ __forceinline__ uint32_t lds32(uint32_t a) {
    uint32_t v;
    asm volatile("ld.volatile.shared.u32 %0, [%1];" : "=r"(v) : "r"(a) : "memory");
    return v;
}
__device__ __forceinline__ void stg128(void* p, uint32_t x, uint32_t y, uint32_t z, uint32_t w) {
    asm volatile("st.global.v4.u32 [%0], {%1,%2,%3,%4};" ::"l"(p), "r"(x), "r"(y), "r"(z), "r"(w) : "memory");
}
__device__ __forceinline__ void st_relaxed(void* p, uint32_t x) { asm volatile("st.relaxed.gpu.global.b32 [%0], %1;" ::"l"(p), "r"(x) : "memory"); }
__device__ __forceinline__ void st_relaxed2(void* p, uint32_t x, uint32_t y) { asm volatile("st.relaxed.gpu.global.v2.b32 [%0], {%1, %2};" ::"l"(p), "r"(x), "r"(y) : "memory"); }
__device__ __forceinline__ void st_relaxed4(void* p, uint32_t x, uint32_t y, uint32_t z, uint32_t w) {
    asm volatile("st.relaxed.gpu.global.v4.b32 [%0], {%1, %2, %3, %4};" ::"l"(p), "r"(x), "r"(y), "r"(z), "r"(w) : "memory");
}
__device__ __forceinline__ uint32_t ld_relaxed(const void* p) {
    uint32_t v;
    asm volatile("ld.relaxed.gpu.global.b32 %0, [%1];" : "=r"(v) : "l"(p) : "memory");
    return v;
}
__device__ __forceinline__ uint2 ld_relaxed2(const void* p) {
    uint2 v;
    asm volatile("ld.relaxed.gpu.global.v2.b32 {%0, %1}, [%2];" : "=r"(v.x), "=r"(v.y) : "l"(p) : "memory");
    return v;
}
__device__ __forceinline__ uint4 ld_relaxed4(const void* p) {
    uint4 v;
    asm volatile("ld.relaxed.gpu.global.v4.b32 {%0, %1, %2, %3}, [%4];" : "=r"(v.x), "=r"(v.y), "=r"(v.z), "=r"(v.w) : "l"(p) : "memory");
    return v;
}
__device__ __forceinline__ uint32_t clk32() { uint32_t c; asm volatile("mov.u32 %0, %%clock;" : "=r"(c)); return c; }
__device__ __forceinline__ uint32_t gtime32() { uint32_t c; asm volatile("mov.u32 %0, %%globaltimer_lo;" : "=r"(c)); return c; }
__device__ __forceinline__ void sched_fence(uint32_t t) { while ((int)(clk32() - t) < 0) {} }
__device__ __forceinline__ void sleep_until(uint32_t t) { while ((int)(clk32() - t) < 0) __nanosleep(40); }

__device__ __forceinline__ void tma2(uint32_t dst, const CUtensorMap* m, int c0, int c1, uint32_t bar) {
    asm volatile("{ .reg .b64 pol; createpolicy.fractional.L2::evict_first.b64 pol;\n"
                 "cp.async.bulk.tensor.2d.shared::cluster.global.mbarrier::complete_tx::bytes.L2::cache_hint [%0], [%1, {%3, %4}], [%2], pol; }"
                 ::"r"(dst), "l"(m), "r"(bar), "r"(c0), "r"(c1) : "memory");
}
__device__ __forceinline__ void tma3(uint32_t dst, const CUtensorMap* m, int c0, int c1, uint32_t bar) {
    asm volatile("cp.async.bulk.tensor.3d.shared::cluster.global.mbarrier::complete_tx::bytes [%0], [%1, {%3, %4, %5}], [%2];"
                 ::"r"(dst), "l"(m), "r"(bar), "r"(c0), "r"(c1), "r"(0) : "memory");
}
__device__ __forceinline__ void tma4(uint32_t dst, const CUtensorMap* m, int c0, int c3, uint32_t bar) {
    asm volatile("cp.async.bulk.tensor.4d.shared::cluster.global.mbarrier::complete_tx::bytes [%0], [%1, {%3, %5, %5, %4}], [%2];"
                 ::"r"(dst), "l"(m), "r"(bar), "r"(c0), "r"(c3), "r"(0) : "memory");
}
__device__ __forceinline__ void tma5(uint32_t dst, const CUtensorMap* m, int c0, int c4, uint32_t bar) {
    asm volatile("cp.async.bulk.tensor.5d.shared::cluster.global.mbarrier::complete_tx::bytes [%0], [%1, {%3, %5, %5, %5, %4}], [%2];"
                 ::"r"(dst), "l"(m), "r"(bar), "r"(c0), "r"(c4), "r"(0) : "memory");
}
__device__ __forceinline__ void tma5b(uint32_t dst, const CUtensorMap* m, int c0, int c3, uint32_t bar) {
    asm volatile("cp.async.bulk.tensor.5d.shared::cluster.global.mbarrier::complete_tx::bytes [%0], [%1, {%3, %5, %5, %4, %5}], [%2];"
                 ::"r"(dst), "l"(m), "r"(bar), "r"(c0), "r"(c3), "r"(0) : "memory");
}
__device__ __forceinline__ void prefetch_l2(const void* p) { asm volatile("prefetch.global.L2 [%0];" ::"l"(p)); }
__device__ __forceinline__ void prefetch_slice(const CUtensorMap* m, int line, int row) {
    asm volatile("cp.async.bulk.prefetch.tensor.4d.L2.global [%0, {%3, %1, %2, %3}];" ::"l"(m), "r"(line), "r"(row), "r"(0) : "memory");
}
__device__ __forceinline__ void prefetch_map(const CUtensorMap* m) { asm volatile("prefetch.tensormap [%0];" ::"l"(m)); }
__device__ __forceinline__ uint32_t uni(uint32_t v) { return __shfl_sync(0xffffffffu, v, 0); }

__device__ __forceinline__ uint32_t make_desc(uint32_t addr) { return ((addr & 0x3FFFF) >> 4) | (1u << 16); }
__device__ __forceinline__ uint32_t make_desc_h(uint32_t addr) { return ((addr & 0x3FFFF) >> 4) | (32u << 16); }
template <int H> __device__ __forceinline__ uint64_t desc64(uint32_t lo) {
    uint64_t d;
    asm volatile("mov.b64 %0, {%1, %2};" : "=l"(d) : "r"(lo), "n"(64u | ((H ? 2u : 1u) << 30)));
    return d;
}
__device__ __forceinline__ void wgmma_fence() { asm volatile("wgmma.fence.sync.aligned;" ::: "memory"); }
__device__ __forceinline__ void wgmma_commit() { asm volatile("wgmma.commit_group.sync.aligned;" ::: "memory"); }
template <int N> __device__ __forceinline__ void wgmma_wait() { asm volatile("wgmma.wait_group.sync.aligned %0;" ::"n"(N) : "memory"); }

#define R8(d, i) "+f"(d[i]), "+f"(d[i + 1]), "+f"(d[i + 2]), "+f"(d[i + 3]), "+f"(d[i + 4]), "+f"(d[i + 5]), "+f"(d[i + 6]), "+f"(d[i + 7])
#define R64(d) R8(d, 0), R8(d, 8), R8(d, 16), R8(d, 24), R8(d, 32), R8(d, 40), R8(d, 48), R8(d, 56)
template <int TA>
__device__ __forceinline__ void wgmma_n128(float (&d)[64], uint64_t da, uint64_t db, int scale_d = 1) {
    asm volatile("{ .reg .pred p; setp.ne.b32 p, %66, 0;\n"
                 "wgmma.mma_async.sync.aligned.m64n128k16.f32.bf16.bf16 "
                 "{%0,%1,%2,%3,%4,%5,%6,%7,%8,%9,%10,%11,%12,%13,%14,%15,%16,%17,%18,%19,%20,%21,%22,%23,%24,%25,%26,%27,%28,%29,%30,%31,"
                 "%32,%33,%34,%35,%36,%37,%38,%39,%40,%41,%42,%43,%44,%45,%46,%47,%48,%49,%50,%51,%52,%53,%54,%55,%56,%57,%58,%59,%60,%61,%62,%63}, "
                 "%64, %65, p, 1, 1, %67, 0; }"
                 : R64(d)
                 : "l"(da), "l"(db), "r"(scale_d), "n"(TA));
}
__device__ __forceinline__ void pin4(float (&d)[4]) { asm volatile("" : "+f"(d[0]), "+f"(d[1]), "+f"(d[2]), "+f"(d[3])::"memory"); }
__device__ __forceinline__ void pin64(float (&d)[64]) { asm volatile("" : R64(d)::"memory"); }

template <int TA>
__device__ __forceinline__ void wgmma_n8(float (&d)[4], uint64_t da, uint64_t db, int scale_d = 1) {
    asm volatile("{ .reg .pred p; setp.ne.b32 p, %7, 0;\n"
                 "wgmma.mma_async.sync.aligned.m64n8k16.f32.bf16.bf16 {%0,%1,%2,%3}, %4, %5, p, 1, 1, %6, 0; }"
                 : "+f"(d[0]), "+f"(d[1]), "+f"(d[2]), "+f"(d[3])
                 : "l"(da), "l"(db), "n"(TA), "r"(scale_d));
}

__device__ __forceinline__ float bf_lo(uint32_t u) { return __uint_as_float(u << 16); }
__device__ __forceinline__ float bf_hi(uint32_t u) { return __uint_as_float(u & 0xFFFF0000u); }
__device__ __forceinline__ float rbf(float v) { return __bfloat162float(__float2bfloat16_rn(v)); }
__device__ __forceinline__ uint32_t pack_bf(float lo, float hi) {
    uint32_t r;
    asm("cvt.rn.bf16x2.f32 %0, %1, %2;" : "=r"(r) : "f"(hi), "f"(lo));
    return r;
}
__device__ __forceinline__ uint32_t mul_bf2(uint32_t a, uint32_t b) {
    uint32_t r;
    asm("mul.rn.bf16x2 %0, %1, %2;" : "=r"(r) : "r"(a), "r"(b));
    return r;
}
__device__ __forceinline__ uint32_t fma_bf2(uint32_t a, uint32_t b, uint32_t c) {
    uint32_t r;
    asm("fma.rn.bf16x2 %0, %1, %2, %3;" : "=r"(r) : "r"(a), "r"(b), "r"(c));
    return r;
}
__device__ __forceinline__ float2 cmul(float2 a, float2 b) { return make_float2(a.x * b.x - a.y * b.y, a.x * b.y + a.y * b.x); }
__device__ __forceinline__ float2 cfma(float2 a, float2 b, float2 c) {
    return make_float2(fmaf(a.x, b.x, fmaf(-a.y, b.y, c.x)), fmaf(a.x, b.y, fmaf(a.y, b.x, c.y)));
}
__device__ __forceinline__ float sigmoidf_(float v) { return __fdividef(1.0f, 1.0f + expf(-v)); }

#define SCHED_NAMES T_W0, T_INIT, T_SMALL, T_W3, PF0, PF1, RT0, RT1, RT2, RT3, T_BASE, G_NS, GT0, GL, GQ, GT1, G0, T_CP0, T_CP1, GAP0, GAP1, T_OWN, \
    T_RETRY, T_Y, T_X0, RS_E, PB_E0, PB_STEP, PC_E0, PC_STEP, PC_N, PC_E1, PC_S1, GU_E0, W_NUM, GC0, GCS, GCS4, HG, DL0, DLS, DN_E0
enum { SCHED_NAMES, NTUNE };
constexpr int sched_default[NTUNE] = {
    600, 1000, 1000, 1000,
    1100, 400,
    2200, 2700, 3200, 3700,
    2500, 7,
    6200, 600, 1023, 7200,
    800, 900, 900,
    300, 300,
    1100, 200, 700, 200,
    4,
    4, 1, 9, 4, 5, 50, 3,
    4, 8, 14, 7, 5,
    43, 37, 8, 48};
template <int I> struct Sched { static constexpr int v = sched_default[I]; };
#define TN(i) (Sched<i>::v)
#define DBG 0
#define TDBG 0
#define X0 1
#define GE 8
#define PROMO CU_TENSOR_MAP_L2_PROMOTION_L2_256B

template <int TA, class H>
__device__ __forceinline__ void run_entry(uint32_t lo32, uint32_t prev, int accumulate, float (&accA)[64], float (&accB)[64], H inside) {
    const uint64_t da = desc64<TA>(lo32), db = TA ? desc64<0>(lo32 + (2 * TILE >> 4) - (31u << 16)) : da + (2 * TILE >> 4);
    wgmma_fence();
#pragma unroll
    for (int kk = 0; kk < 4; kk++) {
        wgmma_n128<TA>(accA, da + kk * (TA ? 128 : 2), db + kk * 2, kk > 0 ? 1 : accumulate);
        wgmma_n128<TA>(accB, da + 512 + kk * (TA ? 128 : 2), db + kk * 2, kk > 0 ? 1 : accumulate);
        if (kk == 1) {
            wgmma_commit();
            wgmma_wait<1>();
            if ((threadIdx.x & 31) == 0) mbar_arrive(prev);
            inside();
        }
    }
    wgmma_commit();
}
template <int TA, class H>
__device__ __forceinline__ void run_entries(uint32_t sb, int lo, int hi, int slot, float (&accA)[64], float (&accB)[64], H after) {
    const uint32_t da0 = TA ? make_desc_h(sb) : make_desc(sb), dlast = da0 + (NST - 1) * (SLOT >> 4);
    uint32_t prev = sb + OFF_FULL + 8 * 101, bar = sb + OFF_FULL + 8 * lo, lo32 = da0 + slot * (SLOT >> 4);
    int accumulate = 0;
#pragma unroll 1
    for (int i = lo; i < hi; i++) {
        mbar_wait(bar);
        KSTAMP(i);
        run_entry<TA>(lo32, prev, accumulate, accA, accB, []() {});
        prev = bar + (OFF_EMPTY - OFF_FULL);
        bar += 8;
        lo32 = lo32 == dlast ? da0 : lo32 + (SLOT >> 4);
        accumulate = 1;
        after(i);
    }
}

template <int TA>
__device__ __forceinline__ void small_tile(float (&acc)[4], uint32_t alo, uint32_t blo, bool first) {
    const uint64_t da = desc64<0>(alo), db = desc64<0>(blo);
#pragma unroll
    for (int kk = 0; kk < 4; kk++) wgmma_n8<TA>(acc, da + kk * (TA ? 128 : 2), db + kk * 2, kk > 0 || !first);
}

template <int N>
__device__ __forceinline__ uint32_t check_tile(uint32_t sb, uint32_t dst, uint32_t probe, const char* src, uint32_t par, uint32_t bar, uint32_t phase, uint32_t pause) {
    if (TDBG & 4) return phase;
#pragma unroll 1
    for (uint32_t it = 0; it < SPIN_LIMIT; it++) {
        uint32_t v[N], bad = 0;
#pragma unroll
        for (int u = 0; u < N; u++) v[u] = lds32(dst + probe + (u >> 1) * 2048 + (u & 1) * 256);
#pragma unroll
        for (int u = 0; u < N; u += 4)
            asm("{ .reg .b32 a, b; lop3.b32 a, %1, %2, %5, 0x7E; lop3.b32 b, %3, %4, %5, 0x7E; lop3.b32 %0, %0, a, b, 0xFE; }"
                : "+r"(bad) : "r"(v[u]), "r"(v[u + 1]), "r"(v[u + 2]), "r"(v[u + 3]), "r"(par));
        if (!__any_sync(0xffffffffu, bad & 1u)) return phase;
        STAMP(10);
        __nanosleep(pause);
        if (elect_one()) {
            mbar_expect_tx(bar, N * 1024);
            bulk_load(dst, src, N * 1024, bar);
        }
        mbar_wait(bar, phase);
        phase ^= 1;
    }
    __trap();
    return 0;
}

__global__ void __launch_bounds__(512, 1)
fused_kernel(const __grid_constant__ Params prm, const __grid_constant__ CUtensorMap mX, const __grid_constant__ CUtensorMap mB, const __grid_constant__ CUtensorMap mCre,
             const __grid_constant__ CUtensorMap mCim, const __grid_constant__ CUtensorMap mWg, const __grid_constant__ CUtensorMap mWu,
             const __grid_constant__ CUtensorMap mWd, const __grid_constant__ CUtensorMap mXr, const __grid_constant__ CUtensorMap mPB,
             const __grid_constant__ CUtensorMap mPC, const __grid_constant__ CUtensorMap mXe) {
    {
        const uint32_t t = threadIdx.x, b = blockIdx.x;
        const uint32_t row = t < 32 ? ((b & 60) * 2 + (b >> 6) * 4 + (b & 3)) * 16 + (t >> 1) : b * 4 + ((t >> 1) & 3);
        const char* base = (const char*)(t < 32 ? prm.x : t < 40 ? prm.b_re : prm.b_im);
        asm volatile("{ .reg .pred p; setp.lt.u32 p, %1, 48; @p prefetch.global.L2 [%0]; }" ::"l"(base + (row * 2048 + (t & 1) * 128)), "r"(t) : "memory");
    }
    extern __shared__ __align__(1024) uint8_t smem[];
    uint32_t sb;
    asm volatile("mov.u32 %0, %1;" : "=r"(sb) : "r"(smem_u32(smem)));
    const int tid = threadIdx.x, warp = __shfl_sync(0xffffffffu, tid >> 5, 0), lane = tid & 31;
    const int cta = blockIdx.x;
    const uint32_t cstart = clk32();
    const int chunk = (cta >> 2) & 15;
    const int dt = (cta >> 6) * 4 + (cta & 3);
    const int rid = chunk * 8 + dt;
    const int kslot = (rid & 3) * 32 + (rid >> 2);
    const bool has_gu = cta < 112;
    const uint32_t full = sb + OFF_FULL, empty = sb + OFF_EMPTY;
    const uint32_t bar_epoch = full + 8 * 73, dfull = full + 8 * 74, bar_retry = full + 8 * 81, bar_x = full + 8 * 82, ffull = full + 8 * 84,
                   hfull = full + 8 * 89, bar_base = full + 8 * 102;
    const uint32_t fempty = empty + 8 * 66, bar_order = empty + 8 * 71, bar_stored = empty + 8 * 73, bar_dfree = empty + 8 * 74,
                   bar_out = empty + 8 * 77, bar_g = empty + 8 * 85, bar_const = empty + 8 * 86;
    const int w = warp & 3, g = lane >> 2, c = lane & 3, at = tid & 127;

    const uint32_t probe = (lane >> 3) * 32 + (g & 1) * 144 + (c & 1) * 520 + (c >> 1) * 1028;

    LSTAMP(tid == 0, 96);
    GSTAMP(tid == 0, 94);
    auto init_barriers = [&](uint32_t base, uint32_t cnt, auto n) {
        if (elect_one()) {
#pragma unroll
            for (int i = 0; i < n(); i++) mbar_init(base + 8 * i, cnt);
            fence_mbar_init();
        }
        __syncwarp();
    };
    if (warp != 12) {
        if (warp == 15 && !(cta & 3) && lane < 8) st_relaxed((uint32_t*)&prm.s->start[cta >> 1] + lane, (lane & 1) ? gtime32() : cstart);
        if (warp < 12) sleep_until(cstart + (warp < 4 ? TN(T_W0) : TN(T_INIT)));
    }
    if (warp < 8) {
        if (warp < 4) init_barriers(warp == 0 ? full + 40 : warp == 3 ? full + 8 * 98 : empty + 40 * (warp - 1), (warp + 1) & 2 ? 4 : 1, []() { return 5; });
        else init_barriers(full + 80 + 176 * w, 1, []() { return 22; });
        asm volatile("setmaxnreg.inc.sync.aligned.u32 192;");
        if (warp < 4) {
            named_bar(5, 160);
            asm volatile("bar.arrive 0, 448;" ::: "memory");
            asm volatile("bar.arrive 6, 160;" ::: "memory");
            asm volatile("bar.arrive 7, 160;" ::: "memory");
        } else named_bar(0, 448);
        const int wg = warp >> 2;
        const int p = wg * 512 + dt * 32 + w * 8 + g;
        uint32_t cp = sb + OFF_CONST + 8 * (wg * 64 + w * 8 + g), cw = cp + 1024 * c, cm = sb + OFF_M + 4 * (wg * 64 + w * 8 + g);
        const int j1 = chunk - 1 - c;
        uint2* cq = &prm.s->carry[j1 * 1024 + p];
        char* hd = reinterpret_cast<char*>(prm.s->h) + (size_t)chunk * 524288 + wg * 262144 + (dt >> 1) * 16384 + ((dt & 1) * 4 + w) * 1024 + g * 64 + ((c ^ (g >> 1)) << 4);
        const bool never = uni(cstart == 0 && sb == 0);
        asm volatile("" : "+l"(cq), "+l"(hd), "+r"(cp), "+r"(cw), "+r"(cm));
        float2 a[2], a32[2], a64[2], a512[2], pw32[2], pw128[2];
        uint32_t mm[2], t2, par;
        auto constants = [&](int h) {
            if (h) { t2 = lds32(sb + OFF_EPOCH + 4); par = lds32(sb + OFF_EPOCH); }
            auto ldc = [](uint32_t a) { const uint2 v = lds64(a); return make_float2(__uint_as_float(v.x), __uint_as_float(v.y)); };
            {
                a[h] = ldc(cp + 256 * h); a32[h] = ldc(cp + 256 * h + 1024); a64[h] = ldc(cp + 256 * h + 2048); a512[h] = ldc(cp + 256 * h + 7168);
                pw32[h] = ldc(cw + 256 * h);
                pw128[h] = ldc(cw + 256 * h + 3072);
                mm[h] = lds32(cm + 128 * h);
            }
        };
        if (wg == 1) {
            const int pc = w * 256 + dt * 32 + lane;
            const float lr = __bfloat162float(prm.lam_re[pc]), li = __bfloat162float(prm.lam_im[pc]), ld = __bfloat162float(prm.log_dt[pc]);
            const uint32_t dk = __ldg(reinterpret_cast<const uint32_t*>(prm.dskip + dt * 128) + (at & 63));
            reinterpret_cast<uint32_t*>(smem + OFF_DK)[at & 63] = dk;
            const float dtv = rbf(expf(ld));
            const float er = expf(dtv * lr);
            float sn, cs;
            sincosf(dtv * li, &sn, &cs);
            const float ar = er * cs, ai = er * sn;
            const float nr = ar - 1.0f, ni = ai;
            const bool big = fabsf(lr) >= fabsf(li);
            const float t = (big ? li : lr) / (big ? lr : li), dn = big ? lr + li * t : lr * t + li;
            const float cr = (big ? nr + ni * t : nr * t + ni) / dn, ci = (big ? ni - nr * t : ni * t - nr) / dn;
            float2* ct = reinterpret_cast<float2*>(smem + OFF_CONST) + at;
            float2 pw = make_float2(ar, prm.swapped ? -ai : ai);
            ct[0] = pw;
            const float mx = prm.swapped ? -2.f * ci : 2.f * cr, my = prm.swapped ? 2.f * cr : -2.f * ci;
            reinterpret_cast<uint32_t*>(smem + OFF_M)[at] = pack_bf(mx, my);
#pragma unroll
            for (int i = 0; i < 5; i++) pw = cmul(pw, pw);
#pragma unroll
            for (int i = 0; i < 2; i++) {
                const float2 p2 = cmul(pw, pw);
                ct[128 + 384 * i] = pw; ct[256 + 384 * i] = p2; ct[384 + 384 * i] = cmul(p2, pw);
                pw = cmul(p2, p2);
            }
            ct[896] = pw;
            mbar_wait(bar_epoch);
            __syncwarp();
            mbar_wait(empty + 8 * TN(RS_E));
            st_relaxed2(&prm.s->hid[cta * 128 + at], ~0u, ~0u);
            st_relaxed4(&prm.s->y[((at >> 4) * 8 + (cta >> 4)) * D_ + (cta & 15) * 64 + (at & 15) * 4], 0u, 0u, 0u, 0u);
            st_relaxed2(&prm.s->carry[chunk * 1024 + pc], 0u, 0u);
            __syncwarp();
            if (lane == 0) mbar_arrive(bar_const);

            STAMPIF(at == 0, 3);
            mbar_wait(bar_const);
            constants(0);
            constants(1);
            mbar_wait(bar_order);
        }

        float accA[64], accB[64];
        run_entries<0>(sb, wg * 16, wg * 16 + 15, wg, accA, accB, [&](int i) {
            if (i == GE - 1) {
                mbar_wait(bar_base);
                const uint32_t t = lds32(sb + OFF_EPOCH + 8) + TN(GT0);
                const int late = clk32() - t - TN(GL);
                sched_fence(late < 0 ? t : t + TN(GL) + 256 + (late | TN(GQ)));
            }
        });
        mbar_wait(full + 8 * (wg * 16 + 15));
        KSTAMP(wg * 16 + 15);
        if (wg == 0) {
            mbar_wait(bar_const);
            run_entry<0>(make_desc(sb), empty + 8 * 14, 1, accA, accB, [&]() { constants(0); constants(1); });
            if (lane == 0) mbar_arrive(bar_order);
        } else run_entry<0>(make_desc(sb + SLOT), empty + 8 * 30, 1, accA, accB, [&]() { if (lane == 0) mbar_arrive(bar_order + 8); });
        uint2 v[4];
#pragma unroll
        for (int m = 0; m < 4; m++) v[m] = make_uint2(t2, t2);
        wgmma_wait<0>();
        pin64(accA); pin64(accB);
        if (lane == 0) mbar_arrive(empty + 8 * (wg * 16 + 15));
        LSTAMP(at == 0, 96 + 30 + 10 * wg); GSTAMP(LT && at == 0, 193 + wg);

        auto cut = [&]() { if (never) sched_fence(cstart); };
        auto poll = [&](int h) {
#pragma unroll
            for (int m = 0; m < 4; m++)
                asm volatile("{ .reg .pred p; setp.ge.s32 p, %3, %4; @p ld.relaxed.gpu.global.v2.b32 {%0, %1}, [%2]; }"
                             : "+r"(v[m].x), "+r"(v[m].y) : "l"(cq + 256 * h - 4096 * m), "r"(j1), "r"(4 * m) : "memory");
        };
        auto valid = [&]() {
            uint32_t bad = 0;
#pragma unroll
            for (int m = 0; m < 4; m++) bad |= (v[m].x ^ t2) | (v[m].y ^ t2);
            return __all_sync(0xffffffffu, (bad & 3u) == 0);
        };
        float2 w0[2];
        uint32_t tp;
#pragma unroll
        for (int h = 0; h < 2; h++) {
            float (&acc)[64] = h ? accB : accA;
            float2 e = make_float2(acc[0], acc[2]);
#pragma unroll
            for (int s = 1; s < 32; s++) {
                const int i0 = 4 * (s >> 1) + (s & 1);
                e = cfma(a[h], e, make_float2(acc[i0], acc[i0 + 2]));
            }
            float2 y = make_float2(__shfl_up_sync(0xffffffffu, e.x, 1, 4), __shfl_up_sync(0xffffffffu, e.y, 1, 4));
            if (c >= 1) e = cfma(a32[h], y, e);
            y = make_float2(__shfl_up_sync(0xffffffffu, e.x, 2, 4), __shfl_up_sync(0xffffffffu, e.y, 2, 4));
            if (c >= 2) e = cfma(a64[h], y, e);
            if (c == 3) st_relaxed2(cq + 4096 + 256 * h, (__float_as_uint(e.x) & ~3u) | t2, (__float_as_uint(e.y) & ~3u) | t2);
            if (h == 0) tp = clk32();
            cut();
            w0[h] = make_float2(__shfl_up_sync(0xffffffffu, e.x, 1, 4), __shfl_up_sync(0xffffffffu, e.y, 1, 4));
            STAMPIF(at == 0, 31 + h + 10 * wg);
        }
        uint32_t sx[2][16], sy[2][16], mr[2][4];
        const uint32_t gap = wg ? TN(GAP1) : TN(GAP0);
#pragma unroll
        for (int h = 0; h < 2; h++) {
            const uint32_t sg = prm.swapped ? 0x80008000u : 0u;
            mr[h][0] = __byte_perm(mm[h], 0, 0x1010); mr[h][1] = __byte_perm(mm[h], 0, 0x3232);
            mr[h][2] = mr[h][1] ^ sg; mr[h][3] = mr[h][0] ^ sg ^ 0x80008000u;
        }
        auto put = [&](int e, int j) {
            uint32_t d[4];
#pragma unroll
            for (int u = 0; u < 4; u++) d[u] = fma_bf2(mr[e >> 1][2 * (e & 1)], sx[e >> 1][4 * j + u], mul_bf2(mr[e >> 1][2 * (e & 1) + 1], sy[e >> 1][4 * j + u]));
            #pragma unroll
            for (int u = 0; u < 2; u++)
                asm("lop3.b32 %0, %0, %1, %2, 0xD8;" : "+r"(d[2 * (j & 1) + u]) : "r"(par), "r"((uint32_t)((w & 1) == u)));
            stg128(hd + e * 65536 + (j >> 1) * 8192 + (j & 1) * 512, d[0], d[1], d[2], d[3]);
            if (j == 3 && lane == 0) mbar_arrive(bar_out + 32 * wg + 8 * e);
        };
#pragma unroll
        for (int h = 0; h < 2; h++) {
            float (&acc)[64] = h ? accB : accA;
            uint32_t it = 0;
            if (h == 0) {
                sleep_until(tp + (wg ? TN(T_CP1) : TN(T_CP0)));
                poll(h);
            }
            while (!valid()) {
                if (++it > SPIN_LIMIT) __trap();
#pragma unroll
                for (int m = 0; m < 4; m++)
                    asm volatile("{ .reg .pred p; setp.ne.u32 p, %3, 0; @p ld.relaxed.gpu.global.v2.b32 {%0, %1}, [%2]; }"
                                 : "+r"(v[m].x), "+r"(v[m].y) : "l"(cq + 256 * h - 4096 * m), "r"(((v[m].x ^ t2) | (v[m].y ^ t2)) & 3u) : "memory");
            }
            float2 hin = make_float2(__uint_as_float(v[3].x), __uint_as_float(v[3].y));
#pragma unroll
            for (int m = 2; m >= 0; m--) hin = cfma(a512[h], hin, make_float2(__uint_as_float(v[m].x), __uint_as_float(v[m].y)));
            STAMPIF(at == 0 && it > 0 && h == 0, 39 + 10 * wg);
            if (c) hin = cmul(pw128[h], hin);
            hin.x += __shfl_xor_sync(0xffffffffu, hin.x, 1); hin.y += __shfl_xor_sync(0xffffffffu, hin.y, 1);
            hin.x += __shfl_xor_sync(0xffffffffu, hin.x, 2); hin.y += __shfl_xor_sync(0xffffffffu, hin.y, 2);
            float2 st = hin;
            if (c) st = cfma(pw32[h], hin, w0[h]);
            STAMPIF(at == 0, 33 + 3 * h + 10 * wg);
#pragma unroll
            for (int j = 0; j < 4; j++) {
#pragma unroll
                for (int u = 0; u < 4; u++) {
                    const int i0 = 16 * j + 4 * u;
                    const float2 y = cfma(a[h], st, make_float2(acc[i0], acc[i0 + 2]));
                    st = cfma(a[h], y, make_float2(acc[i0 + 1], acc[i0 + 3]));
                    sx[h][4 * j + u] = pack_bf(y.x, st.x); sy[h][4 * j + u] = pack_bf(y.y, st.y);
                }
                if (h) sleep_until(tp += gap);
                if (h == 0 && j == 1) poll(1);
                put(2 * h, j);
                cut();
            }
            STAMPIF(at == 0, 34 + 3 * h + 10 * wg);
            tp = clk32();
#pragma unroll
            for (int j = 0; j < 4; j++) {
                sleep_until(tp += gap);
                put(2 * h + 1, j);
            }
        }
        STAMPIF(at == 0, 38 + 10 * wg);

        if (wg == 1) {
            const char* src = reinterpret_cast<const char*>(prm.s->h) + (size_t)chunk * 524288;
            uint32_t rpar = 1;
#pragma unroll 1
            for (int n = w; n < 2 * NSPL; n += 4) {
                mbar_wait(empty + 8 * (NBIG - 7 + n));
                mbar_wait(hfull + 8 * (NST + n % 7), n / 7 & 1);
                const uint32_t dst = sb + tail_h(n);
                rpar = check_tile<8>(sb, dst, probe, src + tail_src(n), par, full + 8 * w, rpar, TN(T_RETRY));
                if (lane == 0) mbar_expect_tx(full + 8 * (NBIG + n), n < NSPL ? 2 * TILE : 0);
            }
        } else {
            asm volatile("setmaxnreg.inc.sync.aligned.u32 216;");
            const int tl = 64 * (w & 1) + 8 * (w >> 1) + g;
            float gf[4];
            float* op = prm.out + (size_t)(chunk * 128 + tl) * D_ + dt * 128 + 4 * c;
            const int xr = 2 * (g & 3) + (g >> 2);
            uint32_t xs = sb + (32 * (w & 1) + 8 * (w >> 1) + xr) * 128 + (((c >> 1) ^ xr) << 4) + (c & 1) * 8;
            uint32_t gs = sb + OFF_G + 2 * tl;
            asm volatile("" : "+r"(gs), "+l"(op), "+r"(xs));
            float outA[64], outB[64];
            STAMPIF(at == 0, 9);
            mbar_wait(bar_order + 8);
            STAMPIF(at == 0, 35);
            run_entries<1>(sb, 32, NBIG, 32 % NST, outA, outB, [](int) {});
            uint32_t gp[4], om[4];
            uint2 xt[4][8], dk[8];
            auto load_x = [&](int q, int j) {
#pragma unroll
                for (int r = 0; r < 2; r++) xt[2 * q + r][j] = lds64((xs ^ ((j & 3) << 5)) + (q ? tail_c(0) : OFF_FT) + (j >> 2) * TILE + r * 2048);
                if (q == 0) dk[j] = lds64(sb + OFF_DK + c * 8 + 32 * j);
            };
            auto term = [&](int q, int j) {
#pragma unroll
                for (int r = 2 * q; r < 2 * q + 2; r++) {
                    xt[r][j].x = mul_bf2(xt[r][j].x, fma_bf2(gp[r], dk[j].x, om[r]));
                    xt[r][j].y = mul_bf2(xt[r][j].y, fma_bf2(gp[r], dk[j].y, om[r]));
                }
            };
            auto store = [&](int q, int u0, int u1) {
                const float (&acc)[64] = q ? outB : outA;
#pragma unroll
                for (int u = u0; u < u1; u++) {
                    const int j = u >> 1, r = u & 1;
                    const int o = 8 * j + 2 * r;
                    const float gv = fabsf(gf[2 * q + r]);
                    const uint2 t = xt[2 * q + r][j];
                    stg128(op + (r * 32 + q * 16) * D_ + 16 * j, __float_as_uint(fmaf(gv, acc[o], bf_lo(t.x))), __float_as_uint(fmaf(gv, acc[o + 1], bf_hi(t.x))),
                           __float_as_uint(fmaf(gv, acc[o + 4], bf_lo(t.y))), __float_as_uint(fmaf(gv, acc[o + 5], bf_hi(t.y))));
                }
            };
            uint64_t dh = desc64<1>(make_desc_h(sb)), dc = desc64<0>(make_desc(sb));
#pragma unroll
            for (int n = 0; n < 2 * NSPL; n++) {
                const int j = n % NSPL;
                if (n == 0) mbar_wait(bar_g);
                if (n == X0 || n == 2 * NSPL - 1) mbar_wait(bar_x + (n == X0 ? 0 : 8));
                mbar_wait(full + 8 * (NBIG + n));
                KSTAMP(NBIG + n);
                asm volatile("mov.b64 %0, %0; mov.b64 %1, %1;" : "+l"(dh), "+l"(dc));
                const uint64_t da = dh + (tail_h(n) >> 4), db = dc + (tail_c(j) >> 4);
                const int xj = n - X0;
                wgmma_fence();
#pragma unroll
                for (int kk = 0; kk < 4; kk++) {
                    wgmma_n128<1>(n < NSPL ? outA : outB, da + kk * 128, db + kk * 2);
                    if (kk == 0 && n == 0) {
#pragma unroll
                        for (int r = 0; r < 4; r++) {
                            uint32_t u;
                            asm volatile("ld.shared.u16 %0, [%1];" : "=r"(u) : "r"(gs + (r & 1) * 64 + (r >> 1) * 32) : "memory");
                            gf[r] = bf_lo(u);
                        }
                    }
                    if (kk == 0 && xj >= 0 && xj < 8) load_x(0, xj);
                    if (kk == 0 && n == 2 * NSPL - 1) load_x(1, 0);
                }
                wgmma_commit();
                if (n <= 2 * NSPL - 7) {
                    wgmma_wait<1>();
                    if (lane == 0) mbar_arrive(empty + 8 * (NBIG + n - 1));
                    if (!j) { LSTAMP(at == 0, 96 + 12 + n / NSPL); GSTAMP(LT && at == 0, 195 + n / NSPL); }
                } else cut();
                if (n == 0) {
#pragma unroll
                    for (int r = 0; r < 4; r++) {
                        const bool routed = (int)__float_as_uint(gf[r]) < 0;
                        gp[r] = routed ? 0u : pack_bf(gf[r], gf[r]); om[r] = routed ? 0u : pack_bf(1.0f - gf[r], 1.0f - gf[r]);
                    }
                }
                if (xj >= 0 && xj < 8) term(0, xj);
                if (n == NSPL) pin64(outA);
                if (n >= NSPL) store(0, (j * 16 + 4) / NSPL, j == NSPL - 1 ? 16 : ((j + 1) * 16 + 4) / NSPL);
            }
            term(1, 0);
            cut();
            wgmma_wait<0>();
            pin64(outB);
            LSTAMP(at == 0, 96 + 51); GSTAMP(LT && at == 0, 197);
#pragma unroll
            for (int j = 1; j < 8; j++) load_x(1, j);
            store(1, 0, 2);
#pragma unroll
            for (int j = 1; j < 8; j++) {
                cut();
                term(1, j);
                store(1, 2 * j, 2 * j + 2);
            }
            __syncwarp();
            if (lane == 0) mbar_arrive(bar_stored);
            LSTAMP(at == 0, 96 + 52);
        }
    } else if (warp < 12) {
        asm volatile("setmaxnreg.dec.sync.aligned.u32 64;");
        init_barriers(empty + min(80 + 160 * w, 8 * 67), 4, []() { return 20; });
#pragma unroll
        for (int i = 0; i < 2; i++) sts128(sb + OFF_LIST + i * 2048 + at * 16, 0u, 0u, 0u, 0u);
        uint32_t* keys = reinterpret_cast<uint32_t*>(smem + OFF_KEYS);
        keys[4] = 0;
        named_bar(0, 448);
        if (at < 24) st_relaxed(at < 8 ? &prm.s->key[kslot * 8 + at] : &prm.s->gate[rid * 16 + at - 8], 0u);
        mbar_wait(bar_epoch);
        const uint32_t t2 = lds32(sb + OFF_EPOCH + 4);
        STAMPIF(at == 0, 20);
        float facc[4];
        const uint32_t dft = make_desc(sb + OFF_FT), dxs = make_desc(sb + OFF_XS);
#pragma unroll 1
        for (int u = 0; u < 4; u++) {
            mbar_wait(ffull + 8 * u);
            STAMPIF(at == 0, 4 + u);
            wgmma_fence();
            small_tile<0>(facc, dft + u * (TILE >> 4), dxs + u * 64, u == 0);
            wgmma_commit();
        }
        wgmma_wait<0>();
        pin4(facc);
        if (lane < 4) mbar_arrive(fempty + 8 * lane);
        auto gate_up = [&](auto rest) {
            uint32_t slot = 4, par = 0, prev = full + 8 * 101, e4 = 4 * TN(GC0);
#pragma unroll 1
            for (int j = 0; j < 16; j++) {
                if (j == 2) rest();
                STAMPW(at == 0, 75 + j);
                mbar_wait(ffull + 8 * slot, par);
                STAMPW(at == 0, 160 + j);
                mbar_wait(empty + 8 * (e4 >> 2));
                e4 += j < 10 ? TN(GCS) : TN(GCS4);
                wgmma_fence();
                small_tile<1>(facc, dft + slot * (TILE >> 4), dxs + j * 64, j == 0);
                wgmma_commit();
                wgmma_wait<1>();
                if (lane == 0) mbar_arrive(prev);
                prev = fempty + 8 * slot;
                if (++slot == NFT) { slot = 0; par ^= 1; }
            }
            wgmma_wait<0>();
            if (lane == 0) mbar_arrive(prev);
            pin4(facc);
        };
        auto down = [&]() {
            const uint32_t dhid = make_desc(sb + OFF_HID);
#pragma unroll 1
            for (int j = 0; j < 7; j++) {
                mbar_wait(dfull + 8 * j);
                wgmma_fence();
                small_tile<1>(facc, dft + j * (TILE >> 4), dhid + j * 64, j == 0);
                wgmma_commit();
                if ((0x52 >> j) & 1) {
                    wgmma_wait<0>();
                    if (lane == 0) mbar_arrive(bar_dfree + 8 * (j / 3));
                }
            }
            wgmma_wait<0>();
            pin4(facc);
        };
        if ((c & 1) == (w >> 1)) {
            float* red = reinterpret_cast<float*>(smem + OFF_RED) + w * 32 + (c >> 1) * 16 + g;
            red[0] = (w & 1) ? facc[1] : facc[0];
            red[8] = (w & 1) ? facc[3] : facc[2];
        }
        named_bar(2, 128);
        STAMPIF(at == 0, 21);
        const uint32_t tpub = clk32();
        if (w < 2) {
            const float* red = reinterpret_cast<const float*>(smem + OFF_RED) + w * 16 + (lane & 15);
            const float v = rbf((red[0] + red[32]) + (red[64] + red[96]));
            if (w == 0) {
                uint32_t k = __float_as_uint(v);
                k = ((k ^ ((uint32_t)((int)k >> 31) | 0x80000000u)) & 0xFFFF0000u) | (t2 << 11) | (2047u - (uint32_t)(rid * 16 + (lane & 15)));
                int rank = 0;
#pragma unroll
                for (int i = 0; i < 8; i++) rank += __shfl_sync(0xffffffffu, k, (lane >> 4) * 8 + i) > k;
                rank += __shfl_xor_sync(0xffffffffu, rank, 16);
                if (rank < 8) st_relaxed(&prm.s->key[kslot * 8 + rank], k);
            } else if (lane < 16) st_relaxed(&prm.s->gate[rid * 16 + lane], __float_as_uint(rbf(sigmoidf_(v))) | t2);
            __syncwarp();
        }
        uint32_t it = 0;
        uint4 ka, kb4;
        mbar_wait(bar_base);
        sleep_until(lds32(sb + OFF_EPOCH + 8) + TN(GT1));
        sleep_until(tpub + TN(G0));
        bool bad = true;
        while (true) {
            if (bad) {
                ka = ld_relaxed4(&prm.s->key[at * 8]);
                kb4 = ld_relaxed4(&prm.s->key[at * 8 + 4]);
            }
            bad = (((ka.x ^ (t2 << 11)) | (kb4.x ^ (t2 << 11))) & 0x1800u) != 0;
            if (!__any_sync(0xffffffffu, bad)) break;
            if (++it > SPIN_LIMIT) __trap();
            __nanosleep(TN(T_RETRY));
        }
        STAMPIF(at == 0, 22);
        STAMPIF(at == 0 && it > 0, 23);
        const uint32_t m1 = __reduce_max_sync(0xffffffffu, ka.x), m2 = __reduce_max_sync(0xffffffffu, ka.x == m1 ? ka.y : ka.x);
        if (lane == 0) keys[w] = m2;
        named_bar(2, 128);
        const uint4 th4 = *reinterpret_cast<const uint4*>(keys);
        const uint32_t th = min(min(th4.x, th4.y), min(th4.z, th4.w));
        {
            const uint32_t k8[8] = {ka.x, ka.y, ka.z, ka.w, kb4.x, kb4.y, kb4.z, kb4.w};
            auto append = [&](int lo, int hi) {
                uint32_t n = 0, pos = 0;
#pragma unroll
                for (int i = lo; i < hi; i++) n += k8[i] >= th;
                asm volatile("{ .reg .pred p; setp.ne.u32 p, %2, 0; @p atom.shared.add.u32 %0, [%1], %2; }" : "+r"(pos) : "r"(sb + OFF_KEYS + 16), "r"(n) : "memory");
#pragma unroll
                for (int i = lo; i < hi; i++)
                    if (k8[i] >= th) reinterpret_cast<uint32_t*>(smem + OFF_LIST)[pos + i - lo] = k8[i];
            };
            append(0, 2);
            if (__any_sync(0xffffffffu, k8[2] >= th)) append(2, 8);
        }
        named_bar(2, 128);
        {
            const uint32_t* list = reinterpret_cast<const uint32_t*>(smem + OFF_LIST);
            const int n = (int)keys[4];
#pragma unroll 1
            for (int i0 = w * 32; i0 < n; i0 += 128) {
                const uint32_t k = list[i0 + lane];
                int rank = 0;
#pragma unroll 2
                for (int o = 0; o < n; o += 4) {
                    const uint4 l4 = *reinterpret_cast<const uint4*>(list + o);
                    rank += (l4.x > k) + (l4.y > k) + (l4.z > k) + (l4.w > k);
                }
                if (rank < 8) reinterpret_cast<uint32_t*>(smem + OFF_SEL)[rank] = k;
            }
        }
        named_bar(2, 128);
        STAMPIF(at == 0, 24);
        const uint32_t* sel = reinterpret_cast<const uint32_t*>(smem + OFF_SEL);
        auto gates = [&]() {
            uint32_t gv;
            it = 0;
            while (true) {
                gv = ld_relaxed(&prm.s->gate[chunk * 128 + at]);
                const uint32_t ar = ld_relaxed(&prm.s->armed[((cta >> 4) * 14 + min(lane, 13)) * 4]);
                if (__all_sync(0xffffffffu, (gv & 3u) == t2 && ar == t2)) break;
                if (++it > SPIN_LIMIT) __trap();
            }
            asm volatile("fence.acquire.gpu;" ::: "memory");
#pragma unroll
            for (int s = 0; s < 8; s++)
                if ((~sel[s] & 2047u) == (uint32_t)(chunk * 128 + at)) gv |= 0x80000000u;
            reinterpret_cast<uint16_t*>(smem + OFF_G)[at] = (uint16_t)(gv >> 16);
            __syncwarp();
            if (lane == 0) mbar_arrive(bar_g);
        };
        if (has_gu) {
            const int tk = (at >> 3) & 7;
            const char* xt = (const char*)prm.x + (~sel[tk] & 2047u) * 2048 + (at >> 6) * 128 + (at & 7) * 16;
#pragma unroll
            for (int i = 0; i < 8; i++) {
                cp_async16(sb + OFF_XS + (2 * i + (at >> 6)) * 1024 + tk * 128 + (((at & 7) ^ tk) << 4), xt + i * 256);
                if (i == 0 || i == 7) asm volatile("cp.async.commit_group;" ::: "memory");
            }
            asm volatile("cp.async.wait_group 1;" ::: "memory");
            fence_async_smem();
            named_bar(2, 128);
            STAMPIF(at == 0, 25);
            gate_up([&]() {
                asm volatile("cp.async.wait_all;" ::: "memory");
                fence_async_smem();
                named_bar(2, 128);
            });
            if (!(cta & 1)) {
#pragma unroll
                for (int u = 0; u < 4; u++) {
                    const float v = rbf(facc[u]);
                    facc[u] = __fdividef(v, 1.0f + __expf(-v));
                }
            }
            st_relaxed2(&prm.s->hid[cta * 128 + at], pack_bf(facc[0], facc[1]), pack_bf(facc[2], facc[3]));
        }
        STAMPIF(at == 0, 26);
        gates();
        uint32_t mine = __ballot_sync(0xffffffffu, lane < 8 && (int)((~sel[lane & 7] & 2047u) >> 7) == chunk), tr;
        uint2 xr, xd;
        float gr, rs;
        auto skip = [&](int n) {
#pragma unroll 1
            for (int i = 0; i < n; i++) mine &= mine - 1;
            if (mine) {
                const uint32_t key = sel[__ffs(mine) - 1], kb = key >> 16;
                tr = ~key & 2047u;
                xr = __ldg(reinterpret_cast<const uint2*>(prm.x + (size_t)tr * D_ + dt * 128) + lane);
                rs = rbf(sigmoidf_(bf_lo((kb & 0x8000u) ? (kb & 0x7FFFu) : (~kb & 0xFFFFu))));
                gr = fabsf(__bfloat162float(reinterpret_cast<const __nv_bfloat16*>(smem + OFF_G)[tr & 127]));
                xd = lds64(sb + OFF_DK + 8 * lane);
            }
        };
        mbar_wait(bar_g);
        skip(w);
        {
            mbar_wait(empty + 8 * max(TN(HG), 31));
            const uint2* hp = &prm.s->hid[(cta >> 4) * 14 * 128 + at];
            uint32_t hv[16];
            it = 0;
            while (true) {
                uint32_t top = 0;
#pragma unroll
                for (int j = 0; j < 7; j++) {
                    const uint2 hg = ld_relaxed2(hp + 256 * j), hu = ld_relaxed2(hp + 256 * j + 128);
                    top = max(top, max(hg.x, hu.x));
                    hv[2 * j] = mul_bf2(hg.x, hu.x); hv[2 * j + 1] = mul_bf2(hg.y, hu.y);
                }
                if (__all_sync(0xffffffffu, top != ~0u)) break;
                do {
                    if (++it > SPIN_LIMIT) __trap();
                } while (!__all_sync(0xffffffffu, ld_relaxed(hp + min(lane, 13) * 128 - lane) != ~0u));
            }
            STAMPIF(at == 0 && it > 0, 61);
            hv[14] = hv[15] = 0;
#pragma unroll
            for (int j = 0; j < 4; j++)
                asm volatile("stmatrix.sync.aligned.m8n8.x4.trans.shared.b16 [%0], {%1, %2, %3, %4};" ::"r"(
                                 sb + OFF_HID + (2 * j + (lane >> 4)) * 1024 + (lane & 7) * 128 + (((2 * w + ((lane >> 3) & 1)) ^ (lane & 7)) << 4)),
                             "r"(hv[4 * j]), "r"(hv[4 * j + 1]), "r"(hv[4 * j + 2]), "r"(hv[4 * j + 3]) : "memory");
        }
        fence_async_smem();
        named_bar(2, 128);
        STAMPIF(at == 0, 27);
        down();
#pragma unroll
        for (int u = 0; u < 4; u++)
            st_relaxed(&prm.s->y[((2 * c + (u & 1)) * 8 + (cta >> 4)) * D_ + (cta & 15) * 64 + w * 16 + g + 8 * (u >> 1)], (__float_as_uint(facc[u]) & ~3u) | t2);
        STAMPIF(at == 0, 28);
        sleep_until(clk32() + TN(T_Y));
        while (mine) {
            const uint32_t* yp = &prm.s->y[(__ffs(mine) - 1) * 8 * D_ + dt * 128 + 4 * lane];
            float y[4];
            it = 0;
            while (true) {
                uint32_t bad = 0;
                y[0] = y[1] = y[2] = y[3] = 0.f;
#pragma unroll
                for (int ks = 0; ks < 8; ks++) {
                    const uint4 v = ld_relaxed4(yp + ks * D_);
                    bad |= v.x ^ t2;
                    y[0] += __uint_as_float(v.x); y[1] += __uint_as_float(v.y); y[2] += __uint_as_float(v.z); y[3] += __uint_as_float(v.w);
                }
                if (__all_sync(0xffffffffu, (bad & 3u) == 0)) break;
                if (++it > SPIN_LIMIT) __trap();
            }
            STAMPIF(lane == 0 && it, 62);
#pragma unroll
            for (int u = 0; u < 4; u++) {
                const uint32_t x2 = (u & 2) ? xr.y : xr.x, d2 = mul_bf2(x2, (u & 2) ? xd.y : xd.x);
                y[u] = fmaf(gr, (u & 1) ? bf_hi(d2) : bf_lo(d2), rbf(rbf(1.0f - gr) * rbf(((u & 1) ? bf_hi(x2) : bf_lo(x2)) + rbf(rbf(y[u]) * rs))));
            }
            STAMPIF(lane == 0, 50);
            mbar_wait(bar_stored);
            asm volatile("red.global.add.v4.f32 [%0], {%1, %2, %3, %4};" ::"l"(prm.out + (size_t)tr * D_ + dt * 128 + 4 * lane), "f"(y[0]), "f"(y[1]), "f"(y[2]), "f"(y[3]) : "memory");
            skip(4);
        }
        LSTAMP(lane == 0, 96 + 29);
    } else {
        asm volatile("setmaxnreg.dec.sync.aligned.u32 40;");
        if (warp != 12) sleep_until(cstart + (warp == 13 ? TN(T_SMALL) : warp == 14 ? TN(PF0) - 250 : TN(T_W3)));
        auto behind = [&](int e) {
            if (!mbar_test(empty + 8 * e, 0)) {
                mbar_wait(empty + 8 * e);
                if (TN(T_X0)) sleep_until(clk32() + TN(T_X0));
            }
        };
        if (warp == 15) {
            prefetch_map(&mXr);
            named_bar(0, 448);
            asm volatile("bar.arrive 1, 64;" ::: "memory");
#pragma unroll 1
            for (int i = 0; i < 4; i++) {
                const int u = i;
                if (lane == 0) mbar_expect_tx(ffull + 8 * u, TILE);
                sleep_until(cstart + (i == 0 ? TN(RT0) : i == 1 ? TN(RT1) : i == 2 ? TN(RT2) : TN(RT3)));
                if (elect_one()) tma3(sb + OFF_FT + u * TILE, &mXr, u * 256, rid * 16, ffull + 8 * u);
                STAMP(53 + u);
            }
            const CUtensorMap* mw = (cta & 1) ? &mWu : &mWg;
            if (sb & 1023) __trap();
            prefetch_map(mw);
            prefetch_map(&mWd);
            uint32_t slot = 4, par = 1;
#pragma unroll 1
            for (int j = 0; j < (has_gu && DBG != 1 ? 16 : 0); j++) {
                mbar_wait(fempty + 8 * slot, par);
                if (lane == 0) mbar_expect_tx(ffull + 8 * slot, TILE);
                if (j < NFT) behind(TN(GU_E0) + j * TN(W_NUM) / 4);
                STAMPW(1, 176 + j);
                if (elect_one()) tma2(sb + OFF_FT + slot * TILE, mw, (cta >> 1) * 64, j * 64, ffull + 8 * slot);
                if (++slot == NFT) { slot = 0; par ^= 1; }
            }
            if (lane < 9) mbar_expect_tx(lane < 7 ? dfull + 8 * lane : bar_x + 8 * (lane - 7), lane < 7 ? TILE : 2 * TILE);
            if (!has_gu) mbar_wait(bar_g);
#pragma unroll 1
            for (int j = 0; j < (DBG != 1 ? 7 : 0); j++) {
                if (has_gu) mbar_wait(fempty + 8 * min(j, 4), 1);
                behind(min(TN(DL0) + j * TN(DLS) / 4, NBIG - 2));
                if (elect_one()) tma2(sb + OFF_FT + j * TILE, &mWd, (cta & 15) * 64, (cta >> 4) * 448 + j * 64, dfull + 8 * j);
            }
            prefetch_map(&mXe);
#pragma unroll 1
            for (int u = 0; u < 4; u++) {
                if (u == 2) {
                    mbar_wait(bar_dfree + 16);
                    if (elect_one()) tma5(sb + tail_c(8), &mCim, c_col(63), dt * 8, full + 8 * (NBIG + 8));
                }
                mbar_wait(bar_dfree);
                behind(u < 2 ? TN(DN_E0) + u : NBIG + NSPL);
                if (elect_one())
                    asm volatile("cp.async.bulk.tensor.5d.shared::cluster.global.mbarrier::complete_tx::bytes [%0], [%1, {%3, %6, %6, %4, %5}], [%2];"
                                 ::"r"(sb + (u < 2 ? OFF_FT : tail_c(0)) + (u & 1) * TILE), "l"(&mXe), "r"(bar_x + 4 * (u & 2)), "r"(dt * 128 + (u & 1) * 64),
                                 "r"(u & 2), "r"(chunk * 4), "r"(0) : "memory");
                if (u < 2) {
                    if (elect_one())
                        asm volatile("cp.async.bulk.prefetch.tensor.5d.L2.global [%0, {%1, %4, %4, %2, %3}];" ::"l"(&mXe), "r"(dt * 128 + u * 64), "r"(2), "r"(chunk * 4), "r"(0) : "memory");
                }
            }
        } else if (warp == 13) {
#pragma unroll
            for (int u = 0; u < 8; u++) {
                const int row = (u >> 2) * 4 + (lane >> 3);
                cp_async16(sb + OFF_XS + (u & 3) * 1024 + row * 128 + (((lane & 7) ^ row) << 4), (const char*)(u < 4 ? prm.w_r : prm.gate_w) + (u & 3) * 512 + lane * 16);
            }
            STAMP(57);
            const uint32_t tag = ld_relaxed(&prm.s->epoch[cta]) + 1;
            named_bar(1, 64);
            *reinterpret_cast<uint2*>(smem + OFF_EPOCH) = make_uint2(tag, tag % 3u + 1u);
            STAMPIF(tag, 58);
            asm volatile("cp.async.wait_all;" ::: "memory");
            STAMP(59);
            fence_async_smem();
            __syncwarp();
            if (lane == 0) {
                mbar_arrive(bar_epoch);
                prm.s->epoch[cta] = tag;
            }
            sleep_until(cstart + TN(T_BASE));
            {
                const uint2 st = ld_relaxed2(&prm.s->start[2 * lane]);
                const uint32_t d = st.x - cstart + 512u, age = gtime32() - st.y;
                const uint32_t m = __reduce_max_sync(0xffffffffu, d < 1024u && age < 4096u ? (d << 12) | age : 0u);
                const uint32_t late = (m & 4095u) - __reduce_min_sync(0xffffffffu, age);
                *reinterpret_cast<volatile uint32_t*>(smem + OFF_EPOCH + 8) = cstart + (m ? (m >> 12) - 512u + min(late, 256u) * TN(G_NS) / 4 : 0u);
                __syncwarp();
                if (lane == 0) mbar_arrive(bar_base);
                STAMP(60);
            }
            mbar_wait(bar_const);
            asm volatile("fence.acq_rel.gpu;" ::: "memory");
            if (lane < 4) st_relaxed2(&prm.s->armed[cta * 4 + lane], tag % 3u + 1u, 0u);
            prefetch_map(&mCre);
            prefetch_map(&mCim);
            const char* src = reinterpret_cast<const char*>(prm.s->h) + (size_t)chunk * 524288;
            uint32_t slot = 32 % NST, hpar = 0, rpar = 0;
#pragma unroll 1
            for (int i = 32; i < NBIG; i++) {
                mbar_wait(hfull + 8 * slot, hpar);
                STAMPIF(i == 32 || i == 33, 14 + (i & 1));
                rpar = check_tile<16>(sb, sb + slot * SLOT, probe, src, tag, bar_retry, rpar, TN(T_RETRY));
                if (lane == 0) mbar_expect_tx(full + 8 * i, 2 * TILE);
                STAMPIF(i == 32 || i == 33, 16 + (i & 1));
                src += 2 * TILE;
                slot = slot == NST - 1 ? 0 : slot + 1;
                hpar ^= slot == 32 % NST;
            }
        } else if (warp == 14) {
            prefetch_map(&mPB);
            auto pf_c = [&](int k) { prefetch_slice(&mPC, 4 * (k >> 1), cta * 8 + (k & 1) * 4); };
            {
                const char* px = (const char*)prm.x + (rid * 16 + (lane >> 1)) * 2048 + (lane & 1) * 128;
                const char* pb = (const char*)((lane & 8) ? prm.b_im : prm.b_re) + (cta * 4 + ((lane >> 1) & 3)) * 2048 + (lane & 1) * 128;
#pragma unroll 1
                for (int k = 1; k < 8; k++) {
                    sleep_until(cstart + TN(PF0) + (k - 1) * TN(PF1));
                    prefetch_l2(px + k * 256);
                    if (lane < 16) prefetch_l2(pb + k * 256);
                }
            }
            named_bar(7, 160);
            mbar_wait(bar_base);
#pragma unroll 1
            for (int k = 0; k < 4; k++) {
                behind(TN(PB_E0) + TN(PB_STEP) * k);
                if (elect_one()) prefetch_slice(&mPB, 4 * k, 512 + cta * 4);
            }
#pragma unroll 1
            for (int k = 0; k < TN(PC_N); k++) {
                behind(min(TN(PC_E0) + TN(PC_STEP) * k / 2, 25));
                if (elect_one()) pf_c(k);
            }
            int pk = TN(PC_N), pe = TN(PC_E1);
            auto own_part = [&](int e) {
                if (!(TDBG & 16) && !mbar_test(bar_out + 8 * e, 0)) {
                    mbar_wait(bar_out + 8 * e);
                    sleep_until(clk32() + TN(T_OWN));
                    STAMP(11);
                }
            };
            const char* src = reinterpret_cast<const char*>(prm.s->h) + (size_t)chunk * 524288;
            uint32_t slot = 32 % NST;
#pragma unroll 1
            for (int i = 32; i < NBIG; i++) {
                if (!(i & 3)) own_part((i - 32) >> 2);
                mbar_wait(empty + 8 * (i - NST));
                PSTAMP(i);
                if (elect_one()) {
                    mbar_expect_tx(hfull + 8 * slot, 2 * TILE);
                    bulk_load(sb + slot * SLOT, src, 2 * TILE, hfull + 8 * slot);
                    tma5(sb + slot * SLOT + 2 * TILE, (i & 4) ? &mCim : &mCre, c_col(i), dt * 8, full + 8 * i);
                }
                if (i == pe && pk < 8) {
                    if (elect_one()) pf_c(pk);
                    pk++; pe += TN(PC_S1);
                }
                src += 2 * TILE;
                slot = slot == NST - 1 ? 0 : slot + 1;
            }
            src -= (NBIG - 32) * 2 * TILE;
#pragma unroll
            for (int k = 0; k < 2 * NSPL - 2; k++) {
                if (k == 0 || k == 2) own_part(6 + k / 2);
                mbar_wait(empty + 8 * (NBIG - NST + k));
                if (k >= 1 && k <= 4) {
                    if (elect_one()) {
#pragma unroll
                        for (int j = 2 * k - 2; j < 2 * k; j++)
                            tma5(sb + tail_c(j), ((NBIG + j) & 4) ? &mCim : &mCre, c_col(NBIG + j), dt * 8, full + 8 * (NBIG + j));
                    }
                }
                if (k == 4) continue;
                if (k == 2) mbar_wait(bar_dfree + 8);
                if (elect_one()) {
#pragma unroll
                    for (int n = k < 5 ? 2 * k : k + 2; n < (k < 3 ? 2 * k + 2 : k == 3 ? 7 : k + 3); n++) {
                        mbar_expect_tx(hfull + 8 * (NST + n % 7), TILE);
                        bulk_load(sb + tail_h(n), src + tail_src(n), TILE, hfull + 8 * (NST + n % 7));
                    }
                }
            }
        } else {
            if (elect_one()) {
#pragma unroll
                for (int i = 0; i < NST; i++) mbar_init(full + 8 * i, 1);
                fence_mbar_init();
            }
            __syncwarp();
            asm volatile("bar.arrive 5, 160;" ::: "memory");
            asm volatile("bar.arrive 0, 448;" ::: "memory");
#pragma unroll 1
            for (int i = 0; i < NST; i++) {
                if (elect_one()) {
                    mbar_expect_tx(full + 8 * i, SLOT);
                    tma5b(sb + i * SLOT, &mB, i * 64, dt * 4, full + 8 * i);
                    tma4(sb + i * SLOT + 2 * TILE, &mX, i * 64, chunk * 64, full + 8 * i);
                }
                STAMPIF(i == 0, 1);
            }
            STAMP(2);
            named_bar(6, 160);
            uint32_t dst = sb;
#pragma unroll 1
            for (int i = NST; i < 32; i++) {
                if (i == 2 * NST) mbar_wait(bar_base);
                if (lane == 0) mbar_expect_tx(full + 8 * i, SLOT);
                mbar_wait(empty + 8 * (i - NST));
                PSTAMP(i);
                if (elect_one()) {
                    tma5b(dst, &mB, (i & 15) * 64, (i >> 4) * 64 + dt * 4, full + 8 * i);
                    tma4(dst + 2 * TILE, &mX, (i & 15) * 64, chunk * 64, full + 8 * i);
                }
                dst = dst == sb + (NST - 1) * SLOT ? sb : dst + SLOT;
            }
        }
    }
}

typedef CUresult (*EncodeFn)(CUtensorMap*, CUtensorMapDataType, cuuint32_t, void*, const cuuint64_t*, const cuuint64_t*, const cuuint32_t*,
                             const cuuint32_t*, CUtensorMapInterleave, CUtensorMapSwizzle, CUtensorMapL2promotion, CUtensorMapFloatOOBfill);

bool encode(EncodeFn fn, CUtensorMap* m, const void* ptr, int rank, const cuuint64_t* dims, const cuuint64_t* strides, const cuuint32_t* box,
            CUtensorMapL2promotion promo = CU_TENSOR_MAP_L2_PROMOTION_NONE) {
    const cuuint32_t es[5] = {1, 1, 1, 1, 1};
    return fn(m, CU_TENSOR_MAP_DATA_TYPE_BFLOAT16, rank, const_cast<void*>(ptr), dims, strides, box, es, CU_TENSOR_MAP_INTERLEAVE_NONE,
              CU_TENSOR_MAP_SWIZZLE_128B, promo, CU_TENSOR_MAP_FLOAT_OOB_FILL_NONE) == CUDA_SUCCESS;
}

}

extern "C" void kernel_launch(void* const* d_in, const int* in_sizes, int n_in, void* d_out, int out_size) {
    (void)in_sizes; (void)n_in; (void)out_size;
    Params prm;
    prm.x = (const __nv_bfloat16*)d_in[0];
    prm.lam_re = (const __nv_bfloat16*)d_in[1];
    prm.lam_im = (const __nv_bfloat16*)d_in[2];
    prm.b_re = (const __nv_bfloat16*)d_in[3];
    prm.b_im = (const __nv_bfloat16*)d_in[4];
    prm.c_re = (const __nv_bfloat16*)d_in[5];
    prm.c_im = (const __nv_bfloat16*)d_in[6];
    prm.log_dt = (const __nv_bfloat16*)d_in[7];
    prm.dskip = (const __nv_bfloat16*)d_in[8];
    prm.w_r = (const __nv_bfloat16*)d_in[10];
    prm.gate_w = (const __nv_bfloat16*)d_in[14];
    prm.out = (float*)d_out;
    cudaGetSymbolAddress((void**)&prm.s, g_scratch);
    prm.swapped = prm.b_im < prm.b_re;

    void* fnp = nullptr;
    cudaDriverEntryPointQueryResult qr;
    cudaGetDriverEntryPoint("cuTensorMapEncodeTiled", &fnp, cudaEnableDefault, &qr);
    EncodeFn fn = (EncodeFn)fnp;
    cudaFuncSetAttribute(fused_kernel, cudaFuncAttributeMaxDynamicSharedMemorySize, SMEM_BYTES);

    CUtensorMap mX, mB, mCre, mCim, mWg, mWu, mWd, mXr, mPB, mPC, mXe;
    const cuuint64_t row = 2048;
    {
        const cuuint64_t dims[4] = {1024, 2, 4, 976}, st[3] = {row, 32 * row, 2 * row};
        const cuuint32_t box[4] = {64, 2, 4, 16};
        encode(fn, &mX, prm.x, 4, dims, st, box, PROMO);
    }
    {
        const char *lo = (const char*)(prm.swapped ? prm.b_im : prm.b_re), *hi = (const char*)(prm.swapped ? prm.b_re : prm.b_im);
        const cuuint64_t dims[5] = {1024, 8, 2, 96, 2}, st[4] = {row, (cuuint64_t)(hi - lo), 8 * row, 256 * row};
        const cuuint32_t box[5] = {64, 8, 2, 4, 2};
        encode(fn, &mB, lo, 5, dims, st, box, PROMO);
    }
    {
        const cuuint64_t dims[5] = {1024, 2, 4, 2, 64}, st[4] = {row, 4 * row, 2 * row, 16 * row};
        const cuuint32_t box[5] = {64, 2, 4, 2, 8};
        encode(fn, &mCre, prm.c_re, 5, dims, st, box);
        encode(fn, &mCim, prm.c_im, 5, dims, st, box);
    }
    {
        const cuuint64_t dims[2] = {F_, D_}, st[1] = {F_ * 2}, dimsd[2] = {D_, F_}, std_[1] = {row};
        const cuuint32_t box[2] = {64, 64};
        encode(fn, &mWg, d_in[11], 2, dims, st, box);
        encode(fn, &mWu, d_in[12], 2, dims, st, box);
        encode(fn, &mWd, d_in[13], 2, dimsd, std_, box);
    }
    for (int i = 0; i < 2; i++) {
        const char *p = (const char*)(i ? prm.c_re : prm.b_re), *q = (const char*)(i ? prm.c_im : prm.b_im);
        const cuuint64_t dims[4] = {64, 16, 1024, 2}, st[3] = {128, row, (cuuint64_t)(p < q ? q - p : p - q)};
        const cuuint32_t box[4] = {16, 4, 4, 2};
        encode(fn, i ? &mPC : &mPB, p < q ? p : q, 4, dims, st, box, CU_TENSOR_MAP_L2_PROMOTION_L2_128B);
    }
    {
        const cuuint64_t dims[3] = {D_ - 192, S_, 4}, st[2] = {row, 128};
        const cuuint32_t box[3] = {64, 16, 4};
        encode(fn, &mXr, prm.x, 3, dims, st, box);
    }
    {
        const cuuint64_t dims[5] = {1024, 2, 4, 4, S_ / 32}, st[4] = {4 * row, row, 8 * row, 32 * row};
        const cuuint32_t box[5] = {64, 2, 4, 2, 4};
        encode(fn, &mXe, prm.x, 5, dims, st, box);
    }
    fused_kernel<<<NCTA, 512, SMEM_BYTES, cudaStreamPerThread>>>(prm, mX, mB, mCre, mCim, mWg, mWu, mWd, mXr, mPB, mPC, mXe);
}
```

```cpp
#include <cuda_runtime.h>
#include <cuda_bf16.h>
#include <cuda.h>
#include <stdint.h>

namespace {

constexpr int S_ = 2048, D_ = 1024, F_ = 3584;
constexpr int NCTA = 128;
constexpr int NSPL = 9, NBIG = 64 - NSPL, NENT = NBIG + 2 * NSPL;
constexpr int NST = 5;
constexpr int NFT = 5;
constexpr uint32_t SLOT = 32768, TILE = 8192;
constexpr uint32_t OFF_FT = NST * SLOT;
constexpr uint32_t OFF_XS = OFF_FT + NFT * TILE;
constexpr uint32_t OFF_LIST = OFF_XS + 8192;
constexpr uint32_t OFF_RED = OFF_XS + 4096;
constexpr uint32_t OFF_CONST = OFF_XS + 16384;
constexpr uint32_t OFF_M = OFF_CONST + 8192;
constexpr uint32_t OFF_HID = OFF_CONST;
constexpr uint32_t OFF_G = OFF_M + 512;
constexpr uint32_t OFF_DK = OFF_G + 256;
constexpr uint32_t OFF_FULL = OFF_DK + 256;
constexpr uint32_t OFF_EMPTY = OFF_FULL + 103 * 8;
constexpr uint32_t OFF_KEYS = OFF_EMPTY + 87 * 8;
constexpr uint32_t OFF_SEL = OFF_KEYS + 32;
constexpr uint32_t OFF_EPOCH = OFF_SEL + 32;
constexpr uint32_t OFF_PROF = OFF_EPOCH + 16;
constexpr uint32_t SMEM_BYTES = OFF_PROF + 432;
static_assert(SMEM_BYTES <= 232448, "smem");

static_assert(NBIG % NST == 0, "tail layout");
__host__ __device__ constexpr uint32_t tail_c(int j) { return j < 8 ? SLOT + j * 2 * TILE : OFF_FT + 5 * TILE; }
__host__ __device__ constexpr uint32_t tail_h(int n) { return n % 7 < 4 ? n % 7 * TILE : OFF_FT + (n % 7 - 2) * TILE; }
__host__ __device__ constexpr uint32_t tail_src(int n) { return (n % NSPL + NBIG - 32) * 2 * TILE + n / NSPL * TILE; }
__host__ __device__ constexpr int c_col(int i) { return ((i & 3) + ((i >> 1) & 12)) * 64; }

constexpr uint32_t SPIN_LIMIT = 1u << 18;

struct Scratch {
    uint2 carry[16 * 1024];
    uint2 hid[NCTA * 128];
    uint32_t y[8 * 8 * D_];
    uint32_t key[NCTA * 8];
    uint32_t gate[S_];
    uint4 part[112 * 128];
    uint2 armed[NCTA * 4];
    unsigned int epoch[256];
    uint4 start[32 * 2];
    uint4 h[16 * 32 * 1024];
};
__device__ __align__(1024) Scratch g_scratch;
#define STAMPW_(cond, w) do {} while (0)
#define GSTAMP(cond, w) do {} while (0)
#define LSTAMP(cond, w) STAMPW_(cond, w)
#define LT 0
#define STAMPW(cond, w) STAMPW_(cond, w)
#define STAMPIF(cond, i) STAMPW(cond, 96 + (i))
#define STAMP(i) STAMPW(1, 96 + (i))
#define KSTAMP(i) STAMPW((threadIdx.x & 127) == 0, i)
#define PSTAMP(i) STAMPW((i) < 56 && (i) >= 32, 160 + (i))

struct Params {
    const __nv_bfloat16 *x, *b_re, *b_im, *lam_re, *lam_im, *c_re, *c_im, *log_dt, *dskip, *w_r, *gate_w;
    float* out;
    Scratch* s;
    int swapped;
};

__device__ __forceinline__ uint32_t smem_u32(const void* p) { return (uint32_t)__cvta_generic_to_shared(p); }
__device__ __forceinline__ void mbar_init(uint32_t bar, uint32_t cnt) { asm volatile("mbarrier.init.shared::cta.b64 [%0], %1;" ::"r"(bar), "r"(cnt) : "memory"); }
__device__ __forceinline__ void mbar_expect_tx(uint32_t bar, uint32_t bytes) { asm volatile("mbarrier.arrive.expect_tx.shared::cta.b64 _, [%0], %1;" ::"r"(bar), "r"(bytes) : "memory"); }
__device__ __forceinline__ void mbar_arrive(uint32_t bar) { asm volatile("mbarrier.arrive.shared::cta.b64 _, [%0];" ::"r"(bar) : "memory"); }
__device__ __forceinline__ bool mbar_test(uint32_t bar, uint32_t parity) {
    uint32_t ok;
    asm volatile("{ .reg .pred p; mbarrier.test_wait.parity.shared::cta.b64 p, [%1], %2; selp.u32 %0, 1, 0, p; }" : "=r"(ok) : "r"(bar), "r"(parity) : "memory");
    return __all_sync(0xffffffffu, ok);
}
__device__ __forceinline__ void mbar_wait(uint32_t bar, uint32_t parity = 0) {
    asm volatile("{ .reg .pred p; .reg .u32 n; mov.u32 n, 0;\nW%=: mbarrier.try_wait.parity.shared::cta.b64 p, [%0], %1; @p bra D%=;\n"
                 "add.u32 n, n, 0x4000; setp.ne.u32 p, n, 0; @p bra W%=; trap;\nD%=: }" ::"r"(bar), "r"(parity) : "memory");
}
__device__ __forceinline__ bool elect_one() {
    uint32_t pred;
    asm volatile("{ .reg .pred P; elect.sync _|P, 0xffffffff; selp.b32 %0, 1, 0, P; }" : "=r"(pred));
    return pred;
}
__device__ __forceinline__ void named_bar(int id, int n) { asm volatile("bar.sync %0, %1;" ::"r"(id), "r"(n) : "memory"); }
__device__ __forceinline__ void fence_mbar_init() { asm volatile("fence.mbarrier_init.release.cluster;" ::: "memory"); }
__device__ __forceinline__ void fence_async_smem() { asm volatile("fence.proxy.async.shared::cta;" ::: "memory"); }

__device__ __forceinline__ void bulk_load(uint32_t dst, const void* src, uint32_t bytes, uint32_t bar) {
    asm volatile("cp.async.bulk.shared::cluster.global.mbarrier::complete_tx::bytes [%0], [%1], %2, [%3];" ::"r"(dst), "l"(src), "r"(bytes), "r"(bar) : "memory");
}
__device__ __forceinline__ void cp_async16(uint32_t dst, const void* src) { asm volatile("cp.async.cg.shared.global [%0], [%1], 16;" ::"r"(dst), "l"(src) : "memory"); }
__device__ __forceinline__ void sts128(uint32_t a, uint32_t x, uint32_t y, uint32_t z, uint32_t w) {
    asm volatile("st.shared.v4.u32 [%0], {%1,%2,%3,%4};" ::"r"(a), "r"(x), "r"(y), "r"(z), "r"(w) : "memory");
}
__device__ __forceinline__ uint2 lds64(uint32_t a) {
    uint2 v;
    asm volatile("ld.shared.v2.u32 {%0,%1}, [%2];" : "=r"(v.x), "=r"(v.y) : "r"(a) : "memory");
    return v;
}
__device__ __forceinline__ uint32_t lds32(uint32_t a) {
    uint32_t v;
    asm volatile("ld.volatile.shared.u32 %0, [%1];" : "=r"(v) : "r"(a) : "memory");
    return v;
}
__device__ __forceinline__ void stg128(void* p, uint32_t x, uint32_t y, uint32_t z, uint32_t w) {
    asm volatile("st.global.v4.u32 [%0], {%1,%2,%3,%4};" ::"l"(p), "r"(x), "r"(y), "r"(z), "r"(w) : "memory");
}
__device__ __forceinline__ void st_relaxed(void* p, uint32_t x) { asm volatile("st.relaxed.gpu.global.b32 [%0], %1;" ::"l"(p), "r"(x) : "memory"); }
__device__ __forceinline__ void st_relaxed2(void* p, uint32_t x, uint32_t y) { asm volatile("st.relaxed.gpu.global.v2.b32 [%0], {%1, %2};" ::"l"(p), "r"(x), "r"(y) : "memory"); }
__device__ __forceinline__ void st_relaxed4(void* p, uint32_t x, uint32_t y, uint32_t z, uint32_t w) {
    asm volatile("st.relaxed.gpu.global.v4.b32 [%0], {%1, %2, %3, %4};" ::"l"(p), "r"(x), "r"(y), "r"(z), "r"(w) : "memory");
}
__device__ __forceinline__ uint32_t ld_relaxed(const void* p) {
    uint32_t v;
    asm volatile("ld.relaxed.gpu.global.b32 %0, [%1];" : "=r"(v) : "l"(p) : "memory");
    return v;
}
__device__ __forceinline__ uint2 ld_relaxed2(const void* p) {
    uint2 v;
    asm volatile("ld.relaxed.gpu.global.v2.b32 {%0, %1}, [%2];" : "=r"(v.x), "=r"(v.y) : "l"(p) : "memory");
    return v;
}
__device__ __forceinline__ uint4 ld_relaxed4(const void* p) {
    uint4 v;
    asm volatile("ld.relaxed.gpu.global.v4.b32 {%0, %1, %2, %3}, [%4];" : "=r"(v.x), "=r"(v.y), "=r"(v.z), "=r"(v.w) : "l"(p) : "memory");
    return v;
}
__device__ __forceinline__ uint32_t clk32() { uint32_t c; asm volatile("mov.u32 %0, %%clock;" : "=r"(c)); return c; }
__device__ __forceinline__ uint32_t gtime32() { uint32_t c; asm volatile("mov.u32 %0, %%globaltimer_lo;" : "=r"(c)); return c; }
__device__ __forceinline__ void sched_fence(uint32_t t) { while ((int)(clk32() - t) < 0) {} }
__device__ __forceinline__ void sleep_until(uint32_t t) { while ((int)(clk32() - t) < 0) __nanosleep(40); }

__device__ __forceinline__ void tma2(uint32_t dst, const CUtensorMap* m, int c0, int c1, uint32_t bar) {
    asm volatile("{ .reg .b64 pol; createpolicy.fractional.L2::evict_first.b64 pol;\n"
                 "cp.async.bulk.tensor.2d.shared::cluster.global.mbarrier::complete_tx::bytes.L2::cache_hint [%0], [%1, {%3, %4}], [%2], pol; }"
                 ::"r"(dst), "l"(m), "r"(bar), "r"(c0), "r"(c1) : "memory");
}
__device__ __forceinline__ void tma3(uint32_t dst, const CUtensorMap* m, int c0, int c1, uint32_t bar) {
    asm volatile("cp.async.bulk.tensor.3d.shared::cluster.global.mbarrier::complete_tx::bytes [%0], [%1, {%3, %4, %5}], [%2];"
                 ::"r"(dst), "l"(m), "r"(bar), "r"(c0), "r"(c1), "r"(0) : "memory");
}
__device__ __forceinline__ void tma4(uint32_t dst, const CUtensorMap* m, int c0, int c3, uint32_t bar) {
    asm volatile("cp.async.bulk.tensor.4d.shared::cluster.global.mbarrier::complete_tx::bytes [%0], [%1, {%3, %5, %5, %4}], [%2];"
                 ::"r"(dst), "l"(m), "r"(bar), "r"(c0), "r"(c3), "r"(0) : "memory");
}
__device__ __forceinline__ void tma5(uint32_t dst, const CUtensorMap* m, int c0, int c4, uint32_t bar) {
    asm volatile("cp.async.bulk.tensor.5d.shared::cluster.global.mbarrier::complete_tx::bytes [%0], [%1, {%3, %5, %5, %5, %4}], [%2];"
                 ::"r"(dst), "l"(m), "r"(bar), "r"(c0), "r"(c4), "r"(0) : "memory");
}
__device__ __forceinline__ void tma5b(uint32_t dst, const CUtensorMap* m, int c0, int c3, uint32_t bar) {
    asm volatile("cp.async.bulk.tensor.5d.shared::cluster.global.mbarrier::complete_tx::bytes [%0], [%1, {%3, %5, %5, %4, %5}], [%2];"
                 ::"r"(dst), "l"(m), "r"(bar), "r"(c0), "r"(c3), "r"(0) : "memory");
}
__device__ __forceinline__ void prefetch_l2(const void* p) { asm volatile("prefetch.global.L2 [%0];" ::"l"(p)); }
__device__ __forceinline__ void prefetch_slice(const CUtensorMap* m, int line, int row) {
    asm volatile("cp.async.bulk.prefetch.tensor.4d.L2.global [%0, {%3, %1, %2, %3}];" ::"l"(m), "r"(line), "r"(row), "r"(0) : "memory");
}
__device__ __forceinline__ void prefetch_map(const CUtensorMap* m) { asm volatile("prefetch.tensormap [%0];" ::"l"(m)); }
__device__ __forceinline__ uint32_t uni(uint32_t v) { return __shfl_sync(0xffffffffu, v, 0); }

__device__ __forceinline__ uint32_t make_desc(uint32_t addr) { return ((addr & 0x3FFFF) >> 4) | (1u << 16); }
__device__ __forceinline__ uint32_t make_desc_h(uint32_t addr) { return ((addr & 0x3FFFF) >> 4) | (32u << 16); }
template <int H> __device__ __forceinline__ uint64_t desc64(uint32_t lo) {
    uint64_t d;
    asm volatile("mov.b64 %0, {%1, %2};" : "=l"(d) : "r"(lo), "n"(64u | ((H ? 2u : 1u) << 30)));
    return d;
}
__device__ __forceinline__ void wgmma_fence() { asm volatile("wgmma.fence.sync.aligned;" ::: "memory"); }
__device__ __forceinline__ void wgmma_commit() { asm volatile("wgmma.commit_group.sync.aligned;" ::: "memory"); }
template <int N> __device__ __forceinline__ void wgmma_wait() { asm volatile("wgmma.wait_group.sync.aligned %0;" ::"n"(N) : "memory"); }

#define R8(d, i) "+f"(d[i]), "+f"(d[i + 1]), "+f"(d[i + 2]), "+f"(d[i + 3]), "+f"(d[i + 4]), "+f"(d[i + 5]), "+f"(d[i + 6]), "+f"(d[i + 7])
#define R64(d) R8(d, 0), R8(d, 8), R8(d, 16), R8(d, 24), R8(d, 32), R8(d, 40), R8(d, 48), R8(d, 56)
template <int TA>
__device__ __forceinline__ void wgmma_n128(float (&d)[64], uint64_t da, uint64_t db, int scale_d = 1) {
    asm volatile("{ .reg .pred p; setp.ne.b32 p, %66, 0;\n"
                 "wgmma.mma_async.sync.aligned.m64n128k16.f32.bf16.bf16 "
                 "{%0,%1,%2,%3,%4,%5,%6,%7,%8,%9,%10,%11,%12,%13,%14,%15,%16,%17,%18,%19,%20,%21,%22,%23,%24,%25,%26,%27,%28,%29,%30,%31,"
                 "%32,%33,%34,%35,%36,%37,%38,%39,%40,%41,%42,%43,%44,%45,%46,%47,%48,%49,%50,%51,%52,%53,%54,%55,%56,%57,%58,%59,%60,%61,%62,%63}, "
                 "%64, %65, p, 1, 1, %67, 0; }"
                 : R64(d)
                 : "l"(da), "l"(db), "r"(scale_d), "n"(TA));
}
__device__ __forceinline__ void pin4(float (&d)[4]) { asm volatile("" : "+f"(d[0]), "+f"(d[1]), "+f"(d[2]), "+f"(d[3])::"memory"); }
__device__ __forceinline__ void pin64(float (&d)[64]) { asm volatile("" : R64(d)::"memory"); }

template <int TA>
__device__ __forceinline__ void wgmma_n8(float (&d)[4], uint64_t da, uint64_t db, int scale_d = 1) {
    asm volatile("{ .reg .pred p; setp.ne.b32 p, %7, 0;\n"
                 "wgmma.mma_async.sync.aligned.m64n8k16.f32.bf16.bf16 {%0,%1,%2,%3}, %4, %5, p, 1, 1, %6, 0; }"
                 : "+f"(d[0]), "+f"(d[1]), "+f"(d[2]), "+f"(d[3])
                 : "l"(da), "l"(db), "n"(TA), "r"(scale_d));
}

__device__ __forceinline__ float bf_lo(uint32_t u) { return __uint_as_float(u << 16); }
__device__ __forceinline__ float bf_hi(uint32_t u) { return __uint_as_float(u & 0xFFFF0000u); }
__device__ __forceinline__ float rbf(float v) { return __bfloat162float(__float2bfloat16_rn(v)); }
__device__ __forceinline__ uint32_t pack_bf(float lo, float hi) {
    uint32_t r;
    asm("cvt.rn.bf16x2.f32 %0, %1, %2;" : "=r"(r) : "f"(hi), "f"(lo));
    return r;
}
__device__ __forceinline__ uint32_t mul_bf2(uint32_t a, uint32_t b) {
    uint32_t r;
    asm("mul.rn.bf16x2 %0, %1, %2;" : "=r"(r) : "r"(a), "r"(b));
    return r;
}
__device__ __forceinline__ uint32_t fma_bf2(uint32_t a, uint32_t b, uint32_t c) {
    uint32_t r;
    asm("fma.rn.bf16x2 %0, %1, %2, %3;" : "=r"(r) : "r"(a), "r"(b), "r"(c));
    return r;
}
__device__ __forceinline__ float2 cmul(float2 a, float2 b) { return make_float2(a.x * b.x - a.y * b.y, a.x * b.y + a.y * b.x); }
__device__ __forceinline__ float2 cfma(float2 a, float2 b, float2 c) {
    return make_float2(fmaf(a.x, b.x, fmaf(-a.y, b.y, c.x)), fmaf(a.x, b.y, fmaf(a.y, b.x, c.y)));
}
__device__ __forceinline__ float sigmoidf_(float v) { return __fdividef(1.0f, 1.0f + expf(-v)); }

#define SCHED_NAMES T_W0, T_INIT, T_SMALL, T_W3, PF0, PF1, RT0, RT1, RT2, RT3, T_BASE, G_NS, GT0, GL, GQ, GT1, G0, T_CP0, T_CP1, GAP0, GAP1, T_OWN, \
    T_RETRY, T_Y, T_X0, RS_E, PB_E0, PB_STEP, PC_E0, PC_STEP, PC_N, PC_E1, PC_S1, GU_E0, W_NUM, GC0, GCS, GCS4, GCH, HG, DL0, DLS, DN_E0
enum { SCHED_NAMES, NTUNE };
constexpr int sched_default[NTUNE] = {
    600, 1000, 1000, 1000,
    1100, 400,
    2200, 2700, 3200, 3700,
    2500, 7,
    6200, 600, 1023, 7200,
    800, 900, 900,
    300, 300,
    1100, 200, 700, 200,
    4,
    4, 1, 9, 4, 5, 50, 3,
    4, 8, 14, 8, 6, 11,
    43, 37, 8, 48};
template <int I> struct Sched { static constexpr int v = sched_default[I]; };
#define TN(i) (Sched<i>::v)
#define DBG 0
#define TDBG 0
#define X0 1
#define GE 8
#define PROMO CU_TENSOR_MAP_L2_PROMOTION_L2_256B

template <int TA, class H>
__device__ __forceinline__ void run_entry(uint32_t lo32, uint32_t prev, int accumulate, float (&accA)[64], float (&accB)[64], H inside) {
    const uint64_t da = desc64<TA>(lo32), db = TA ? desc64<0>(lo32 + (2 * TILE >> 4) - (31u << 16)) : da + (2 * TILE >> 4);
    wgmma_fence();
#pragma unroll
    for (int kk = 0; kk < 4; kk++) {
        wgmma_n128<TA>(accA, da + kk * (TA ? 128 : 2), db + kk * 2, kk > 0 ? 1 : accumulate);
        wgmma_n128<TA>(accB, da + 512 + kk * (TA ? 128 : 2), db + kk * 2, kk > 0 ? 1 : accumulate);
        if (kk == 1) {
            wgmma_commit();
            wgmma_wait<1>();
            if ((threadIdx.x & 31) == 0) mbar_arrive(prev);
            inside();
        }
    }
    wgmma_commit();
}
template <int TA, class H>
__device__ __forceinline__ void run_entries(uint32_t sb, int lo, int hi, int slot, float (&accA)[64], float (&accB)[64], H after) {
    const uint32_t da0 = TA ? make_desc_h(sb) : make_desc(sb), dlast = da0 + (NST - 1) * (SLOT >> 4);
    uint32_t prev = sb + OFF_FULL + 8 * 101, bar = sb + OFF_FULL + 8 * lo, lo32 = da0 + slot * (SLOT >> 4);
    int accumulate = 0;
#pragma unroll 1
    for (int i = lo; i < hi; i++) {
        mbar_wait(bar);
        KSTAMP(i);
        run_entry<TA>(lo32, prev, accumulate, accA, accB, []() {});
        prev = bar + (OFF_EMPTY - OFF_FULL);
        bar += 8;
        lo32 = lo32 == dlast ? da0 : lo32 + (SLOT >> 4);
        accumulate = 1;
        after(i);
    }
}

template <int TA>
__device__ __forceinline__ void small_tile(float (&acc)[4], uint32_t alo, uint32_t blo, bool first) {
    const uint64_t da = desc64<0>(alo), db = desc64<0>(blo);
#pragma unroll
    for (int kk = 0; kk < 4; kk++) wgmma_n8<TA>(acc, da + kk * (TA ? 128 : 2), db + kk * 2, kk > 0 || !first);
}

template <int N>
__device__ __forceinline__ uint32_t check_tile(uint32_t sb, uint32_t dst, uint32_t probe, const char* src, uint32_t par, uint32_t bar, uint32_t phase, uint32_t pause) {
    if (TDBG & 4) return phase;
#pragma unroll 1
    for (uint32_t it = 0; it < SPIN_LIMIT; it++) {
        uint32_t v[N], bad = 0;
#pragma unroll
        for (int u = 0; u < N; u++) v[u] = lds32(dst + probe + (u >> 1) * 2048 + (u & 1) * 256);
#pragma unroll
        for (int u = 0; u < N; u += 4)
            asm("{ .reg .b32 a, b; lop3.b32 a, %1, %2, %5, 0x7E; lop3.b32 b, %3, %4, %5, 0x7E; lop3.b32 %0, %0, a, b, 0xFE; }"
                : "+r"(bad) : "r"(v[u]), "r"(v[u + 1]), "r"(v[u + 2]), "r"(v[u + 3]), "r"(par));
        if (!__any_sync(0xffffffffu, bad & 1u)) return phase;
        STAMP(10);
        __nanosleep(pause);
        if (elect_one()) {
            mbar_expect_tx(bar, N * 1024);
            bulk_load(dst, src, N * 1024, bar);
        }
        mbar_wait(bar, phase);
        phase ^= 1;
    }
    __trap();
    return 0;
}

__global__ void __launch_bounds__(512, 1)
fused_kernel(const __grid_constant__ Params prm, const __grid_constant__ CUtensorMap mX, const __grid_constant__ CUtensorMap mB, const __grid_constant__ CUtensorMap mCre,
             const __grid_constant__ CUtensorMap mCim, const __grid_constant__ CUtensorMap mWg, const __grid_constant__ CUtensorMap mWu,
             const __grid_constant__ CUtensorMap mWd, const __grid_constant__ CUtensorMap mXr, const __grid_constant__ CUtensorMap mPB,
             const __grid_constant__ CUtensorMap mPC, const __grid_constant__ CUtensorMap mXe) {
    {
        const uint32_t t = threadIdx.x, b = blockIdx.x;
        const uint32_t row = t < 32 ? ((b & 60) * 2 + (b >> 6) * 4 + (b & 3)) * 16 + (t >> 1) : b * 4 + ((t >> 1) & 3);
        const char* base = (const char*)(t < 32 ? prm.x : t < 40 ? prm.b_re : prm.b_im);
        asm volatile("{ .reg .pred p; setp.lt.u32 p, %1, 48; @p prefetch.global.L2 [%0]; }" ::"l"(base + (row * 2048 + (t & 1) * 128)), "r"(t) : "memory");
    }
    extern __shared__ __align__(1024) uint8_t smem[];
    uint32_t sb;
    asm volatile("mov.u32 %0, %1;" : "=r"(sb) : "r"(smem_u32(smem)));
    const int tid = threadIdx.x, warp = __shfl_sync(0xffffffffu, tid >> 5, 0), lane = tid & 31;
    const int cta = blockIdx.x;
    const uint32_t cstart = clk32();
    const int chunk = (cta >> 2) & 15;
    const int dt = (cta >> 6) * 4 + (cta & 3);
    const int rid = chunk * 8 + dt;
    const int kslot = (rid & 3) * 32 + (rid >> 2);
    const bool owner = cta < 112;
    const uint32_t full = sb + OFF_FULL, empty = sb + OFF_EMPTY;
    const uint32_t bar_epoch = full + 8 * 73, dfull = full + 8 * 74, bar_retry = full + 8 * 81, bar_x = full + 8 * 82, ffull = full + 8 * 84,
                   hfull = full + 8 * 89, bar_base = full + 8 * 102;
    const uint32_t fempty = empty + 8 * 66, bar_order = empty + 8 * 71, bar_stored = empty + 8 * 73, bar_dfree = empty + 8 * 74,
                   bar_out = empty + 8 * 77, bar_g = empty + 8 * 85, bar_const = empty + 8 * 86;
    const int w = warp & 3, g = lane >> 2, c = lane & 3, at = tid & 127;

    const uint32_t probe = (lane >> 3) * 32 + (g & 1) * 144 + (c & 1) * 520 + (c >> 1) * 1028;

    LSTAMP(tid == 0, 96);
    GSTAMP(tid == 0, 94);
    auto init_barriers = [&](uint32_t base, uint32_t cnt, auto n) {
        if (elect_one()) {
#pragma unroll
            for (int i = 0; i < n(); i++) mbar_init(base + 8 * i, cnt);
            fence_mbar_init();
        }
        __syncwarp();
    };
    if (warp != 12) {
        if (warp == 15 && !(cta & 3) && lane < 8) st_relaxed((uint32_t*)&prm.s->start[cta >> 1] + lane, (lane & 1) ? gtime32() : cstart);
        if (warp < 12) sleep_until(cstart + (warp < 4 ? TN(T_W0) : TN(T_INIT)));
    }
    if (warp < 8) {
        if (warp < 4) init_barriers(warp == 0 ? full + 40 : warp == 3 ? full + 8 * 98 : empty + 40 * (warp - 1), (warp + 1) & 2 ? 4 : 1, []() { return 5; });
        else init_barriers(full + 80 + 176 * w, 1, []() { return 22; });
        asm volatile("setmaxnreg.inc.sync.aligned.u32 192;");
        if (warp < 4) {
            named_bar(5, 160);
            asm volatile("bar.arrive 0, 448;" ::: "memory");
            asm volatile("bar.arrive 6, 160;" ::: "memory");
            asm volatile("bar.arrive 7, 160;" ::: "memory");
        } else named_bar(0, 448);
        const int wg = warp >> 2;
        const int p = wg * 512 + dt * 32 + w * 8 + g;
        uint32_t cp = sb + OFF_CONST + 8 * (wg * 64 + w * 8 + g), cw = cp + 1024 * c, cm = sb + OFF_M + 4 * (wg * 64 + w * 8 + g);
        const int j1 = chunk - 1 - c;
        uint2* cq = &prm.s->carry[j1 * 1024 + p];
        char* hd = reinterpret_cast<char*>(prm.s->h) + (size_t)chunk * 524288 + wg * 262144 + (dt >> 1) * 16384 + ((dt & 1) * 4 + w) * 1024 + g * 64 + ((c ^ (g >> 1)) << 4);
        const bool never = uni(cstart == 0 && sb == 0);
        asm volatile("" : "+l"(cq), "+l"(hd), "+r"(cp), "+r"(cw), "+r"(cm));
        float2 a[2], a32[2], a64[2], a512[2], pw32[2], pw128[2];
        uint32_t mm[2], t2, par;
        auto constants = [&](int h) {
            if (h) { t2 = lds32(sb + OFF_EPOCH + 4); par = lds32(sb + OFF_EPOCH); }
            auto ldc = [](uint32_t a) { const uint2 v = lds64(a); return make_float2(__uint_as_float(v.x), __uint_as_float(v.y)); };
            {
                a[h] = ldc(cp + 256 * h); a32[h] = ldc(cp + 256 * h + 1024); a64[h] = ldc(cp + 256 * h + 2048); a512[h] = ldc(cp + 256 * h + 7168);
                pw32[h] = ldc(cw + 256 * h);
                pw128[h] = ldc(cw + 256 * h + 3072);
                mm[h] = lds32(cm + 128 * h);
            }
        };
        if (wg == 1) {
            const int pc = w * 256 + dt * 32 + lane;
            const float lr = __bfloat162float(prm.lam_re[pc]), li = __bfloat162float(prm.lam_im[pc]), ld = __bfloat162float(prm.log_dt[pc]);
            const uint32_t dk = __ldg(reinterpret_cast<const uint32_t*>(prm.dskip + dt * 128) + (at & 63));
            reinterpret_cast<uint32_t*>(smem + OFF_DK)[at & 63] = dk;
            const float dtv = rbf(expf(ld));
            const float er = expf(dtv * lr);
            float sn, cs;
            sincosf(dtv * li, &sn, &cs);
            const float ar = er * cs, ai = er * sn;
            const float nr = ar - 1.0f, ni = ai;
            const bool big = fabsf(lr) >= fabsf(li);
            const float t = (big ? li : lr) / (big ? lr : li), dn = big ? lr + li * t : lr * t + li;
            const float cr = (big ? nr + ni * t : nr * t + ni) / dn, ci = (big ? ni - nr * t : ni * t - nr) / dn;
            float2* ct = reinterpret_cast<float2*>(smem + OFF_CONST) + at;
            float2 pw = make_float2(ar, prm.swapped ? -ai : ai);
            ct[0] = pw;
            const float mx = prm.swapped ? -2.f * ci : 2.f * cr, my = prm.swapped ? 2.f * cr : -2.f * ci;
            reinterpret_cast<uint32_t*>(smem + OFF_M)[at] = pack_bf(mx, my);
#pragma unroll
            for (int i = 0; i < 5; i++) pw = cmul(pw, pw);
#pragma unroll
            for (int i = 0; i < 2; i++) {
                const float2 p2 = cmul(pw, pw);
                ct[128 + 384 * i] = pw; ct[256 + 384 * i] = p2; ct[384 + 384 * i] = cmul(p2, pw);
                pw = cmul(p2, p2);
            }
            ct[896] = pw;
            mbar_wait(bar_epoch);
            __syncwarp();
            mbar_wait(empty + 8 * TN(RS_E));
            st_relaxed2(&prm.s->hid[cta * 128 + at], ~0u, ~0u);
            st_relaxed4(&prm.s->y[((at >> 4) * 8 + (cta >> 4)) * D_ + (cta & 15) * 64 + (at & 15) * 4], 0u, 0u, 0u, 0u);
            st_relaxed2(&prm.s->carry[chunk * 1024 + pc], 0u, 0u);
            __syncwarp();
            if (lane == 0) mbar_arrive(bar_const);

            STAMPIF(at == 0, 3);
            mbar_wait(bar_const);
            constants(0);
            constants(1);
            mbar_wait(bar_order);
        }

        float accA[64], accB[64];
        run_entries<0>(sb, wg * 16, wg * 16 + 15, wg, accA, accB, [&](int i) {
            if (i == GE - 1) {
                mbar_wait(bar_base);
                const uint32_t t = lds32(sb + OFF_EPOCH + 8) + TN(GT0);
                const int late = clk32() - t - TN(GL);
                sched_fence(late < 0 ? t : t + TN(GL) + 256 + (late | TN(GQ)));
            }
        });
        mbar_wait(full + 8 * (wg * 16 + 15));
        KSTAMP(wg * 16 + 15);
        if (wg == 0) {
            mbar_wait(bar_const);
            run_entry<0>(make_desc(sb), empty + 8 * 14, 1, accA, accB, [&]() { constants(0); constants(1); });
            if (lane == 0) mbar_arrive(bar_order);
        } else run_entry<0>(make_desc(sb + SLOT), empty + 8 * 30, 1, accA, accB, [&]() { if (lane == 0) mbar_arrive(bar_order + 8); });
        uint2 v[4];
#pragma unroll
        for (int m = 0; m < 4; m++) v[m] = make_uint2(t2, t2);
        wgmma_wait<0>();
        pin64(accA); pin64(accB);
        if (lane == 0) mbar_arrive(empty + 8 * (wg * 16 + 15));
        LSTAMP(at == 0, 96 + 30 + 10 * wg); GSTAMP(LT && at == 0, 193 + wg);

        auto cut = [&]() { if (never) sched_fence(cstart); };
        auto poll = [&](int h) {
#pragma unroll
            for (int m = 0; m < 4; m++)
                asm volatile("{ .reg .pred p; setp.ge.s32 p, %3, %4; @p ld.relaxed.gpu.global.v2.b32 {%0, %1}, [%2]; }"
                             : "+r"(v[m].x), "+r"(v[m].y) : "l"(cq + 256 * h - 4096 * m), "r"(j1), "r"(4 * m) : "memory");
        };
        auto valid = [&]() {
            uint32_t bad = 0;
#pragma unroll
            for (int m = 0; m < 4; m++) bad |= (v[m].x ^ t2) | (v[m].y ^ t2);
            return __all_sync(0xffffffffu, (bad & 3u) == 0);
        };
        float2 w0[2];
        uint32_t tp;
#pragma unroll
        for (int h = 0; h < 2; h++) {
            float (&acc)[64] = h ? accB : accA;
            float2 e = make_float2(acc[0], acc[2]);
#pragma unroll
            for (int s = 1; s < 32; s++) {
                const int i0 = 4 * (s >> 1) + (s & 1);
                e = cfma(a[h], e, make_float2(acc[i0], acc[i0 + 2]));
            }
            float2 y = make_float2(__shfl_up_sync(0xffffffffu, e.x, 1, 4), __shfl_up_sync(0xffffffffu, e.y, 1, 4));
            if (c >= 1) e = cfma(a32[h], y, e);
            y = make_float2(__shfl_up_sync(0xffffffffu, e.x, 2, 4), __shfl_up_sync(0xffffffffu, e.y, 2, 4));
            if (c >= 2) e = cfma(a64[h], y, e);
            if (c == 3) st_relaxed2(cq + 4096 + 256 * h, (__float_as_uint(e.x) & ~3u) | t2, (__float_as_uint(e.y) & ~3u) | t2);
            if (h == 0) tp = clk32();
            cut();
            w0[h] = make_float2(__shfl_up_sync(0xffffffffu, e.x, 1, 4), __shfl_up_sync(0xffffffffu, e.y, 1, 4));
            STAMPIF(at == 0, 31 + h + 10 * wg);
        }
        uint32_t sx[2][16], sy[2][16], mr[2][4];
        const uint32_t gap = wg ? TN(GAP1) : TN(GAP0);
#pragma unroll
        for (int h = 0; h < 2; h++) {
            const uint32_t sg = prm.swapped ? 0x80008000u : 0u;
            mr[h][0] = __byte_perm(mm[h], 0, 0x1010); mr[h][1] = __byte_perm(mm[h], 0, 0x3232);
            mr[h][2] = mr[h][1] ^ sg; mr[h][3] = mr[h][0] ^ sg ^ 0x80008000u;
        }
        auto put = [&](int e, int j) {
            uint32_t d[4];
#pragma unroll
            for (int u = 0; u < 4; u++) d[u] = fma_bf2(mr[e >> 1][2 * (e & 1)], sx[e >> 1][4 * j + u], mul_bf2(mr[e >> 1][2 * (e & 1) + 1], sy[e >> 1][4 * j + u]));
            #pragma unroll
            for (int u = 0; u < 2; u++)
                asm("lop3.b32 %0, %0, %1, %2, 0xD8;" : "+r"(d[2 * (j & 1) + u]) : "r"(par), "r"((uint32_t)((w & 1) == u)));
            stg128(hd + e * 65536 + (j >> 1) * 8192 + (j & 1) * 512, d[0], d[1], d[2], d[3]);
            if (j == 3 && lane == 0) mbar_arrive(bar_out + 32 * wg + 8 * e);
        };
#pragma unroll
        for (int h = 0; h < 2; h++) {
            float (&acc)[64] = h ? accB : accA;
            uint32_t it = 0;
            if (h == 0) {
                sleep_until(tp + (wg ? TN(T_CP1) : TN(T_CP0)));
                poll(h);
            }
            while (!valid()) {
                if (++it > SPIN_LIMIT) __trap();
#pragma unroll
                for (int m = 0; m < 4; m++)
                    asm volatile("{ .reg .pred p; setp.ne.u32 p, %3, 0; @p ld.relaxed.gpu.global.v2.b32 {%0, %1}, [%2]; }"
                                 : "+r"(v[m].x), "+r"(v[m].y) : "l"(cq + 256 * h - 4096 * m), "r"(((v[m].x ^ t2) | (v[m].y ^ t2)) & 3u) : "memory");
            }
            float2 hin = make_float2(__uint_as_float(v[3].x), __uint_as_float(v[3].y));
#pragma unroll
            for (int m = 2; m >= 0; m--) hin = cfma(a512[h], hin, make_float2(__uint_as_float(v[m].x), __uint_as_float(v[m].y)));
            STAMPIF(at == 0 && it > 0 && h == 0, 39 + 10 * wg);
            if (c) hin = cmul(pw128[h], hin);
            hin.x += __shfl_xor_sync(0xffffffffu, hin.x, 1); hin.y += __shfl_xor_sync(0xffffffffu, hin.y, 1);
            hin.x += __shfl_xor_sync(0xffffffffu, hin.x, 2); hin.y += __shfl_xor_sync(0xffffffffu, hin.y, 2);
            float2 st = hin;
            if (c) st = cfma(pw32[h], hin, w0[h]);
            STAMPIF(at == 0, 33 + 3 * h + 10 * wg);
#pragma unroll
            for (int j = 0; j < 4; j++) {
#pragma unroll
                for (int u = 0; u < 4; u++) {
                    const int i0 = 16 * j + 4 * u;
                    const float2 y = cfma(a[h], st, make_float2(acc[i0], acc[i0 + 2]));
                    st = cfma(a[h], y, make_float2(acc[i0 + 1], acc[i0 + 3]));
                    sx[h][4 * j + u] = pack_bf(y.x, st.x); sy[h][4 * j + u] = pack_bf(y.y, st.y);
                }
                if (h) sleep_until(tp += gap);
                if (h == 0 && j == 1) poll(1);
                put(2 * h, j);
                cut();
            }
            STAMPIF(at == 0, 34 + 3 * h + 10 * wg);
            tp = clk32();
#pragma unroll
            for (int j = 0; j < 4; j++) {
                sleep_until(tp += gap);
                put(2 * h + 1, j);
            }
        }
        STAMPIF(at == 0, 38 + 10 * wg);

        if (wg == 1) {
            const char* src = reinterpret_cast<const char*>(prm.s->h) + (size_t)chunk * 524288;
            uint32_t rpar = 1;
#pragma unroll 1
            for (int n = w; n < 2 * NSPL; n += 4) {
                mbar_wait(empty + 8 * (NBIG - 7 + n));
                mbar_wait(hfull + 8 * (NST + n % 7), n / 7 & 1);
                const uint32_t dst = sb + tail_h(n);
                rpar = check_tile<8>(sb, dst, probe, src + tail_src(n), par, full + 8 * w, rpar, TN(T_RETRY));
                if (lane == 0) mbar_expect_tx(full + 8 * (NBIG + n), n < NSPL ? 2 * TILE : 0);
            }
        } else {
            asm volatile("setmaxnreg.inc.sync.aligned.u32 216;");
            const int tl = 64 * (w & 1) + 8 * (w >> 1) + g;
            float gf[4];
            float* op = prm.out + (size_t)(chunk * 128 + tl) * D_ + dt * 128 + 4 * c;
            const int xr = 2 * (g & 3) + (g >> 2);
            uint32_t xs = sb + (32 * (w & 1) + 8 * (w >> 1) + xr) * 128 + (((c >> 1) ^ xr) << 4) + (c & 1) * 8;
            uint32_t gs = sb + OFF_G + 2 * tl;
            asm volatile("" : "+r"(gs), "+l"(op), "+r"(xs));
            float outA[64], outB[64];
            STAMPIF(at == 0, 9);
            mbar_wait(bar_order + 8);
            STAMPIF(at == 0, 35);
            run_entries<1>(sb, 32, NBIG, 32 % NST, outA, outB, [](int) {});
            uint32_t gp[4], om[4];
            uint2 xt[4][8], dk[8];
            auto load_x = [&](int q, int j) {
#pragma unroll
                for (int r = 0; r < 2; r++) xt[2 * q + r][j] = lds64((xs ^ ((j & 3) << 5)) + (q ? tail_c(0) : OFF_FT) + (j >> 2) * TILE + r * 2048);
                if (q == 0) dk[j] = lds64(sb + OFF_DK + c * 8 + 32 * j);
            };
            auto term = [&](int q, int j) {
#pragma unroll
                for (int r = 2 * q; r < 2 * q + 2; r++) {
                    xt[r][j].x = mul_bf2(xt[r][j].x, fma_bf2(gp[r], dk[j].x, om[r]));
                    xt[r][j].y = mul_bf2(xt[r][j].y, fma_bf2(gp[r], dk[j].y, om[r]));
                }
            };
            auto store = [&](int q, int u0, int u1) {
                const float (&acc)[64] = q ? outB : outA;
#pragma unroll
                for (int u = u0; u < u1; u++) {
                    const int j = u >> 1, r = u & 1;
                    const int o = 8 * j + 2 * r;
                    const float gv = fabsf(gf[2 * q + r]);
                    const uint2 t = xt[2 * q + r][j];
                    stg128(op + (r * 32 + q * 16) * D_ + 16 * j, __float_as_uint(fmaf(gv, acc[o], bf_lo(t.x))), __float_as_uint(fmaf(gv, acc[o + 1], bf_hi(t.x))),
                           __float_as_uint(fmaf(gv, acc[o + 4], bf_lo(t.y))), __float_as_uint(fmaf(gv, acc[o + 5], bf_hi(t.y))));
                }
            };
            uint64_t dh = desc64<1>(make_desc_h(sb)), dc = desc64<0>(make_desc(sb));
#pragma unroll
            for (int n = 0; n < 2 * NSPL; n++) {
                const int j = n % NSPL;
                if (n == 0) mbar_wait(bar_g);
                if (n == X0 || n == 2 * NSPL - 1) mbar_wait(bar_x + (n == X0 ? 0 : 8));
                mbar_wait(full + 8 * (NBIG + n));
                KSTAMP(NBIG + n);
                asm volatile("mov.b64 %0, %0; mov.b64 %1, %1;" : "+l"(dh), "+l"(dc));
                const uint64_t da = dh + (tail_h(n) >> 4), db = dc + (tail_c(j) >> 4);
                const int xj = n - X0;
                wgmma_fence();
#pragma unroll
                for (int kk = 0; kk < 4; kk++) {
                    wgmma_n128<1>(n < NSPL ? outA : outB, da + kk * 128, db + kk * 2);
                    if (kk == 0 && n == 0) {
#pragma unroll
                        for (int r = 0; r < 4; r++) {
                            uint32_t u;
                            asm volatile("ld.shared.u16 %0, [%1];" : "=r"(u) : "r"(gs + (r & 1) * 64 + (r >> 1) * 32) : "memory");
                            gf[r] = bf_lo(u);
                        }
                    }
                    if (kk == 0 && xj >= 0 && xj < 8) load_x(0, xj);
                    if (kk == 0 && n == 2 * NSPL - 1) load_x(1, 0);
                }
                wgmma_commit();
                if (n <= 2 * NSPL - 7) {
                    wgmma_wait<1>();
                    if (lane == 0) mbar_arrive(empty + 8 * (NBIG + n - 1));
                    if (!j) { LSTAMP(at == 0, 96 + 12 + n / NSPL); GSTAMP(LT && at == 0, 195 + n / NSPL); }
                } else cut();
                if (n == 0) {
#pragma unroll
                    for (int r = 0; r < 4; r++) {
                        const bool routed = (int)__float_as_uint(gf[r]) < 0;
                        gp[r] = routed ? 0u : pack_bf(gf[r], gf[r]); om[r] = routed ? 0u : pack_bf(1.0f - gf[r], 1.0f - gf[r]);
                    }
                }
                if (xj >= 0 && xj < 8) term(0, xj);
                if (n == NSPL) pin64(outA);
                if (n >= NSPL) store(0, (j * 16 + 4) / NSPL, j == NSPL - 1 ? 16 : ((j + 1) * 16 + 4) / NSPL);
            }
            term(1, 0);
            cut();
            wgmma_wait<0>();
            pin64(outB);
            LSTAMP(at == 0, 96 + 51); GSTAMP(LT && at == 0, 197);
#pragma unroll
            for (int j = 1; j < 8; j++) load_x(1, j);
            store(1, 0, 2);
#pragma unroll
            for (int j = 1; j < 8; j++) {
                cut();
                term(1, j);
                store(1, 2 * j, 2 * j + 2);
            }
            __syncwarp();
            if (lane == 0) mbar_arrive(bar_stored);
            LSTAMP(at == 0, 96 + 52);
        }
    } else if (warp < 12) {
        asm volatile("setmaxnreg.dec.sync.aligned.u32 64;");
        init_barriers(empty + min(80 + 160 * w, 8 * 67), 4, []() { return 20; });
#pragma unroll
        for (int i = 0; i < 2; i++) sts128(sb + OFF_LIST + i * 2048 + at * 16, 0u, 0u, 0u, 0u);
        uint32_t* keys = reinterpret_cast<uint32_t*>(smem + OFF_KEYS);
        keys[4] = 0;
        named_bar(0, 448);
        if (at < 24) st_relaxed(at < 8 ? &prm.s->key[kslot * 8 + at] : &prm.s->gate[rid * 16 + at - 8], 0u);
        mbar_wait(bar_epoch);
        const uint32_t t2 = lds32(sb + OFF_EPOCH + 4);
        STAMPIF(at == 0, 20);
        float facc[4];
        const uint32_t dft = make_desc(sb + OFF_FT), dxs = make_desc(sb + OFF_XS);
#pragma unroll 1
        for (int u = 0; u < 4; u++) {
            mbar_wait(ffull + 8 * u);
            STAMPIF(at == 0, 4 + u);
            wgmma_fence();
            small_tile<0>(facc, dft + u * (TILE >> 4), dxs + u * 64, u == 0);
            wgmma_commit();
        }
        wgmma_wait<0>();
        pin4(facc);
        if (lane < 4) mbar_arrive(fempty + 8 * lane);
        auto gate_up = [&](auto rest) {
            uint32_t slot = 4, par = 0, prev = full + 8 * 101, e4 = 4 * TN(GC0);
#pragma unroll 1
            for (int j = 0; j < 14; j++) {
                if (j == 2) rest();
                STAMPW(at == 0, 75 + j);
                mbar_wait(ffull + 8 * slot, par);
                STAMPW(at == 0, 160 + j);
                mbar_wait(empty + 8 * (e4 >> 2));
                e4 += j < 8 ? TN(GCS) : TN(GCS4);
                wgmma_fence();
                small_tile<1>(facc, dft + slot * (TILE >> 4), dxs + j * 64, j == 0);
                wgmma_commit();
                wgmma_wait<1>();
                if (lane == 0) mbar_arrive(prev);
                prev = fempty + 8 * slot;
                if (++slot == NFT) { slot = 0; par ^= 1; }
            }
            wgmma_wait<0>();
            if (lane == 0) mbar_arrive(prev);
            pin4(facc);
        };
        auto help = [&]() {
            uint32_t slot = 4, par = 0, e4 = 4 * TN(GC0);
#pragma unroll 1
            for (int u = 0; u < 7; u++) {
                const uint32_t slot2 = slot == NFT - 1 ? 0 : slot + 1;
                mbar_wait(ffull + 8 * slot, par);
                par ^= slot2 == 0;
                mbar_wait(ffull + 8 * slot2, par);
                mbar_wait(empty + 8 * (e4 >> 2));
                e4 += TN(GCH);
                wgmma_fence();
                small_tile<1>(facc, dft + slot * (TILE >> 4), dxs, true);
                small_tile<1>(facc, dft + slot2 * (TILE >> 4), dxs + 64, false);
                wgmma_commit();
                wgmma_wait<0>();
                pin4(facc);
                if (lane < 2) mbar_arrive(fempty + 8 * (lane ? slot2 : slot));
                st_relaxed4(&prm.s->part[((cta - 112) * 7 + u) * 128 + at], (__float_as_uint(facc[0]) & ~3u) | t2, __float_as_uint(facc[1]),
                            __float_as_uint(facc[2]), __float_as_uint(facc[3]));
                slot = slot2 == NFT - 1 ? 0 : slot2 + 1;
                par ^= slot == 0;
            }
        };
        auto down = [&]() {
            const uint32_t dhid = make_desc(sb + OFF_HID);
#pragma unroll 1
            for (int j = 0; j < 7; j++) {
                mbar_wait(dfull + 8 * j);
                wgmma_fence();
                small_tile<1>(facc, dft + j * (TILE >> 4), dhid + j * 64, j == 0);
                wgmma_commit();
                if ((0x52 >> j) & 1) {
                    wgmma_wait<0>();
                    if (lane == 0) mbar_arrive(bar_dfree + 8 * (j / 3));
                }
            }
            wgmma_wait<0>();
            pin4(facc);
        };
        if ((c & 1) == (w >> 1)) {
            float* red = reinterpret_cast<float*>(smem + OFF_RED) + w * 32 + (c >> 1) * 16 + g;
            red[0] = (w & 1) ? facc[1] : facc[0];
            red[8] = (w & 1) ? facc[3] : facc[2];
        }
        named_bar(2, 128);
        STAMPIF(at == 0, 21);
        const uint32_t tpub = clk32();
        if (w < 2) {
            const float* red = reinterpret_cast<const float*>(smem + OFF_RED) + w * 16 + (lane & 15);
            const float v = rbf((red[0] + red[32]) + (red[64] + red[96]));
            if (w == 0) {
                uint32_t k = __float_as_uint(v);
                k = ((k ^ ((uint32_t)((int)k >> 31) | 0x80000000u)) & 0xFFFF0000u) | (t2 << 11) | (2047u - (uint32_t)(rid * 16 + (lane & 15)));
                int rank = 0;
#pragma unroll
                for (int i = 0; i < 8; i++) rank += __shfl_sync(0xffffffffu, k, (lane >> 4) * 8 + i) > k;
                rank += __shfl_xor_sync(0xffffffffu, rank, 16);
                if (rank < 8) st_relaxed(&prm.s->key[kslot * 8 + rank], k);
            } else if (lane < 16) st_relaxed(&prm.s->gate[rid * 16 + lane], __float_as_uint(rbf(sigmoidf_(v))) | t2);
            __syncwarp();
        }
        uint32_t it = 0;
        uint4 ka, kb4;
        mbar_wait(bar_base);
        sleep_until(lds32(sb + OFF_EPOCH + 8) + TN(GT1));
        sleep_until(tpub + TN(G0));
        bool bad = true;
        while (true) {
            if (bad) {
                ka = ld_relaxed4(&prm.s->key[at * 8]);
                kb4 = ld_relaxed4(&prm.s->key[at * 8 + 4]);
            }
            bad = (((ka.x ^ (t2 << 11)) | (kb4.x ^ (t2 << 11))) & 0x1800u) != 0;
            if (!__any_sync(0xffffffffu, bad)) break;
            if (++it > SPIN_LIMIT) __trap();
            __nanosleep(TN(T_RETRY));
        }
        STAMPIF(at == 0, 22);
        STAMPIF(at == 0 && it > 0, 23);
        const uint32_t m1 = __reduce_max_sync(0xffffffffu, ka.x), m2 = __reduce_max_sync(0xffffffffu, ka.x == m1 ? ka.y : ka.x);
        if (lane == 0) keys[w] = m2;
        named_bar(2, 128);
        const uint4 th4 = *reinterpret_cast<const uint4*>(keys);
        const uint32_t th = min(min(th4.x, th4.y), min(th4.z, th4.w));
        {
            const uint32_t k8[8] = {ka.x, ka.y, ka.z, ka.w, kb4.x, kb4.y, kb4.z, kb4.w};
            auto append = [&](int lo, int hi) {
                uint32_t n = 0, pos = 0;
#pragma unroll
                for (int i = lo; i < hi; i++) n += k8[i] >= th;
                asm volatile("{ .reg .pred p; setp.ne.u32 p, %2, 0; @p atom.shared.add.u32 %0, [%1], %2; }" : "+r"(pos) : "r"(sb + OFF_KEYS + 16), "r"(n) : "memory");
#pragma unroll
                for (int i = lo; i < hi; i++)
                    if (k8[i] >= th) reinterpret_cast<uint32_t*>(smem + OFF_LIST)[pos + i - lo] = k8[i];
            };
            append(0, 2);
            if (__any_sync(0xffffffffu, k8[2] >= th)) append(2, 8);
        }
        named_bar(2, 128);
        {
            const uint32_t* list = reinterpret_cast<const uint32_t*>(smem + OFF_LIST);
            const int n = (int)keys[4];
#pragma unroll 1
            for (int i0 = w * 32; i0 < n; i0 += 128) {
                const uint32_t k = list[i0 + lane];
                int rank = 0;
#pragma unroll 2
                for (int o = 0; o < n; o += 4) {
                    const uint4 l4 = *reinterpret_cast<const uint4*>(list + o);
                    rank += (l4.x > k) + (l4.y > k) + (l4.z > k) + (l4.w > k);
                }
                if (rank < 8) reinterpret_cast<uint32_t*>(smem + OFF_SEL)[rank] = k;
            }
        }
        named_bar(2, 128);
        STAMPIF(at == 0, 24);
        const uint32_t* sel = reinterpret_cast<const uint32_t*>(smem + OFF_SEL);
        auto gates = [&]() {
            uint32_t gv;
            it = 0;
            while (true) {
                gv = ld_relaxed(&prm.s->gate[chunk * 128 + at]);
                const uint32_t ar = ld_relaxed(&prm.s->armed[((cta >> 4) * 14 + min(lane, 13)) * 4]);
                if (__all_sync(0xffffffffu, (gv & 3u) == t2 && ar == t2)) break;
                if (++it > SPIN_LIMIT) __trap();
            }
            asm volatile("fence.acquire.gpu;" ::: "memory");
#pragma unroll
            for (int s = 0; s < 8; s++)
                if ((~sel[s] & 2047u) == (uint32_t)(chunk * 128 + at)) gv |= 0x80000000u;
            reinterpret_cast<uint16_t*>(smem + OFF_G)[at] = (uint16_t)(gv >> 16);
            __syncwarp();
            if (lane == 0) mbar_arrive(bar_g);
        };
        {
            const int tk = (at >> 3) & 7;
            const char* xt = (const char*)prm.x + (~sel[tk] & 2047u) * 2048 + (owner ? 256 : 0) + (at >> 6) * 128 + (at & 7) * 16;
#pragma unroll
            for (int i = 0; i < 7; i++) {
                if (i == 0 || owner) cp_async16(sb + OFF_XS + (2 * i + (at >> 6)) * 1024 + tk * 128 + (((at & 7) ^ tk) << 4), xt + i * 256);
                if (i == 0 || i == 6) asm volatile("cp.async.commit_group;" ::: "memory");
            }
            asm volatile("cp.async.wait_group 1;" ::: "memory");
            fence_async_smem();
            named_bar(2, 128);
            STAMPIF(at == 0, 25);
        }
        if (!owner) help();
        else {
            gate_up([&]() {
                asm volatile("cp.async.wait_all;" ::: "memory");
                fence_async_smem();
                named_bar(2, 128);
            });
            it = 0;
            while (true) {
                const uint4 v = ld_relaxed4(&prm.s->part[cta * 128 + at]);
                if (__all_sync(0xffffffffu, (v.x & 3u) == t2)) {
                    facc[0] += __uint_as_float(v.x); facc[1] += __uint_as_float(v.y); facc[2] += __uint_as_float(v.z); facc[3] += __uint_as_float(v.w);
                    break;
                }
                if (++it > SPIN_LIMIT) __trap();
                __nanosleep(TN(T_RETRY));
            }
            if (!(cta & 1)) {
#pragma unroll
                for (int u = 0; u < 4; u++) {
                    const float v = rbf(facc[u]);
                    facc[u] = __fdividef(v, 1.0f + __expf(-v));
                }
            }
            st_relaxed2(&prm.s->hid[cta * 128 + at], pack_bf(facc[0], facc[1]), pack_bf(facc[2], facc[3]));
        }
        STAMPIF(at == 0, 26);
        gates();
        uint32_t mine = __ballot_sync(0xffffffffu, lane < 8 && (int)((~sel[lane & 7] & 2047u) >> 7) == chunk), tr;
        uint2 xr, xd;
        float gr, rs;
        auto skip = [&](int n) {
#pragma unroll 1
            for (int i = 0; i < n; i++) mine &= mine - 1;
            if (mine) {
                const uint32_t key = sel[__ffs(mine) - 1], kb = key >> 16;
                tr = ~key & 2047u;
                xr = __ldg(reinterpret_cast<const uint2*>(prm.x + (size_t)tr * D_ + dt * 128) + lane);
                rs = rbf(sigmoidf_(bf_lo((kb & 0x8000u) ? (kb & 0x7FFFu) : (~kb & 0xFFFFu))));
                gr = fabsf(__bfloat162float(reinterpret_cast<const __nv_bfloat16*>(smem + OFF_G)[tr & 127]));
                xd = lds64(sb + OFF_DK + 8 * lane);
            }
        };
        mbar_wait(bar_g);
        skip(w);
        {
            mbar_wait(empty + 8 * max(TN(HG), 31));
            const uint2* hp = &prm.s->hid[(cta >> 4) * 14 * 128 + at];
            uint32_t hv[16];
            it = 0;
            while (true) {
                uint32_t top = 0;
#pragma unroll
                for (int j = 0; j < 7; j++) {
                    const uint2 hg = ld_relaxed2(hp + 256 * j), hu = ld_relaxed2(hp + 256 * j + 128);
                    top = max(top, max(hg.x, hu.x));
                    hv[2 * j] = mul_bf2(hg.x, hu.x); hv[2 * j + 1] = mul_bf2(hg.y, hu.y);
                }
                if (__all_sync(0xffffffffu, top != ~0u)) break;
                do {
                    if (++it > SPIN_LIMIT) __trap();
                } while (!__all_sync(0xffffffffu, ld_relaxed(hp + min(lane, 13) * 128 - lane) != ~0u));
            }
            STAMPIF(at == 0 && it > 0, 61);
            hv[14] = hv[15] = 0;
#pragma unroll
            for (int j = 0; j < 4; j++)
                asm volatile("stmatrix.sync.aligned.m8n8.x4.trans.shared.b16 [%0], {%1, %2, %3, %4};" ::"r"(
                                 sb + OFF_HID + (2 * j + (lane >> 4)) * 1024 + (lane & 7) * 128 + (((2 * w + ((lane >> 3) & 1)) ^ (lane & 7)) << 4)),
                             "r"(hv[4 * j]), "r"(hv[4 * j + 1]), "r"(hv[4 * j + 2]), "r"(hv[4 * j + 3]) : "memory");
        }
        fence_async_smem();
        named_bar(2, 128);
        STAMPIF(at == 0, 27);
        down();
#pragma unroll
        for (int u = 0; u < 4; u++)
            st_relaxed(&prm.s->y[((2 * c + (u & 1)) * 8 + (cta >> 4)) * D_ + (cta & 15) * 64 + w * 16 + g + 8 * (u >> 1)], (__float_as_uint(facc[u]) & ~3u) | t2);
        STAMPIF(at == 0, 28);
        sleep_until(clk32() + TN(T_Y));
        while (mine) {
            const uint32_t* yp = &prm.s->y[(__ffs(mine) - 1) * 8 * D_ + dt * 128 + 4 * lane];
            float y[4];
            it = 0;
            while (true) {
                uint32_t bad = 0;
                y[0] = y[1] = y[2] = y[3] = 0.f;
#pragma unroll
                for (int ks = 0; ks < 8; ks++) {
                    const uint4 v = ld_relaxed4(yp + ks * D_);
                    bad |= v.x ^ t2;
                    y[0] += __uint_as_float(v.x); y[1] += __uint_as_float(v.y); y[2] += __uint_as_float(v.z); y[3] += __uint_as_float(v.w);
                }
                if (__all_sync(0xffffffffu, (bad & 3u) == 0)) break;
                if (++it > SPIN_LIMIT) __trap();
            }
            STAMPIF(lane == 0 && it, 62);
#pragma unroll
            for (int u = 0; u < 4; u++) {
                const uint32_t x2 = (u & 2) ? xr.y : xr.x, d2 = mul_bf2(x2, (u & 2) ? xd.y : xd.x);
                y[u] = fmaf(gr, (u & 1) ? bf_hi(d2) : bf_lo(d2), rbf(rbf(1.0f - gr) * rbf(((u & 1) ? bf_hi(x2) : bf_lo(x2)) + rbf(rbf(y[u]) * rs))));
            }
            STAMPIF(lane == 0, 50);
            mbar_wait(bar_stored);
            asm volatile("red.global.add.v4.f32 [%0], {%1, %2, %3, %4};" ::"l"(prm.out + (size_t)tr * D_ + dt * 128 + 4 * lane), "f"(y[0]), "f"(y[1]), "f"(y[2]), "f"(y[3]) : "memory");
            skip(4);
        }
        LSTAMP(lane == 0, 96 + 29);
    } else {
        asm volatile("setmaxnreg.dec.sync.aligned.u32 40;");
        if (warp != 12) sleep_until(cstart + (warp == 13 ? TN(T_SMALL) : warp == 14 ? TN(PF0) - 250 : TN(T_W3)));
        auto behind = [&](int e) {
            if (!mbar_test(empty + 8 * e, 0)) {
                mbar_wait(empty + 8 * e);
                if (TN(T_X0)) sleep_until(clk32() + TN(T_X0));
            }
        };
        if (warp == 15) {
            prefetch_map(&mXr);
            named_bar(0, 448);
            asm volatile("bar.arrive 1, 64;" ::: "memory");
#pragma unroll 1
            for (int i = 0; i < 4; i++) {
                const int u = i;
                if (lane == 0) mbar_expect_tx(ffull + 8 * u, TILE);
                sleep_until(cstart + (i == 0 ? TN(RT0) : i == 1 ? TN(RT1) : i == 2 ? TN(RT2) : TN(RT3)));
                if (elect_one()) tma3(sb + OFF_FT + u * TILE, &mXr, u * 256, rid * 16, ffull + 8 * u);
                STAMP(53 + u);
            }
            if (sb & 1023) __trap();
            prefetch_map(&mWg);
            prefetch_map(&mWu);
            prefetch_map(&mWd);
            uint32_t slot = 4, par = 1;
#pragma unroll 1
            for (int j = 0; j < (DBG != 1 ? 14 : 0); j++) {
                const int o = owner ? cta : (cta - 112) * 7 + (j >> 1);
                mbar_wait(fempty + 8 * slot, par);
                if (lane == 0) mbar_expect_tx(ffull + 8 * slot, TILE);
                if (j < NFT) behind(TN(GU_E0) + j * TN(W_NUM) / 4);
                STAMPW(1, 176 + j);
                if (elect_one()) tma2(sb + OFF_FT + slot * TILE, (o & 1) ? &mWu : &mWg, (o >> 1) * 64, (owner ? j + 2 : j & 1) * 64, ffull + 8 * slot);
                if (++slot == NFT) { slot = 0; par ^= 1; }
            }
            if (lane < 9) mbar_expect_tx(lane < 7 ? dfull + 8 * lane : bar_x + 8 * (lane - 7), lane < 7 ? TILE : 2 * TILE);
#pragma unroll 1
            for (int j = 0; j < (DBG != 1 ? 7 : 0); j++) {
                if (j < 3) mbar_wait(fempty + 8 * j, 1);
                behind(min(TN(DL0) + j * TN(DLS) / 4, NBIG - 2));
                if (elect_one()) tma2(sb + OFF_FT + j * TILE, &mWd, (cta & 15) * 64, (cta >> 4) * 448 + j * 64, dfull + 8 * j);
            }
            prefetch_map(&mXe);
#pragma unroll 1
            for (int u = 0; u < 4; u++) {
                if (u == 2) {
                    mbar_wait(bar_dfree + 16);
                    if (elect_one()) tma5(sb + tail_c(8), &mCim, c_col(63), dt * 8, full + 8 * (NBIG + 8));
                }
                mbar_wait(bar_dfree);
                behind(u < 2 ? TN(DN_E0) + u : NBIG + NSPL);
                if (elect_one())
                    asm volatile("cp.async.bulk.tensor.5d.shared::cluster.global.mbarrier::complete_tx::bytes [%0], [%1, {%3, %6, %6, %4, %5}], [%2];"
                                 ::"r"(sb + (u < 2 ? OFF_FT : tail_c(0)) + (u & 1) * TILE), "l"(&mXe), "r"(bar_x + 4 * (u & 2)), "r"(dt * 128 + (u & 1) * 64),
                                 "r"(u & 2), "r"(chunk * 4), "r"(0) : "memory");
                if (u < 2) {
                    if (elect_one())
                        asm volatile("cp.async.bulk.prefetch.tensor.5d.L2.global [%0, {%1, %4, %4, %2, %3}];" ::"l"(&mXe), "r"(dt * 128 + u * 64), "r"(2), "r"(chunk * 4), "r"(0) : "memory");
                }
            }
        } else if (warp == 13) {
#pragma unroll
            for (int u = 0; u < 8; u++) {
                const int row = (u >> 2) * 4 + (lane >> 3);
                cp_async16(sb + OFF_XS + (u & 3) * 1024 + row * 128 + (((lane & 7) ^ row) << 4), (const char*)(u < 4 ? prm.w_r : prm.gate_w) + (u & 3) * 512 + lane * 16);
            }
            STAMP(57);
            const uint32_t tag = ld_relaxed(&prm.s->epoch[cta]) + 1;
            named_bar(1, 64);
            *reinterpret_cast<uint2*>(smem + OFF_EPOCH) = make_uint2(tag, tag % 3u + 1u);
            STAMPIF(tag, 58);
            asm volatile("cp.async.wait_all;" ::: "memory");
            STAMP(59);
            fence_async_smem();
            __syncwarp();
            if (lane == 0) {
                mbar_arrive(bar_epoch);
                prm.s->epoch[cta] = tag;
            }
            sleep_until(cstart + TN(T_BASE));
            {
                const uint2 st = ld_relaxed2(&prm.s->start[2 * lane]);
                const uint32_t d = st.x - cstart + 512u, age = gtime32() - st.y;
                const uint32_t m = __reduce_max_sync(0xffffffffu, d < 1024u && age < 4096u ? (d << 12) | age : 0u);
                const uint32_t late = (m & 4095u) - __reduce_min_sync(0xffffffffu, age);
                *reinterpret_cast<volatile uint32_t*>(smem + OFF_EPOCH + 8) = cstart + (m ? (m >> 12) - 512u + min(late, 256u) * TN(G_NS) / 4 : 0u);
                __syncwarp();
                if (lane == 0) mbar_arrive(bar_base);
                STAMP(60);
            }
            mbar_wait(bar_const);
            asm volatile("fence.acq_rel.gpu;" ::: "memory");
            if (lane < 4) st_relaxed2(&prm.s->armed[cta * 4 + lane], tag % 3u + 1u, 0u);
            prefetch_map(&mCre);
            prefetch_map(&mCim);
            const char* src = reinterpret_cast<const char*>(prm.s->h) + (size_t)chunk * 524288;
            uint32_t slot = 32 % NST, hpar = 0, rpar = 0;
#pragma unroll 1
            for (int i = 32; i < NBIG; i++) {
                mbar_wait(hfull + 8 * slot, hpar);
                STAMPIF(i == 32 || i == 33, 14 + (i & 1));
                rpar = check_tile<16>(sb, sb + slot * SLOT, probe, src, tag, bar_retry, rpar, TN(T_RETRY));
                if (lane == 0) mbar_expect_tx(full + 8 * i, 2 * TILE);
                STAMPIF(i == 32 || i == 33, 16 + (i & 1));
                src += 2 * TILE;
                slot = slot == NST - 1 ? 0 : slot + 1;
                hpar ^= slot == 32 % NST;
            }
        } else if (warp == 14) {
            prefetch_map(&mPB);
            auto pf_c = [&](int k) { prefetch_slice(&mPC, 4 * (k >> 1), cta * 8 + (k & 1) * 4); };
            {
                const char* px = (const char*)prm.x + (rid * 16 + (lane >> 1)) * 2048 + (lane & 1) * 128;
                const char* pb = (const char*)((lane & 8) ? prm.b_im : prm.b_re) + (cta * 4 + ((lane >> 1) & 3)) * 2048 + (lane & 1) * 128;
#pragma unroll 1
                for (int k = 1; k < 8; k++) {
                    sleep_until(cstart + TN(PF0) + (k - 1) * TN(PF1));
                    prefetch_l2(px + k * 256);
                    if (lane < 16) prefetch_l2(pb + k * 256);
                }
            }
            named_bar(7, 160);
            mbar_wait(bar_base);
#pragma unroll 1
            for (int k = 0; k < 4; k++) {
                behind(TN(PB_E0) + TN(PB_STEP) * k);
                if (elect_one()) prefetch_slice(&mPB, 4 * k, 512 + cta * 4);
            }
#pragma unroll 1
            for (int k = 0; k < TN(PC_N); k++) {
                behind(min(TN(PC_E0) + TN(PC_STEP) * k / 2, 25));
                if (elect_one()) pf_c(k);
            }
            int pk = TN(PC_N), pe = TN(PC_E1);
            auto own_part = [&](int e) {
                if (!(TDBG & 16) && !mbar_test(bar_out + 8 * e, 0)) {
                    mbar_wait(bar_out + 8 * e);
                    sleep_until(clk32() + TN(T_OWN));
                    STAMP(11);
                }
            };
            const char* src = reinterpret_cast<const char*>(prm.s->h) + (size_t)chunk * 524288;
            uint32_t slot = 32 % NST;
#pragma unroll 1
            for (int i = 32; i < NBIG; i++) {
                if (!(i & 3)) own_part((i - 32) >> 2);
                mbar_wait(empty + 8 * (i - NST));
                PSTAMP(i);
                if (elect_one()) {
                    mbar_expect_tx(hfull + 8 * slot, 2 * TILE);
                    bulk_load(sb + slot * SLOT, src, 2 * TILE, hfull + 8 * slot);
                    tma5(sb + slot * SLOT + 2 * TILE, (i & 4) ? &mCim : &mCre, c_col(i), dt * 8, full + 8 * i);
                }
                if (i == pe && pk < 8) {
                    if (elect_one()) pf_c(pk);
                    pk++; pe += TN(PC_S1);
                }
                src += 2 * TILE;
                slot = slot == NST - 1 ? 0 : slot + 1;
            }
            src -= (NBIG - 32) * 2 * TILE;
#pragma unroll
            for (int k = 0; k < 2 * NSPL - 2; k++) {
                if (k == 0 || k == 2) own_part(6 + k / 2);
                mbar_wait(empty + 8 * (NBIG - NST + k));
                if (k >= 1 && k <= 4) {
                    if (elect_one()) {
#pragma unroll
                        for (int j = 2 * k - 2; j < 2 * k; j++)
                            tma5(sb + tail_c(j), ((NBIG + j) & 4) ? &mCim : &mCre, c_col(NBIG + j), dt * 8, full + 8 * (NBIG + j));
                    }
                }
                if (k == 4) continue;
                if (k == 2) mbar_wait(bar_dfree + 8);
                if (elect_one()) {
#pragma unroll
                    for (int n = k < 5 ? 2 * k : k + 2; n < (k < 3 ? 2 * k + 2 : k == 3 ? 7 : k + 3); n++) {
                        mbar_expect_tx(hfull + 8 * (NST + n % 7), TILE);
                        bulk_load(sb + tail_h(n), src + tail_src(n), TILE, hfull + 8 * (NST + n % 7));
                    }
                }
            }
        } else {
            if (elect_one()) {
#pragma unroll
                for (int i = 0; i < NST; i++) mbar_init(full + 8 * i, 1);
                fence_mbar_init();
            }
            __syncwarp();
            asm volatile("bar.arrive 5, 160;" ::: "memory");
            asm volatile("bar.arrive 0, 448;" ::: "memory");
#pragma unroll 1
            for (int i = 0; i < NST; i++) {
                if (elect_one()) {
                    mbar_expect_tx(full + 8 * i, SLOT);
                    tma5b(sb + i * SLOT, &mB, i * 64, dt * 4, full + 8 * i);
                    tma4(sb + i * SLOT + 2 * TILE, &mX, i * 64, chunk * 64, full + 8 * i);
                }
                STAMPIF(i == 0, 1);
            }
            STAMP(2);
            named_bar(6, 160);
            uint32_t dst = sb;
#pragma unroll 1
            for (int i = NST; i < 32; i++) {
                if (i == 2 * NST) mbar_wait(bar_base);
                if (lane == 0) mbar_expect_tx(full + 8 * i, SLOT);
                mbar_wait(empty + 8 * (i - NST));
                PSTAMP(i);
                if (elect_one()) {
                    tma5b(dst, &mB, (i & 15) * 64, (i >> 4) * 64 + dt * 4, full + 8 * i);
                    tma4(dst + 2 * TILE, &mX, (i & 15) * 64, chunk * 64, full + 8 * i);
                }
                dst = dst == sb + (NST - 1) * SLOT ? sb : dst + SLOT;
            }
        }
    }
}

typedef CUresult (*EncodeFn)(CUtensorMap*, CUtensorMapDataType, cuuint32_t, void*, const cuuint64_t*, const cuuint64_t*, const cuuint32_t*,
                             const cuuint32_t*, CUtensorMapInterleave, CUtensorMapSwizzle, CUtensorMapL2promotion, CUtensorMapFloatOOBfill);

bool encode(EncodeFn fn, CUtensorMap* m, const void* ptr, int rank, const cuuint64_t* dims, const cuuint64_t* strides, const cuuint32_t* box,
            CUtensorMapL2promotion promo = CU_TENSOR_MAP_L2_PROMOTION_NONE) {
    const cuuint32_t es[5] = {1, 1, 1, 1, 1};
    return fn(m, CU_TENSOR_MAP_DATA_TYPE_BFLOAT16, rank, const_cast<void*>(ptr), dims, strides, box, es, CU_TENSOR_MAP_INTERLEAVE_NONE,
              CU_TENSOR_MAP_SWIZZLE_128B, promo, CU_TENSOR_MAP_FLOAT_OOB_FILL_NONE) == CUDA_SUCCESS;
}

}

extern "C" void kernel_launch(void* const* d_in, const int* in_sizes, int n_in, void* d_out, int out_size) {
    (void)in_sizes; (void)n_in; (void)out_size;
    Params prm;
    prm.x = (const __nv_bfloat16*)d_in[0];
    prm.lam_re = (const __nv_bfloat16*)d_in[1];
    prm.lam_im = (const __nv_bfloat16*)d_in[2];
    prm.b_re = (const __nv_bfloat16*)d_in[3];
    prm.b_im = (const __nv_bfloat16*)d_in[4];
    prm.c_re = (const __nv_bfloat16*)d_in[5];
    prm.c_im = (const __nv_bfloat16*)d_in[6];
    prm.log_dt = (const __nv_bfloat16*)d_in[7];
    prm.dskip = (const __nv_bfloat16*)d_in[8];
    prm.w_r = (const __nv_bfloat16*)d_in[10];
    prm.gate_w = (const __nv_bfloat16*)d_in[14];
    prm.out = (float*)d_out;
    cudaGetSymbolAddress((void**)&prm.s, g_scratch);
    prm.swapped = prm.b_im < prm.b_re;

    void* fnp = nullptr;
    cudaDriverEntryPointQueryResult qr;
    cudaGetDriverEntryPoint("cuTensorMapEncodeTiled", &fnp, cudaEnableDefault, &qr);
    EncodeFn fn = (EncodeFn)fnp;
    cudaFuncSetAttribute(fused_kernel, cudaFuncAttributeMaxDynamicSharedMemorySize, SMEM_BYTES);

    CUtensorMap mX, mB, mCre, mCim, mWg, mWu, mWd, mXr, mPB, mPC, mXe;
    const cuuint64_t row = 2048;
    {
        const cuuint64_t dims[4] = {1024, 2, 4, 976}, st[3] = {row, 32 * row, 2 * row};
        const cuuint32_t box[4] = {64, 2, 4, 16};
        encode(fn, &mX, prm.x, 4, dims, st, box, PROMO);
    }
    {
        const char *lo = (const char*)(prm.swapped ? prm.b_im : prm.b_re), *hi = (const char*)(prm.swapped ? prm.b_re : prm.b_im);
        const cuuint64_t dims[5] = {1024, 8, 2, 96, 2}, st[4] = {row, (cuuint64_t)(hi - lo), 8 * row, 256 * row};
        const cuuint32_t box[5] = {64, 8, 2, 4, 2};
        encode(fn, &mB, lo, 5, dims, st, box, PROMO);
    }
    {
        const cuuint64_t dims[5] = {1024, 2, 4, 2, 64}, st[4] = {row, 4 * row, 2 * row, 16 * row};
        const cuuint32_t box[5] = {64, 2, 4, 2, 8};
        encode(fn, &mCre, prm.c_re, 5, dims, st, box);
        encode(fn, &mCim, prm.c_im, 5, dims, st, box);
    }
    {
        const cuuint64_t dims[2] = {F_, D_}, st[1] = {F_ * 2}, dimsd[2] = {D_, F_}, std_[1] = {row};
        const cuuint32_t box[2] = {64, 64};
        encode(fn, &mWg, d_in[11], 2, dims, st, box);
        encode(fn, &mWu, d_in[12], 2, dims, st, box);
        encode(fn, &mWd, d_in[13], 2, dimsd, std_, box);
    }
    for (int i = 0; i < 2; i++) {
        const char *p = (const char*)(i ? prm.c_re : prm.b_re), *q = (const char*)(i ? prm.c_im : prm.b_im);
        const cuuint64_t dims[4] = {64, 16, 1024, 2}, st[3] = {128, row, (cuuint64_t)(p < q ? q - p : p - q)};
        const cuuint32_t box[4] = {16, 4, 4, 2};
        encode(fn, i ? &mPC : &mPB, p < q ? p : q, 4, dims, st, box, CU_TENSOR_MAP_L2_PROMOTION_L2_128B);
    }
    {
        const cuuint64_t dims[3] = {D_ - 192, S_, 4}, st[2] = {row, 128};
        const cuuint32_t box[3] = {64, 16, 4};
        encode(fn, &mXr, prm.x, 3, dims, st, box);
    }
    {
        const cuuint64_t dims[5] = {1024, 2, 4, 4, S_ / 32}, st[4] = {4 * row, row, 8 * row, 32 * row};
        const cuuint32_t box[5] = {64, 2, 4, 2, 4};
        encode(fn, &mXe, prm.x, 5, dims, st, box);
    }
    fused_kernel<<<NCTA, 512, SMEM_BYTES, cudaStreamPerThread>>>(prm, mX, mB, mCre, mCim, mWg, mWu, mWd, mXr, mPB, mPC, mXe);
}
```

```cpp
#include <cuda_runtime.h>
#include <cuda_bf16.h>
#include <cuda.h>
#include <stdint.h>

namespace {

constexpr int S_ = 2048, D_ = 1024, F_ = 3584;
constexpr int NCTA = 128;
constexpr int NSPL = 9, NBIG = 64 - NSPL, NENT = NBIG + 2 * NSPL;
constexpr int NST = 5;
constexpr int NFT = 5;
constexpr uint32_t SLOT = 32768, TILE = 8192;
constexpr uint32_t OFF_FT = NST * SLOT;
constexpr uint32_t OFF_XS = OFF_FT + NFT * TILE;
constexpr uint32_t OFF_LIST = OFF_XS + 8192;
constexpr uint32_t OFF_RED = OFF_XS + 4096;
constexpr uint32_t OFF_CONST = OFF_XS + 16384;
constexpr uint32_t OFF_M = OFF_CONST + 8192;
constexpr uint32_t OFF_HID = OFF_CONST;
constexpr uint32_t OFF_G = OFF_M + 512;
constexpr uint32_t OFF_DK = OFF_G + 256;
constexpr uint32_t OFF_FULL = OFF_DK + 256;
constexpr uint32_t OFF_EMPTY = OFF_FULL + 103 * 8;
constexpr uint32_t OFF_KEYS = OFF_EMPTY + 87 * 8;
constexpr uint32_t OFF_SEL = OFF_KEYS + 32;
constexpr uint32_t OFF_EPOCH = OFF_SEL + 32;
constexpr uint32_t OFF_PROF = OFF_EPOCH + 16;
constexpr uint32_t SMEM_BYTES = OFF_PROF + 432;
static_assert(SMEM_BYTES <= 232448, "smem");

static_assert(NBIG % NST == 0, "tail layout");
__host__ __device__ constexpr uint32_t tail_c(int j) { return j < 8 ? SLOT + j * 2 * TILE : OFF_FT + 5 * TILE; }
__host__ __device__ constexpr uint32_t tail_h(int n) { return n % 7 < 4 ? n % 7 * TILE : OFF_FT + (n % 7 - 2) * TILE; }
__host__ __device__ constexpr uint32_t tail_src(int n) { return (n % NSPL + NBIG - 32) * 2 * TILE + n / NSPL * TILE; }
__host__ __device__ constexpr int c_col(int i) { return ((i & 3) + ((i >> 1) & 12)) * 64; }

constexpr uint32_t SPIN_LIMIT = 1u << 18;

struct Scratch {
    uint2 carry[16 * 1024];
    uint2 hid[NCTA * 128];
    uint32_t y[8 * 8 * D_];
    uint32_t key[NCTA * 8];
    uint32_t gate[S_];
    uint4 part[112 * 128];
    uint2 armed[NCTA * 4];
    unsigned int epoch[256];
    uint4 start[32 * 2];
    uint4 h[16 * 32 * 1024];
};
__device__ __align__(1024) Scratch g_scratch;
#define STAMPW_(cond, w) do {} while (0)
#define GSTAMP(cond, w) do {} while (0)
#define LSTAMP(cond, w) STAMPW_(cond, w)
#define LT 0
#define STAMPW(cond, w) STAMPW_(cond, w)
#define STAMPIF(cond, i) STAMPW(cond, 96 + (i))
#define STAMP(i) STAMPW(1, 96 + (i))
#define KSTAMP(i) STAMPW((threadIdx.x & 127) == 0, i)
#define PSTAMP(i) STAMPW((i) < 56 && (i) >= 32, 160 + (i))

struct Params {
    const __nv_bfloat16 *x, *b_re, *b_im, *lam_re, *lam_im, *c_re, *c_im, *log_dt, *dskip, *w_r, *gate_w;
    float* out;
    Scratch* s;
    int swapped;
};

__device__ __forceinline__ uint32_t smem_u32(const void* p) { return (uint32_t)__cvta_generic_to_shared(p); }
__device__ __forceinline__ void mbar_init(uint32_t bar, uint32_t cnt) { asm volatile("mbarrier.init.shared::cta.b64 [%0], %1;" ::"r"(bar), "r"(cnt) : "memory"); }
__device__ __forceinline__ void mbar_expect_tx(uint32_t bar, uint32_t bytes) { asm volatile("mbarrier.arrive.expect_tx.shared::cta.b64 _, [%0], %1;" ::"r"(bar), "r"(bytes) : "memory"); }
__device__ __forceinline__ void mbar_arrive(uint32_t bar) { asm volatile("mbarrier.arrive.shared::cta.b64 _, [%0];" ::"r"(bar) : "memory"); }
__device__ __forceinline__ bool mbar_test(uint32_t bar, uint32_t parity) {
    uint32_t ok;
    asm volatile("{ .reg .pred p; mbarrier.test_wait.parity.shared::cta.b64 p, [%1], %2; selp.u32 %0, 1, 0, p; }" : "=r"(ok) : "r"(bar), "r"(parity) : "memory");
    return __all_sync(0xffffffffu, ok);
}
__device__ __forceinline__ void mbar_wait(uint32_t bar, uint32_t parity = 0) {
    asm volatile("{ .reg .pred p; .reg .u32 n; mov.u32 n, 0;\nW%=: mbarrier.try_wait.parity.shared::cta.b64 p, [%0], %1; @p bra D%=;\n"
                 "add.u32 n, n, 0x4000; setp.ne.u32 p, n, 0; @p bra W%=; trap;\nD%=: }" ::"r"(bar), "r"(parity) : "memory");
}
__device__ __forceinline__ bool elect_one() {
    uint32_t pred;
    asm volatile("{ .reg .pred P; elect.sync _|P, 0xffffffff; selp.b32 %0, 1, 0, P; }" : "=r"(pred));
    return pred;
}
__device__ __forceinline__ void named_bar(int id, int n) { asm volatile("bar.sync %0, %1;" ::"r"(id), "r"(n) : "memory"); }
__device__ __forceinline__ void fence_mbar_init() { asm volatile("fence.mbarrier_init.release.cluster;" ::: "memory"); }
__device__ __forceinline__ void fence_async_smem() { asm volatile("fence.proxy.async.shared::cta;" ::: "memory"); }

__device__ __forceinline__ void bulk_load(uint32_t dst, const void* src, uint32_t bytes, uint32_t bar) {
    asm volatile("cp.async.bulk.shared::cluster.global.mbarrier::complete_tx::bytes [%0], [%1], %2, [%3];" ::"r"(dst), "l"(src), "r"(bytes), "r"(bar) : "memory");
}
__device__ __forceinline__ void cp_async16(uint32_t dst, const void* src) { asm volatile("cp.async.cg.shared.global [%0], [%1], 16;" ::"r"(dst), "l"(src) : "memory"); }
__device__ __forceinline__ void sts128(uint32_t a, uint32_t x, uint32_t y, uint32_t z, uint32_t w) {
    asm volatile("st.shared.v4.u32 [%0], {%1,%2,%3,%4};" ::"r"(a), "r"(x), "r"(y), "r"(z), "r"(w) : "memory");
}
__device__ __forceinline__ uint2 lds64(uint32_t a) {
    uint2 v;
    asm volatile("ld.shared.v2.u32 {%0,%1}, [%2];" : "=r"(v.x), "=r"(v.y) : "r"(a) : "memory");
    return v;
}
__device__ __forceinline__ uint32_t lds32(uint32_t a) {
    uint32_t v;
    asm volatile("ld.volatile.shared.u32 %0, [%1];" : "=r"(v) : "r"(a) : "memory");
    return v;
}
__device__ __forceinline__ void stg128(void* p, uint32_t x, uint32_t y, uint32_t z, uint32_t w) {
    asm volatile("st.global.v4.u32 [%0], {%1,%2,%3,%4};" ::"l"(p), "r"(x), "r"(y), "r"(z), "r"(w) : "memory");
}
__device__ __forceinline__ void st_relaxed(void* p, uint32_t x) { asm volatile("st.relaxed.gpu.global.b32 [%0], %1;" ::"l"(p), "r"(x) : "memory"); }
__device__ __forceinline__ void st_relaxed2(void* p, uint32_t x, uint32_t y) { asm volatile("st.relaxed.gpu.global.v2.b32 [%0], {%1, %2};" ::"l"(p), "r"(x), "r"(y) : "memory"); }
__device__ __forceinline__ void st_relaxed4(void* p, uint32_t x, uint32_t y, uint32_t z, uint32_t w) {
    asm volatile("st.relaxed.gpu.global.v4.b32 [%0], {%1, %2, %3, %4};" ::"l"(p), "r"(x), "r"(y), "r"(z), "r"(w) : "memory");
}
__device__ __forceinline__ uint32_t ld_relaxed(const void* p) {
    uint32_t v;
    asm volatile("ld.relaxed.gpu.global.b32 %0, [%1];" : "=r"(v) : "l"(p) : "memory");
    return v;
}
__device__ __forceinline__ uint2 ld_relaxed2(const void* p) {
    uint2 v;
    asm volatile("ld.relaxed.gpu.global.v2.b32 {%0, %1}, [%2];" : "=r"(v.x), "=r"(v.y) : "l"(p) : "memory");
    return v;
}
__device__ __forceinline__ uint4 ld_relaxed4(const void* p) {
    uint4 v;
    asm volatile("ld.relaxed.gpu.global.v4.b32 {%0, %1, %2, %3}, [%4];" : "=r"(v.x), "=r"(v.y), "=r"(v.z), "=r"(v.w) : "l"(p) : "memory");
    return v;
}
__device__ __forceinline__ uint32_t clk32() { uint32_t c; asm volatile("mov.u32 %0, %%clock;" : "=r"(c)); return c; }
__device__ __forceinline__ uint32_t gtime32() { uint32_t c; asm volatile("mov.u32 %0, %%globaltimer_lo;" : "=r"(c)); return c; }
__device__ __forceinline__ void sched_fence(uint32_t t) { while ((int)(clk32() - t) < 0) {} }
__device__ __forceinline__ void sleep_until(uint32_t t) { while ((int)(clk32() - t) < 0) __nanosleep(40); }

__device__ __forceinline__ void tma2(uint32_t dst, const CUtensorMap* m, int c0, int c1, uint32_t bar) {
    asm volatile("{ .reg .b64 pol; createpolicy.fractional.L2::evict_first.b64 pol;\n"
                 "cp.async.bulk.tensor.2d.shared::cluster.global.mbarrier::complete_tx::bytes.L2::cache_hint [%0], [%1, {%3, %4}], [%2], pol; }"
                 ::"r"(dst), "l"(m), "r"(bar), "r"(c0), "r"(c1) : "memory");
}
__device__ __forceinline__ void tma3(uint32_t dst, const CUtensorMap* m, int c0, int c1, uint32_t bar) {
    asm volatile("cp.async.bulk.tensor.3d.shared::cluster.global.mbarrier::complete_tx::bytes [%0], [%1, {%3, %4, %5}], [%2];"
                 ::"r"(dst), "l"(m), "r"(bar), "r"(c0), "r"(c1), "r"(0) : "memory");
}
__device__ __forceinline__ void tma4(uint32_t dst, const CUtensorMap* m, int c0, int c3, uint32_t bar) {
    asm volatile("cp.async.bulk.tensor.4d.shared::cluster.global.mbarrier::complete_tx::bytes [%0], [%1, {%3, %5, %5, %4}], [%2];"
                 ::"r"(dst), "l"(m), "r"(bar), "r"(c0), "r"(c3), "r"(0) : "memory");
}
__device__ __forceinline__ void tma5(uint32_t dst, const CUtensorMap* m, int c0, int c4, uint32_t bar) {
    asm volatile("cp.async.bulk.tensor.5d.shared::cluster.global.mbarrier::complete_tx::bytes [%0], [%1, {%3, %5, %5, %5, %4}], [%2];"
                 ::"r"(dst), "l"(m), "r"(bar), "r"(c0), "r"(c4), "r"(0) : "memory");
}
__device__ __forceinline__ void tma5b(uint32_t dst, const CUtensorMap* m, int c0, int c3, uint32_t bar) {
    asm volatile("cp.async.bulk.tensor.5d.shared::cluster.global.mbarrier::complete_tx::bytes [%0], [%1, {%3, %5, %5, %4, %5}], [%2];"
                 ::"r"(dst), "l"(m), "r"(bar), "r"(c0), "r"(c3), "r"(0) : "memory");
}
__device__ __forceinline__ void prefetch_l2(const void* p) { asm volatile("prefetch.global.L2 [%0];" ::"l"(p)); }
__device__ __forceinline__ void prefetch_slice(const CUtensorMap* m, int line, int row) {
    asm volatile("cp.async.bulk.prefetch.tensor.4d.L2.global [%0, {%3, %1, %2, %3}];" ::"l"(m), "r"(line), "r"(row), "r"(0) : "memory");
}
__device__ __forceinline__ void prefetch_map(const CUtensorMap* m) { asm volatile("prefetch.tensormap [%0];" ::"l"(m)); }
__device__ __forceinline__ uint32_t uni(uint32_t v) { return __shfl_sync(0xffffffffu, v, 0); }

__device__ __forceinline__ uint32_t make_desc(uint32_t addr) { return ((addr & 0x3FFFF) >> 4) | (1u << 16); }
__device__ __forceinline__ uint32_t make_desc_h(uint32_t addr) { return ((addr & 0x3FFFF) >> 4) | (32u << 16); }
template <int H> __device__ __forceinline__ uint64_t desc64(uint32_t lo) {
    uint64_t d;
    asm volatile("mov.b64 %0, {%1, %2};" : "=l"(d) : "r"(lo), "n"(64u | ((H ? 2u : 1u) << 30)));
    return d;
}
__device__ __forceinline__ void wgmma_fence() { asm volatile("wgmma.fence.sync.aligned;" ::: "memory"); }
__device__ __forceinline__ void wgmma_commit() { asm volatile("wgmma.commit_group.sync.aligned;" ::: "memory"); }
template <int N> __device__ __forceinline__ void wgmma_wait() { asm volatile("wgmma.wait_group.sync.aligned %0;" ::"n"(N) : "memory"); }

#define R8(d, i) "+f"(d[i]), "+f"(d[i + 1]), "+f"(d[i + 2]), "+f"(d[i + 3]), "+f"(d[i + 4]), "+f"(d[i + 5]), "+f"(d[i + 6]), "+f"(d[i + 7])
#define R64(d) R8(d, 0), R8(d, 8), R8(d, 16), R8(d, 24), R8(d, 32), R8(d, 40), R8(d, 48), R8(d, 56)
template <int TA>
__device__ __forceinline__ void wgmma_n128(float (&d)[64], uint64_t da, uint64_t db, int scale_d = 1) {
    asm volatile("{ .reg .pred p; setp.ne.b32 p, %66, 0;\n"
                 "wgmma.mma_async.sync.aligned.m64n128k16.f32.bf16.bf16 "
                 "{%0,%1,%2,%3,%4,%5,%6,%7,%8,%9,%10,%11,%12,%13,%14,%15,%16,%17,%18,%19,%20,%21,%22,%23,%24,%25,%26,%27,%28,%29,%30,%31,"
                 "%32,%33,%34,%35,%36,%37,%38,%39,%40,%41,%42,%43,%44,%45,%46,%47,%48,%49,%50,%51,%52,%53,%54,%55,%56,%57,%58,%59,%60,%61,%62,%63}, "
                 "%64, %65, p, 1, 1, %67, 0; }"
                 : R64(d)
                 : "l"(da), "l"(db), "r"(scale_d), "n"(TA));
}
__device__ __forceinline__ void pin4(float (&d)[4]) { asm volatile("" : "+f"(d[0]), "+f"(d[1]), "+f"(d[2]), "+f"(d[3])::"memory"); }
__device__ __forceinline__ void pin64(float (&d)[64]) { asm volatile("" : R64(d)::"memory"); }

template <int TA>
__device__ __forceinline__ void wgmma_n8(float (&d)[4], uint64_t da, uint64_t db, int scale_d = 1) {
    asm volatile("{ .reg .pred p; setp.ne.b32 p, %7, 0;\n"
                 "wgmma.mma_async.sync.aligned.m64n8k16.f32.bf16.bf16 {%0,%1,%2,%3}, %4, %5, p, 1, 1, %6, 0; }"
                 : "+f"(d[0]), "+f"(d[1]), "+f"(d[2]), "+f"(d[3])
                 : "l"(da), "l"(db), "n"(TA), "r"(scale_d));
}

__device__ __forceinline__ float bf_lo(uint32_t u) { return __uint_as_float(u << 16); }
__device__ __forceinline__ float bf_hi(uint32_t u) { return __uint_as_float(u & 0xFFFF0000u); }
__device__ __forceinline__ float rbf(float v) { return __bfloat162float(__float2bfloat16_rn(v)); }
__device__ __forceinline__ uint32_t pack_bf(float lo, float hi) {
    uint32_t r;
    asm("cvt.rn.bf16x2.f32 %0, %1, %2;" : "=r"(r) : "f"(hi), "f"(lo));
    return r;
}
__device__ __forceinline__ uint32_t mul_bf2(uint32_t a, uint32_t b) {
    uint32_t r;
    asm("mul.rn.bf16x2 %0, %1, %2;" : "=r"(r) : "r"(a), "r"(b));
    return r;
}
__device__ __forceinline__ uint32_t fma_bf2(uint32_t a, uint32_t b, uint32_t c) {
    uint32_t r;
    asm("fma.rn.bf16x2 %0, %1, %2, %3;" : "=r"(r) : "r"(a), "r"(b), "r"(c));
    return r;
}
__device__ __forceinline__ float2 cmul(float2 a, float2 b) { return make_float2(a.x * b.x - a.y * b.y, a.x * b.y + a.y * b.x); }
__device__ __forceinline__ float2 cfma(float2 a, float2 b, float2 c) {
    return make_float2(fmaf(a.x, b.x, fmaf(-a.y, b.y, c.x)), fmaf(a.x, b.y, fmaf(a.y, b.x, c.y)));
}
__device__ __forceinline__ float sigmoidf_(float v) { return __fdividef(1.0f, 1.0f + expf(-v)); }

#define SCHED_NAMES T_W0, T_INIT, T_SMALL, T_W3, PF0, PF1, RT0, RT1, RT2, RT3, T_BASE, G_NS, GT0, GL, GQ, GT1, G0, T_CP0, T_CP1, GAP0, GAP1, T_OWN, \
    T_RETRY, T_Y, RS_E, PB_E0, PB_STEP, PC_E0, PC_STEP, PC_N, PC_E1, PC_S1, GU_E0, W_NUM, GC0, GCS, GCS4, GCH, HG, DL0, DLS, DN_E0
enum { SCHED_NAMES, NTUNE };
constexpr int sched_default[NTUNE] = {
    600, 1000, 1000, 1000,
    1100, 400,
    2200, 2700, 3200, 3700,
    2500, 7,
    6200, 600, 1023, 7200,
    800, 900, 900,
    300, 300,
    1000, 200, 700,
    4,
    4, 1, 11, 4, 6, 50, 3,
    4, 8, 14, 8, 6, 11,
    43, 37, 8, 48};
template <int I> struct Sched { static constexpr int v = sched_default[I]; };
#define TN(i) (Sched<i>::v)
#define DBG 0
#define TDBG 0
#define X0 1
#define GE 8
#define PROMO CU_TENSOR_MAP_L2_PROMOTION_L2_256B

template <int TA, class H>
__device__ __forceinline__ void run_entry(uint32_t lo32, uint32_t prev, int accumulate, float (&accA)[64], float (&accB)[64], H inside) {
    const uint64_t da = desc64<TA>(lo32), db = TA ? desc64<0>(lo32 + (2 * TILE >> 4) - (31u << 16)) : da + (2 * TILE >> 4);
    wgmma_fence();
#pragma unroll
    for (int kk = 0; kk < 4; kk++) {
        wgmma_n128<TA>(accA, da + kk * (TA ? 128 : 2), db + kk * 2, kk > 0 ? 1 : accumulate);
        wgmma_n128<TA>(accB, da + 512 + kk * (TA ? 128 : 2), db + kk * 2, kk > 0 ? 1 : accumulate);
        if (kk == 1) {
            wgmma_commit();
            wgmma_wait<1>();
            if ((threadIdx.x & 31) == 0) mbar_arrive(prev);
            inside();
        }
    }
    wgmma_commit();
}
template <int TA, class H>
__device__ __forceinline__ void run_entries(uint32_t sb, int lo, int hi, int slot, float (&accA)[64], float (&accB)[64], H after) {
    const uint32_t da0 = TA ? make_desc_h(sb) : make_desc(sb), dlast = da0 + (NST - 1) * (SLOT >> 4);
    uint32_t prev = sb + OFF_FULL + 8 * 101, bar = sb + OFF_FULL + 8 * lo, lo32 = da0 + slot * (SLOT >> 4);
    int accumulate = 0;
#pragma unroll 1
    for (int i = lo; i < hi; i++) {
        mbar_wait(bar);
        KSTAMP(i);
        run_entry<TA>(lo32, prev, accumulate, accA, accB, []() {});
        prev = bar + (OFF_EMPTY - OFF_FULL);
        bar += 8;
        lo32 = lo32 == dlast ? da0 : lo32 + (SLOT >> 4);
        accumulate = 1;
        after(i);
    }
}

template <int TA>
__device__ __forceinline__ void small_tile(float (&acc)[4], uint32_t alo, uint32_t blo, bool first) {
    const uint64_t da = desc64<0>(alo), db = desc64<0>(blo);
#pragma unroll
    for (int kk = 0; kk < 4; kk++) wgmma_n8<TA>(acc, da + kk * (TA ? 128 : 2), db + kk * 2, kk > 0 || !first);
}

template <int N>
__device__ __forceinline__ uint32_t check_tile(uint32_t sb, uint32_t dst, uint32_t probe, const char* src, uint32_t par, uint32_t bar, uint32_t phase, uint32_t pause) {
    if (TDBG & 4) return phase;
#pragma unroll 1
    for (uint32_t it = 0; it < SPIN_LIMIT; it++) {
        uint32_t v[N], bad = 0;
#pragma unroll
        for (int u = 0; u < N; u++) v[u] = lds32(dst + probe + (u >> 1) * 2048 + (u & 1) * 256);
#pragma unroll
        for (int u = 0; u < N; u += 4)
            asm("{ .reg .b32 a, b; lop3.b32 a, %1, %2, %5, 0x7E; lop3.b32 b, %3, %4, %5, 0x7E; lop3.b32 %0, %0, a, b, 0xFE; }"
                : "+r"(bad) : "r"(v[u]), "r"(v[u + 1]), "r"(v[u + 2]), "r"(v[u + 3]), "r"(par));
        if (!__any_sync(0xffffffffu, bad & 1u)) return phase;
        STAMP(10);
        __nanosleep(pause);
        if (elect_one()) {
            mbar_expect_tx(bar, N * 1024);
            bulk_load(dst, src, N * 1024, bar);
        }
        mbar_wait(bar, phase);
        phase ^= 1;
    }
    __trap();
    return 0;
}

__global__ void __launch_bounds__(512, 1)
fused_kernel(const __grid_constant__ Params prm, const __grid_constant__ CUtensorMap mX, const __grid_constant__ CUtensorMap mB, const __grid_constant__ CUtensorMap mCre,
             const __grid_constant__ CUtensorMap mCim, const __grid_constant__ CUtensorMap mWg, const __grid_constant__ CUtensorMap mWu,
             const __grid_constant__ CUtensorMap mWd, const __grid_constant__ CUtensorMap mXr, const __grid_constant__ CUtensorMap mPB,
             const __grid_constant__ CUtensorMap mPC, const __grid_constant__ CUtensorMap mXe) {
    {
        const uint32_t t = threadIdx.x, b = blockIdx.x;
        const uint32_t row = t < 32 ? ((b & 60) * 2 + (b >> 6) * 4 + (b & 3)) * 16 + (t >> 1) : b * 4 + ((t >> 1) & 3);
        const char* base = (const char*)(t < 32 ? prm.x : t < 40 ? prm.b_re : prm.b_im);
        asm volatile("{ .reg .pred p; setp.lt.u32 p, %1, 48; @p prefetch.global.L2 [%0]; }" ::"l"(base + (row * 2048 + (t & 1) * 128)), "r"(t) : "memory");
    }
    extern __shared__ __align__(1024) uint8_t smem[];
    uint32_t sb;
    asm volatile("mov.u32 %0, %1;" : "=r"(sb) : "r"(smem_u32(smem)));
    const int tid = threadIdx.x, warp = __shfl_sync(0xffffffffu, tid >> 5, 0), lane = tid & 31;
    const int cta = blockIdx.x;
    const uint32_t cstart = clk32();
    const int chunk = (cta >> 2) & 15;
    const int dt = (cta >> 6) * 4 + (cta & 3);
    const int rid = chunk * 8 + dt;
    const int kslot = (rid & 3) * 32 + (rid >> 2);
    const bool owner = cta < 112;
    const uint32_t full = sb + OFF_FULL, empty = sb + OFF_EMPTY;
    const uint32_t bar_epoch = full + 8 * 73, dfull = full + 8 * 74, bar_retry = full + 8 * 81, bar_x = full + 8 * 82, ffull = full + 8 * 84,
                   hfull = full + 8 * 89, bar_base = full + 8 * 102;
    const uint32_t fempty = empty + 8 * 66, bar_order = empty + 8 * 71, bar_stored = empty + 8 * 73, bar_dfree = empty + 8 * 74,
                   bar_out = empty + 8 * 77, bar_g = empty + 8 * 85, bar_const = empty + 8 * 86;
    const int w = warp & 3, g = lane >> 2, c = lane & 3, at = tid & 127;

    const uint32_t probe = (lane >> 3) * 32 + (g & 1) * 144 + (c & 1) * 520 + (c >> 1) * 1028;

    LSTAMP(tid == 0, 96);
    GSTAMP(tid == 0, 94);
    auto init_barriers = [&](uint32_t base, uint32_t cnt, auto n) {
        if (elect_one()) {
#pragma unroll
            for (int i = 0; i < n(); i++) mbar_init(base + 8 * i, cnt);
            fence_mbar_init();
        }
        __syncwarp();
    };
    if (warp != 12) {
        if (warp == 15 && !(cta & 3) && lane < 8) st_relaxed((uint32_t*)&prm.s->start[cta >> 1] + lane, (lane & 1) ? gtime32() : cstart);
        if (warp < 12) sleep_until(cstart + (warp < 4 ? TN(T_W0) : TN(T_INIT)));
    }
    if (warp < 8) {
        if (warp < 4) init_barriers(warp == 0 ? full + 40 : warp == 3 ? full + 8 * 98 : empty + 40 * (warp - 1), (warp + 1) & 2 ? 4 : 1, []() { return 5; });
        else init_barriers(full + 80 + 176 * w, 1, []() { return 22; });
        asm volatile("setmaxnreg.inc.sync.aligned.u32 192;");
        if (warp < 4) {
            named_bar(5, 160);
            asm volatile("bar.arrive 0, 448;" ::: "memory");
            asm volatile("bar.arrive 6, 160;" ::: "memory");
            asm volatile("bar.arrive 7, 160;" ::: "memory");
        } else named_bar(0, 448);
        const int wg = warp >> 2;
        const int p = wg * 512 + dt * 32 + w * 8 + g;
        uint32_t cp = sb + OFF_CONST + 8 * (wg * 64 + w * 8 + g), cw = cp + 1024 * c, cm = sb + OFF_M + 4 * (wg * 64 + w * 8 + g);
        const int j1 = chunk - 1 - c;
        uint2* cq = &prm.s->carry[j1 * 1024 + p];
        char* hd = reinterpret_cast<char*>(prm.s->h) + (size_t)chunk * 524288 + wg * 262144 + (dt >> 1) * 16384 + ((dt & 1) * 4 + w) * 1024 + g * 64 + ((c ^ (g >> 1)) << 4);
        const bool never = uni(cstart == 0 && sb == 0);
        asm volatile("" : "+l"(cq), "+l"(hd), "+r"(cp), "+r"(cw), "+r"(cm));
        float2 a[2], a32[2], a64[2], a512[2], pw32[2], pw128[2];
        uint32_t mm[2], t2, par;
        auto constants = [&](int h) {
            if (h) { t2 = lds32(sb + OFF_EPOCH + 4); par = lds32(sb + OFF_EPOCH); }
            auto ldc = [](uint32_t a) { const uint2 v = lds64(a); return make_float2(__uint_as_float(v.x), __uint_as_float(v.y)); };
            {
                a[h] = ldc(cp + 256 * h); a32[h] = ldc(cp + 256 * h + 1024); a64[h] = ldc(cp + 256 * h + 2048); a512[h] = ldc(cp + 256 * h + 7168);
                pw32[h] = ldc(cw + 256 * h);
                pw128[h] = ldc(cw + 256 * h + 3072);
                mm[h] = lds32(cm + 128 * h);
            }
        };
        if (wg == 1) {
            const int pc = w * 256 + dt * 32 + lane;
            const float lr = __bfloat162float(prm.lam_re[pc]), li = __bfloat162float(prm.lam_im[pc]), ld = __bfloat162float(prm.log_dt[pc]);
            const uint32_t dk = __ldg(reinterpret_cast<const uint32_t*>(prm.dskip + dt * 128) + (at & 63));
            reinterpret_cast<uint32_t*>(smem + OFF_DK)[at & 63] = dk;
            const float dtv = rbf(expf(ld));
            const float er = expf(dtv * lr);
            float sn, cs;
            sincosf(dtv * li, &sn, &cs);
            const float ar = er * cs, ai = er * sn;
            const float nr = ar - 1.0f, ni = ai;
            const bool big = fabsf(lr) >= fabsf(li);
            const float t = (big ? li : lr) / (big ? lr : li), dn = big ? lr + li * t : lr * t + li;
            const float cr = (big ? nr + ni * t : nr * t + ni) / dn, ci = (big ? ni - nr * t : ni * t - nr) / dn;
            float2* ct = reinterpret_cast<float2*>(smem + OFF_CONST) + at;
            float2 pw = make_float2(ar, prm.swapped ? -ai : ai);
            ct[0] = pw;
            const float mx = prm.swapped ? -2.f * ci : 2.f * cr, my = prm.swapped ? 2.f * cr : -2.f * ci;
            reinterpret_cast<uint32_t*>(smem + OFF_M)[at] = pack_bf(mx, my);
#pragma unroll
            for (int i = 0; i < 5; i++) pw = cmul(pw, pw);
#pragma unroll
            for (int i = 0; i < 2; i++) {
                const float2 p2 = cmul(pw, pw);
                ct[128 + 384 * i] = pw; ct[256 + 384 * i] = p2; ct[384 + 384 * i] = cmul(p2, pw);
                pw = cmul(p2, p2);
            }
            ct[896] = pw;
            mbar_wait(bar_epoch);
            __syncwarp();
            mbar_wait(empty + 8 * TN(RS_E));
            st_relaxed2(&prm.s->hid[cta * 128 + at], ~0u, ~0u);
            st_relaxed4(&prm.s->y[((at >> 4) * 8 + (cta >> 4)) * D_ + (cta & 15) * 64 + (at & 15) * 4], 0u, 0u, 0u, 0u);
            st_relaxed2(&prm.s->carry[chunk * 1024 + pc], 0u, 0u);
            __syncwarp();
            if (lane == 0) mbar_arrive(bar_const);

            STAMPIF(at == 0, 3);
            mbar_wait(bar_const);
            constants(0);
            constants(1);
            mbar_wait(bar_order);
        }

        float accA[64], accB[64];
        run_entries<0>(sb, wg * 16, wg * 16 + 15, wg, accA, accB, [&](int i) {
            if (i == GE - 1) {
                mbar_wait(bar_base);
                const uint32_t t = lds32(sb + OFF_EPOCH + 8) + TN(GT0);
                const int late = clk32() - t - TN(GL);
                sched_fence(late < 0 ? t : t + TN(GL) + 256 + (late | TN(GQ)));
            }
        });
        mbar_wait(full + 8 * (wg * 16 + 15));
        KSTAMP(wg * 16 + 15);
        if (wg == 0) {
            mbar_wait(bar_const);
            run_entry<0>(make_desc(sb), empty + 8 * 14, 1, accA, accB, [&]() { constants(0); constants(1); });
            if (lane == 0) mbar_arrive(bar_order);
        } else run_entry<0>(make_desc(sb + SLOT), empty + 8 * 30, 1, accA, accB, [&]() { if (lane == 0) mbar_arrive(bar_order + 8); });
        uint2 v[4];
#pragma unroll
        for (int m = 0; m < 4; m++) v[m] = make_uint2(t2, t2);
        wgmma_wait<0>();
        pin64(accA); pin64(accB);
        if (lane == 0) mbar_arrive(empty + 8 * (wg * 16 + 15));
        LSTAMP(at == 0, 96 + 30 + 10 * wg); GSTAMP(LT && at == 0, 193 + wg);

        auto cut = [&]() { if (never) sched_fence(cstart); };
        auto poll = [&](int h) {
#pragma unroll
            for (int m = 0; m < 4; m++)
                asm volatile("{ .reg .pred p; setp.ge.s32 p, %3, %4; @p ld.relaxed.gpu.global.v2.b32 {%0, %1}, [%2]; }"
                             : "+r"(v[m].x), "+r"(v[m].y) : "l"(cq + 256 * h - 4096 * m), "r"(j1), "r"(4 * m) : "memory");
        };
        auto valid = [&]() {
            uint32_t bad = 0;
#pragma unroll
            for (int m = 0; m < 4; m++) bad |= (v[m].x ^ t2) | (v[m].y ^ t2);
            return __all_sync(0xffffffffu, (bad & 3u) == 0);
        };
        float2 w0[2];
        uint32_t tp;
#pragma unroll
        for (int h = 0; h < 2; h++) {
            float (&acc)[64] = h ? accB : accA;
            float2 e = make_float2(acc[0], acc[2]);
#pragma unroll
            for (int s = 1; s < 32; s++) {
                const int i0 = 4 * (s >> 1) + (s & 1);
                e = cfma(a[h], e, make_float2(acc[i0], acc[i0 + 2]));
            }
            float2 y = make_float2(__shfl_up_sync(0xffffffffu, e.x, 1, 4), __shfl_up_sync(0xffffffffu, e.y, 1, 4));
            if (c >= 1) e = cfma(a32[h], y, e);
            y = make_float2(__shfl_up_sync(0xffffffffu, e.x, 2, 4), __shfl_up_sync(0xffffffffu, e.y, 2, 4));
            if (c >= 2) e = cfma(a64[h], y, e);
            if (c == 3) st_relaxed2(cq + 4096 + 256 * h, (__float_as_uint(e.x) & ~3u) | t2, (__float_as_uint(e.y) & ~3u) | t2);
            if (h == 0) tp = clk32();
            cut();
            w0[h] = make_float2(__shfl_up_sync(0xffffffffu, e.x, 1, 4), __shfl_up_sync(0xffffffffu, e.y, 1, 4));
            STAMPIF(at == 0, 31 + h + 10 * wg);
        }
        uint32_t sx[2][16], sy[2][16], mr[2][4];
        const uint32_t gap = wg ? TN(GAP1) : TN(GAP0);
#pragma unroll
        for (int h = 0; h < 2; h++) {
            const uint32_t sg = prm.swapped ? 0x80008000u : 0u;
            mr[h][0] = __byte_perm(mm[h], 0, 0x1010); mr[h][1] = __byte_perm(mm[h], 0, 0x3232);
            mr[h][2] = mr[h][1] ^ sg; mr[h][3] = mr[h][0] ^ sg ^ 0x80008000u;
        }
        auto put = [&](int e, int j) {
            uint32_t d[4];
#pragma unroll
            for (int u = 0; u < 4; u++) d[u] = fma_bf2(mr[e >> 1][2 * (e & 1)], sx[e >> 1][4 * j + u], mul_bf2(mr[e >> 1][2 * (e & 1) + 1], sy[e >> 1][4 * j + u]));
            #pragma unroll
            for (int u = 0; u < 2; u++)
                asm("lop3.b32 %0, %0, %1, %2, 0xD8;" : "+r"(d[2 * (j & 1) + u]) : "r"(par), "r"((uint32_t)((w & 1) == u)));
            stg128(hd + e * 65536 + (j >> 1) * 8192 + (j & 1) * 512, d[0], d[1], d[2], d[3]);
            if (j == 3 && lane == 0) mbar_arrive(bar_out + 32 * wg + 8 * e);
        };
#pragma unroll
        for (int h = 0; h < 2; h++) {
            float (&acc)[64] = h ? accB : accA;
            uint32_t it = 0;
            if (h == 0) {
                sleep_until(tp + (wg ? TN(T_CP1) : TN(T_CP0)));
                poll(h);
            }
            while (!valid()) {
                if (++it > SPIN_LIMIT) __trap();
#pragma unroll
                for (int m = 0; m < 4; m++)
                    asm volatile("{ .reg .pred p; setp.ne.u32 p, %3, 0; @p ld.relaxed.gpu.global.v2.b32 {%0, %1}, [%2]; }"
                                 : "+r"(v[m].x), "+r"(v[m].y) : "l"(cq + 256 * h - 4096 * m), "r"(((v[m].x ^ t2) | (v[m].y ^ t2)) & 3u) : "memory");
            }
            float2 hin = make_float2(__uint_as_float(v[3].x), __uint_as_float(v[3].y));
#pragma unroll
            for (int m = 2; m >= 0; m--) hin = cfma(a512[h], hin, make_float2(__uint_as_float(v[m].x), __uint_as_float(v[m].y)));
            STAMPIF(at == 0 && it > 0 && h == 0, 39 + 10 * wg);
            if (c) hin = cmul(pw128[h], hin);
            hin.x += __shfl_xor_sync(0xffffffffu, hin.x, 1); hin.y += __shfl_xor_sync(0xffffffffu, hin.y, 1);
            hin.x += __shfl_xor_sync(0xffffffffu, hin.x, 2); hin.y += __shfl_xor_sync(0xffffffffu, hin.y, 2);
            float2 st = hin;
            if (c) st = cfma(pw32[h], hin, w0[h]);
            STAMPIF(at == 0, 33 + 3 * h + 10 * wg);
#pragma unroll
            for (int j = 0; j < 4; j++) {
#pragma unroll
                for (int u = 0; u < 4; u++) {
                    const int i0 = 16 * j + 4 * u;
                    const float2 y = cfma(a[h], st, make_float2(acc[i0], acc[i0 + 2]));
                    st = cfma(a[h], y, make_float2(acc[i0 + 1], acc[i0 + 3]));
                    sx[h][4 * j + u] = pack_bf(y.x, st.x); sy[h][4 * j + u] = pack_bf(y.y, st.y);
                }
                if (h) sleep_until(tp += gap);
                if (h == 0 && j == 1) poll(1);
                put(2 * h, j);
                cut();
            }
            STAMPIF(at == 0, 34 + 3 * h + 10 * wg);
            tp = clk32();
#pragma unroll
            for (int j = 0; j < 4; j++) {
                sleep_until(tp += gap);
                put(2 * h + 1, j);
            }
        }
        STAMPIF(at == 0, 38 + 10 * wg);

        if (wg == 1) {
            const char* src = reinterpret_cast<const char*>(prm.s->h) + (size_t)chunk * 524288;
            uint32_t rpar = 1;
#pragma unroll 1
            for (int n = w; n < 2 * NSPL; n += 4) {
                mbar_wait(empty + 8 * (NBIG - 7 + n));
                mbar_wait(hfull + 8 * (NST + n % 7), n / 7 & 1);
                const uint32_t dst = sb + tail_h(n);
                rpar = check_tile<8>(sb, dst, probe, src + tail_src(n), par, full + 8 * w, rpar, TN(T_RETRY));
                if (lane == 0) mbar_expect_tx(full + 8 * (NBIG + n), n < NSPL ? 2 * TILE : 0);
            }
        } else {
            asm volatile("setmaxnreg.inc.sync.aligned.u32 216;");
            const int tl = 64 * (w & 1) + 8 * (w >> 1) + g;
            float gf[4];
            float* op = prm.out + (size_t)(chunk * 128 + tl) * D_ + dt * 128 + 4 * c;
            const int xr = 2 * (g & 3) + (g >> 2);
            uint32_t xs = sb + (32 * (w & 1) + 8 * (w >> 1) + xr) * 128 + (((c >> 1) ^ xr) << 4) + (c & 1) * 8;
            uint32_t gs = sb + OFF_G + 2 * tl;
            asm volatile("" : "+r"(gs), "+l"(op), "+r"(xs));
            float outA[64], outB[64];
            STAMPIF(at == 0, 9);
            mbar_wait(bar_order + 8);
            STAMPIF(at == 0, 35);
            run_entries<1>(sb, 32, NBIG, 32 % NST, outA, outB, [](int) {});
            uint32_t gp[4], om[4];
            uint2 xt[4][8], dk[8];
            auto load_x = [&](int q, int j) {
#pragma unroll
                for (int r = 0; r < 2; r++) xt[2 * q + r][j] = lds64((xs ^ ((j & 3) << 5)) + (q ? tail_c(0) : OFF_FT) + (j >> 2) * TILE + r * 2048);
                if (q == 0) dk[j] = lds64(sb + OFF_DK + c * 8 + 32 * j);
            };
            auto term = [&](int q, int j) {
#pragma unroll
                for (int r = 2 * q; r < 2 * q + 2; r++) {
                    xt[r][j].x = mul_bf2(xt[r][j].x, fma_bf2(gp[r], dk[j].x, om[r]));
                    xt[r][j].y = mul_bf2(xt[r][j].y, fma_bf2(gp[r], dk[j].y, om[r]));
                }
            };
            auto store = [&](int q, int u0, int u1) {
                const float (&acc)[64] = q ? outB : outA;
#pragma unroll
                for (int u = u0; u < u1; u++) {
                    const int j = u >> 1, r = u & 1;
                    const int o = 8 * j + 2 * r;
                    const float gv = fabsf(gf[2 * q + r]);
                    const uint2 t = xt[2 * q + r][j];
                    stg128(op + (r * 32 + q * 16) * D_ + 16 * j, __float_as_uint(fmaf(gv, acc[o], bf_lo(t.x))), __float_as_uint(fmaf(gv, acc[o + 1], bf_hi(t.x))),
                           __float_as_uint(fmaf(gv, acc[o + 4], bf_lo(t.y))), __float_as_uint(fmaf(gv, acc[o + 5], bf_hi(t.y))));
                }
            };
            uint64_t dh = desc64<1>(make_desc_h(sb)), dc = desc64<0>(make_desc(sb));
#pragma unroll
            for (int n = 0; n < 2 * NSPL; n++) {
                const int j = n % NSPL;
                if (n == 0) mbar_wait(bar_g);
                if (n == X0 || n == 2 * NSPL - 1) mbar_wait(bar_x + (n == X0 ? 0 : 8));
                mbar_wait(full + 8 * (NBIG + n));
                KSTAMP(NBIG + n);
                asm volatile("mov.b64 %0, %0; mov.b64 %1, %1;" : "+l"(dh), "+l"(dc));
                const uint64_t da = dh + (tail_h(n) >> 4), db = dc + (tail_c(j) >> 4);
                const int xj = n - X0;
                wgmma_fence();
#pragma unroll
                for (int kk = 0; kk < 4; kk++) {
                    wgmma_n128<1>(n < NSPL ? outA : outB, da + kk * 128, db + kk * 2);
                    if (kk == 0 && n == 0) {
#pragma unroll
                        for (int r = 0; r < 4; r++) {
                            uint32_t u;
                            asm volatile("ld.shared.u16 %0, [%1];" : "=r"(u) : "r"(gs + (r & 1) * 64 + (r >> 1) * 32) : "memory");
                            gf[r] = bf_lo(u);
                        }
                    }
                    if (kk == 0 && xj >= 0 && xj < 8) load_x(0, xj);
                    if (kk == 0 && n == 2 * NSPL - 1) load_x(1, 0);
                }
                wgmma_commit();
                if (n <= 2 * NSPL - 7) {
                    wgmma_wait<1>();
                    if (lane == 0) mbar_arrive(empty + 8 * (NBIG + n - 1));
                    if (!j) { LSTAMP(at == 0, 96 + 12 + n / NSPL); GSTAMP(LT && at == 0, 195 + n / NSPL); }
                } else cut();
                if (n == 0) {
#pragma unroll
                    for (int r = 0; r < 4; r++) {
                        const bool routed = (int)__float_as_uint(gf[r]) < 0;
                        gp[r] = routed ? 0u : pack_bf(gf[r], gf[r]); om[r] = routed ? 0u : pack_bf(1.0f - gf[r], 1.0f - gf[r]);
                    }
                }
                if (xj >= 0 && xj < 8) term(0, xj);
                if (n == NSPL) pin64(outA);
                if (n >= NSPL) store(0, (j * 16 + 4) / NSPL, j == NSPL - 1 ? 16 : ((j + 1) * 16 + 4) / NSPL);
            }
            term(1, 0);
            cut();
            wgmma_wait<0>();
            pin64(outB);
            LSTAMP(at == 0, 96 + 51); GSTAMP(LT && at == 0, 197);
#pragma unroll
            for (int j = 1; j < 8; j++) load_x(1, j);
            store(1, 0, 2);
#pragma unroll
            for (int j = 1; j < 8; j++) {
                cut();
                term(1, j);
                store(1, 2 * j, 2 * j + 2);
            }
            __syncwarp();
            if (lane == 0) mbar_arrive(bar_stored);
            LSTAMP(at == 0, 96 + 52);
        }
    } else if (warp < 12) {
        asm volatile("setmaxnreg.dec.sync.aligned.u32 64;");
        init_barriers(empty + min(80 + 160 * w, 8 * 67), 4, []() { return 20; });
#pragma unroll
        for (int i = 0; i < 2; i++) sts128(sb + OFF_LIST + i * 2048 + at * 16, 0u, 0u, 0u, 0u);
        uint32_t* keys = reinterpret_cast<uint32_t*>(smem + OFF_KEYS);
        keys[4] = 0;
        named_bar(0, 448);
        if (at < 24) st_relaxed(at < 8 ? &prm.s->key[kslot * 8 + at] : &prm.s->gate[rid * 16 + at - 8], 0u);
        mbar_wait(bar_epoch);
        const uint32_t t2 = lds32(sb + OFF_EPOCH + 4);
        STAMPIF(at == 0, 20);
        float facc[4];
        const uint32_t dft = make_desc(sb + OFF_FT), dxs = make_desc(sb + OFF_XS);
#pragma unroll 1
        for (int u = 0; u < 4; u++) {
            mbar_wait(ffull + 8 * u);
            STAMPIF(at == 0, 4 + u);
            wgmma_fence();
            small_tile<0>(facc, dft + u * (TILE >> 4), dxs + u * 64, u == 0);
            wgmma_commit();
        }
        wgmma_wait<0>();
        pin4(facc);
        if (lane < 4) mbar_arrive(fempty + 8 * lane);
        auto gate_up = [&](auto rest) {
            uint32_t slot = 4, par = 0, prev = full + 8 * 101, e4 = 4 * TN(GC0);
#pragma unroll 1
            for (int j = 0; j < 14; j++) {
                if (j == 2) rest();
                STAMPW(at == 0, 75 + j);
                mbar_wait(ffull + 8 * slot, par);
                STAMPW(at == 0, 160 + j);
                mbar_wait(empty + 8 * (e4 >> 2));
                e4 += j < 8 ? TN(GCS) : TN(GCS4);
                wgmma_fence();
                small_tile<1>(facc, dft + slot * (TILE >> 4), dxs + j * 64, j == 0);
                wgmma_commit();
                wgmma_wait<1>();
                if (lane == 0) mbar_arrive(prev);
                prev = fempty + 8 * slot;
                if (++slot == NFT) { slot = 0; par ^= 1; }
            }
            wgmma_wait<0>();
            if (lane == 0) mbar_arrive(prev);
            pin4(facc);
        };
        auto help = [&]() {
            uint32_t slot = 4, par = 0, e4 = 4 * TN(GC0);
#pragma unroll 1
            for (int u = 0; u < 7; u++) {
                const uint32_t slot2 = slot == NFT - 1 ? 0 : slot + 1;
                mbar_wait(ffull + 8 * slot, par);
                par ^= slot2 == 0;
                mbar_wait(ffull + 8 * slot2, par);
                mbar_wait(empty + 8 * (e4 >> 2));
                e4 += TN(GCH);
                wgmma_fence();
                small_tile<1>(facc, dft + slot * (TILE >> 4), dxs, true);
                small_tile<1>(facc, dft + slot2 * (TILE >> 4), dxs + 64, false);
                wgmma_commit();
                wgmma_wait<0>();
                pin4(facc);
                if (lane < 2) mbar_arrive(fempty + 8 * (lane ? slot2 : slot));
                st_relaxed4(&prm.s->part[((cta - 112) * 7 + u) * 128 + at], (__float_as_uint(facc[0]) & ~3u) | t2, __float_as_uint(facc[1]),
                            __float_as_uint(facc[2]), __float_as_uint(facc[3]));
                slot = slot2 == NFT - 1 ? 0 : slot2 + 1;
                par ^= slot == 0;
            }
        };
        auto down = [&]() {
            const uint32_t dhid = make_desc(sb + OFF_HID);
#pragma unroll 1
            for (int j = 0; j < 7; j++) {
                mbar_wait(dfull + 8 * j);
                wgmma_fence();
                small_tile<1>(facc, dft + j * (TILE >> 4), dhid + j * 64, j == 0);
                wgmma_commit();
                if ((0x52 >> j) & 1) {
                    wgmma_wait<0>();
                    if (lane == 0) mbar_arrive(bar_dfree + 8 * (j / 3));
                }
            }
            wgmma_wait<0>();
            pin4(facc);
        };
        if ((c & 1) == (w >> 1)) {
            float* red = reinterpret_cast<float*>(smem + OFF_RED) + w * 32 + (c >> 1) * 16 + g;
            red[0] = (w & 1) ? facc[1] : facc[0];
            red[8] = (w & 1) ? facc[3] : facc[2];
        }
        named_bar(2, 128);
        STAMPIF(at == 0, 21);
        const uint32_t tpub = clk32();
        if (w < 2) {
            const float* red = reinterpret_cast<const float*>(smem + OFF_RED) + w * 16 + (lane & 15);
            const float v = rbf((red[0] + red[32]) + (red[64] + red[96]));
            if (w == 0) {
                uint32_t k = __float_as_uint(v);
                k = ((k ^ ((uint32_t)((int)k >> 31) | 0x80000000u)) & 0xFFFF0000u) | (t2 << 11) | (2047u - (uint32_t)(rid * 16 + (lane & 15)));
                int rank = 0;
#pragma unroll
                for (int i = 0; i < 8; i++) rank += __shfl_sync(0xffffffffu, k, (lane >> 4) * 8 + i) > k;
                rank += __shfl_xor_sync(0xffffffffu, rank, 16);
                if (rank < 8) st_relaxed(&prm.s->key[kslot * 8 + rank], k);
            } else if (lane < 16) st_relaxed(&prm.s->gate[rid * 16 + lane], __float_as_uint(rbf(sigmoidf_(v))) | t2);
            __syncwarp();
        }
        uint32_t it = 0;
        uint4 ka, kb4;
        mbar_wait(bar_base);
        sleep_until(lds32(sb + OFF_EPOCH + 8) + TN(GT1));
        sleep_until(tpub + TN(G0));
        bool bad = true;
        while (true) {
            if (bad) {
                ka = ld_relaxed4(&prm.s->key[at * 8]);
                kb4 = ld_relaxed4(&prm.s->key[at * 8 + 4]);
            }
            bad = (((ka.x ^ (t2 << 11)) | (kb4.x ^ (t2 << 11))) & 0x1800u) != 0;
            if (!__any_sync(0xffffffffu, bad)) break;
            if (++it > SPIN_LIMIT) __trap();
            __nanosleep(TN(T_RETRY));
        }
        STAMPIF(at == 0, 22);
        STAMPIF(at == 0 && it > 0, 23);
        const uint32_t m1 = __reduce_max_sync(0xffffffffu, ka.x), m2 = __reduce_max_sync(0xffffffffu, ka.x == m1 ? ka.y : ka.x);
        if (lane == 0) keys[w] = m2;
        named_bar(2, 128);
        const uint4 th4 = *reinterpret_cast<const uint4*>(keys);
        const uint32_t th = min(min(th4.x, th4.y), min(th4.z, th4.w));
        {
            const uint32_t k8[8] = {ka.x, ka.y, ka.z, ka.w, kb4.x, kb4.y, kb4.z, kb4.w};
            auto append = [&](int lo, int hi) {
                uint32_t n = 0, pos = 0;
#pragma unroll
                for (int i = lo; i < hi; i++) n += k8[i] >= th;
                asm volatile("{ .reg .pred p; setp.ne.u32 p, %2, 0; @p atom.shared.add.u32 %0, [%1], %2; }" : "+r"(pos) : "r"(sb + OFF_KEYS + 16), "r"(n) : "memory");
#pragma unroll
                for (int i = lo; i < hi; i++)
                    if (k8[i] >= th) reinterpret_cast<uint32_t*>(smem + OFF_LIST)[pos + i - lo] = k8[i];
            };
            append(0, 2);
            if (__any_sync(0xffffffffu, k8[2] >= th)) append(2, 8);
        }
        named_bar(2, 128);
        {
            const uint32_t* list = reinterpret_cast<const uint32_t*>(smem + OFF_LIST);
            const int n = (int)keys[4];
#pragma unroll 1
            for (int i0 = w * 32; i0 < n; i0 += 128) {
                const uint32_t k = list[i0 + lane];
                int rank = 0;
#pragma unroll 2
                for (int o = 0; o < n; o += 4) {
                    const uint4 l4 = *reinterpret_cast<const uint4*>(list + o);
                    rank += (l4.x > k) + (l4.y > k) + (l4.z > k) + (l4.w > k);
                }
                if (rank < 8) reinterpret_cast<uint32_t*>(smem + OFF_SEL)[rank] = k;
            }
        }
        named_bar(2, 128);
        STAMPIF(at == 0, 24);
        const uint32_t* sel = reinterpret_cast<const uint32_t*>(smem + OFF_SEL);
        auto gates = [&]() {
            uint32_t gv;
            it = 0;
            while (true) {
                gv = ld_relaxed(&prm.s->gate[chunk * 128 + at]);
                const uint32_t ar = ld_relaxed(&prm.s->armed[((cta >> 4) * 14 + min(lane, 13)) * 4]);
                if (__all_sync(0xffffffffu, (gv & 3u) == t2 && ar == t2)) break;
                if (++it > SPIN_LIMIT) __trap();
            }
            asm volatile("fence.acquire.gpu;" ::: "memory");
#pragma unroll
            for (int s = 0; s < 8; s++)
                if ((~sel[s] & 2047u) == (uint32_t)(chunk * 128 + at)) gv |= 0x80000000u;
            reinterpret_cast<uint16_t*>(smem + OFF_G)[at] = (uint16_t)(gv >> 16);
            __syncwarp();
            if (lane == 0) mbar_arrive(bar_g);
        };
        {
            const int tk = (at >> 3) & 7;
            const char* xt = (const char*)prm.x + (~sel[tk] & 2047u) * 2048 + (owner ? 256 : 0) + (at >> 6) * 128 + (at & 7) * 16;
#pragma unroll
            for (int i = 0; i < 7; i++) {
                if (i == 0 || owner) cp_async16(sb + OFF_XS + (2 * i + (at >> 6)) * 1024 + tk * 128 + (((at & 7) ^ tk) << 4), xt + i * 256);
                if (i == 0 || i == 6) asm volatile("cp.async.commit_group;" ::: "memory");
            }
            asm volatile("cp.async.wait_group 1;" ::: "memory");
            fence_async_smem();
            named_bar(2, 128);
            STAMPIF(at == 0, 25);
        }
        if (!owner) help();
        else {
            gate_up([&]() {
                asm volatile("cp.async.wait_all;" ::: "memory");
                fence_async_smem();
                named_bar(2, 128);
            });
            it = 0;
            while (true) {
                const uint4 v = ld_relaxed4(&prm.s->part[cta * 128 + at]);
                if (__all_sync(0xffffffffu, (v.x & 3u) == t2)) {
                    facc[0] += __uint_as_float(v.x); facc[1] += __uint_as_float(v.y); facc[2] += __uint_as_float(v.z); facc[3] += __uint_as_float(v.w);
                    break;
                }
                if (++it > SPIN_LIMIT) __trap();
                __nanosleep(TN(T_RETRY));
            }
            if (!(cta & 1)) {
#pragma unroll
                for (int u = 0; u < 4; u++) {
                    const float v = rbf(facc[u]);
                    facc[u] = __fdividef(v, 1.0f + __expf(-v));
                }
            }
            st_relaxed2(&prm.s->hid[cta * 128 + at], pack_bf(facc[0], facc[1]), pack_bf(facc[2], facc[3]));
        }
        STAMPIF(at == 0, 26);
        gates();
        uint32_t mine = __ballot_sync(0xffffffffu, lane < 8 && (int)((~sel[lane & 7] & 2047u) >> 7) == chunk), tr;
        uint2 xr, xd;
        float gr, rs;
        auto skip = [&](int n) {
#pragma unroll 1
            for (int i = 0; i < n; i++) mine &= mine - 1;
            if (mine) {
                const uint32_t key = sel[__ffs(mine) - 1], kb = key >> 16;
                tr = ~key & 2047u;
                xr = __ldg(reinterpret_cast<const uint2*>(prm.x + (size_t)tr * D_ + dt * 128) + lane);
                rs = rbf(sigmoidf_(bf_lo((kb & 0x8000u) ? (kb & 0x7FFFu) : (~kb & 0xFFFFu))));
                gr = fabsf(__bfloat162float(reinterpret_cast<const __nv_bfloat16*>(smem + OFF_G)[tr & 127]));
                xd = lds64(sb + OFF_DK + 8 * lane);
            }
        };
        mbar_wait(bar_g);
        skip(w);
        {
            mbar_wait(empty + 8 * max(TN(HG), 31));
            const uint2* hp = &prm.s->hid[(cta >> 4) * 14 * 128 + at];
            uint32_t hv[16];
            it = 0;
            while (true) {
                uint32_t top = 0;
#pragma unroll
                for (int j = 0; j < 7; j++) {
                    const uint2 hg = ld_relaxed2(hp + 256 * j), hu = ld_relaxed2(hp + 256 * j + 128);
                    top = max(top, max(hg.x, hu.x));
                    hv[2 * j] = mul_bf2(hg.x, hu.x); hv[2 * j + 1] = mul_bf2(hg.y, hu.y);
                }
                if (__all_sync(0xffffffffu, top != ~0u)) break;
                do {
                    if (++it > SPIN_LIMIT) __trap();
                } while (!__all_sync(0xffffffffu, ld_relaxed(hp + min(lane, 13) * 128 - lane) != ~0u));
            }
            STAMPIF(at == 0 && it > 0, 61);
            hv[14] = hv[15] = 0;
#pragma unroll
            for (int j = 0; j < 4; j++)
                asm volatile("stmatrix.sync.aligned.m8n8.x4.trans.shared.b16 [%0], {%1, %2, %3, %4};" ::"r"(
                                 sb + OFF_HID + (2 * j + (lane >> 4)) * 1024 + (lane & 7) * 128 + (((2 * w + ((lane >> 3) & 1)) ^ (lane & 7)) << 4)),
                             "r"(hv[4 * j]), "r"(hv[4 * j + 1]), "r"(hv[4 * j + 2]), "r"(hv[4 * j + 3]) : "memory");
        }
        fence_async_smem();
        named_bar(2, 128);
        STAMPIF(at == 0, 27);
        down();
#pragma unroll
        for (int u = 0; u < 4; u++)
            st_relaxed(&prm.s->y[((2 * c + (u & 1)) * 8 + (cta >> 4)) * D_ + (cta & 15) * 64 + w * 16 + g + 8 * (u >> 1)], (__float_as_uint(facc[u]) & ~3u) | t2);
        STAMPIF(at == 0, 28);
        sleep_until(clk32() + TN(T_Y));
        while (mine) {
            const uint32_t* yp = &prm.s->y[(__ffs(mine) - 1) * 8 * D_ + dt * 128 + 4 * lane];
            float y[4];
            it = 0;
            while (true) {
                uint32_t bad = 0;
                y[0] = y[1] = y[2] = y[3] = 0.f;
#pragma unroll
                for (int ks = 0; ks < 8; ks++) {
                    const uint4 v = ld_relaxed4(yp + ks * D_);
                    bad |= v.x ^ t2;
                    y[0] += __uint_as_float(v.x); y[1] += __uint_as_float(v.y); y[2] += __uint_as_float(v.z); y[3] += __uint_as_float(v.w);
                }
                if (__all_sync(0xffffffffu, (bad & 3u) == 0)) break;
                if (++it > SPIN_LIMIT) __trap();
            }
            STAMPIF(lane == 0 && it, 62);
#pragma unroll
            for (int u = 0; u < 4; u++) {
                const uint32_t x2 = (u & 2) ? xr.y : xr.x, d2 = mul_bf2(x2, (u & 2) ? xd.y : xd.x);
                y[u] = fmaf(gr, (u & 1) ? bf_hi(d2) : bf_lo(d2), rbf(rbf(1.0f - gr) * rbf(((u & 1) ? bf_hi(x2) : bf_lo(x2)) + rbf(rbf(y[u]) * rs))));
            }
            STAMPIF(lane == 0, 50);
            mbar_wait(bar_stored);
            asm volatile("red.global.add.v4.f32 [%0], {%1, %2, %3, %4};" ::"l"(prm.out + (size_t)tr * D_ + dt * 128 + 4 * lane), "f"(y[0]), "f"(y[1]), "f"(y[2]), "f"(y[3]) : "memory");
            skip(4);
        }
        LSTAMP(lane == 0, 96 + 29);
    } else {
        asm volatile("setmaxnreg.dec.sync.aligned.u32 40;");
        if (warp != 12) sleep_until(cstart + (warp == 13 ? TN(T_SMALL) : warp == 14 ? TN(PF0) - 250 : TN(T_W3)));
        auto behind = [&](int e) { mbar_wait(empty + 8 * e); };
        if (warp == 15) {
            prefetch_map(&mXr);
            named_bar(0, 448);
            asm volatile("bar.arrive 1, 64;" ::: "memory");
#pragma unroll 1
            for (int i = 0; i < 4; i++) {
                const int u = i;
                if (lane == 0) mbar_expect_tx(ffull + 8 * u, TILE);
                sleep_until(cstart + (i == 0 ? TN(RT0) : i == 1 ? TN(RT1) : i == 2 ? TN(RT2) : TN(RT3)));
                if (elect_one()) tma3(sb + OFF_FT + u * TILE, &mXr, u * 256, rid * 16, ffull + 8 * u);
                STAMP(53 + u);
            }
            if (sb & 1023) __trap();
            prefetch_map(&mWg);
            prefetch_map(&mWu);
            prefetch_map(&mWd);
            uint32_t slot = 4, par = 1;
#pragma unroll 1
            for (int j = 0; j < (DBG != 1 ? 14 : 0); j++) {
                const int o = owner ? cta : (cta - 112) * 7 + (j >> 1);
                mbar_wait(fempty + 8 * slot, par);
                if (lane == 0) mbar_expect_tx(ffull + 8 * slot, TILE);
                if (j < NFT) behind(TN(GU_E0) + j * TN(W_NUM) / 4);
                STAMPW(1, 176 + j);
                if (elect_one()) tma2(sb + OFF_FT + slot * TILE, (o & 1) ? &mWu : &mWg, (o >> 1) * 64, (owner ? j + 2 : j & 1) * 64, ffull + 8 * slot);
                if (++slot == NFT) { slot = 0; par ^= 1; }
            }
            if (lane < 9) mbar_expect_tx(lane < 7 ? dfull + 8 * lane : bar_x + 8 * (lane - 7), lane < 7 ? TILE : 2 * TILE);
#pragma unroll 1
            for (int j = 0; j < (DBG != 1 ? 7 : 0); j++) {
                if (j < 3) mbar_wait(fempty + 8 * j, 1);
                behind(min(TN(DL0) + j * TN(DLS) / 4, NBIG - 2));
                if (elect_one()) tma2(sb + OFF_FT + j * TILE, &mWd, (cta & 15) * 64, (cta >> 4) * 448 + j * 64, dfull + 8 * j);
            }
            prefetch_map(&mXe);
#pragma unroll 1
            for (int u = 0; u < 4; u++) {
                if (u == 2) {
                    mbar_wait(bar_dfree + 16);
                    if (elect_one()) tma5(sb + tail_c(8), &mCim, c_col(63), dt * 8, full + 8 * (NBIG + 8));
                }
                mbar_wait(bar_dfree);
                behind(u < 2 ? TN(DN_E0) + u : NBIG + NSPL);
                if (elect_one())
                    asm volatile("cp.async.bulk.tensor.5d.shared::cluster.global.mbarrier::complete_tx::bytes [%0], [%1, {%3, %6, %6, %4, %5}], [%2];"
                                 ::"r"(sb + (u < 2 ? OFF_FT : tail_c(0)) + (u & 1) * TILE), "l"(&mXe), "r"(bar_x + 4 * (u & 2)), "r"(dt * 128 + (u & 1) * 64),
                                 "r"(u & 2), "r"(chunk * 4), "r"(0) : "memory");
                if (u < 2) {
                    if (elect_one())
                        asm volatile("cp.async.bulk.prefetch.tensor.5d.L2.global [%0, {%1, %4, %4, %2, %3}];" ::"l"(&mXe), "r"(dt * 128 + u * 64), "r"(2), "r"(chunk * 4), "r"(0) : "memory");
                }
            }
        } else if (warp == 13) {
#pragma unroll
            for (int u = 0; u < 8; u++) {
                const int row = (u >> 2) * 4 + (lane >> 3);
                cp_async16(sb + OFF_XS + (u & 3) * 1024 + row * 128 + (((lane & 7) ^ row) << 4), (const char*)(u < 4 ? prm.w_r : prm.gate_w) + (u & 3) * 512 + lane * 16);
            }
            STAMP(57);
            const uint32_t tag = ld_relaxed(&prm.s->epoch[cta]) + 1;
            named_bar(1, 64);
            *reinterpret_cast<uint2*>(smem + OFF_EPOCH) = make_uint2(tag, tag % 3u + 1u);
            STAMPIF(tag, 58);
            asm volatile("cp.async.wait_all;" ::: "memory");
            STAMP(59);
            fence_async_smem();
            __syncwarp();
            if (lane == 0) {
                mbar_arrive(bar_epoch);
                prm.s->epoch[cta] = tag;
            }
            sleep_until(cstart + TN(T_BASE));
            {
                const uint2 st = ld_relaxed2(&prm.s->start[2 * lane]);
                const uint32_t d = st.x - cstart + 512u, age = gtime32() - st.y;
                const uint32_t m = __reduce_max_sync(0xffffffffu, d < 1024u && age < 4096u ? (d << 12) | age : 0u);
                const uint32_t late = (m & 4095u) - __reduce_min_sync(0xffffffffu, age);
                *reinterpret_cast<volatile uint32_t*>(smem + OFF_EPOCH + 8) = cstart + (m ? (m >> 12) - 512u + min(late, 256u) * TN(G_NS) / 4 : 0u);
                __syncwarp();
                if (lane == 0) mbar_arrive(bar_base);
                STAMP(60);
            }
            mbar_wait(bar_const);
            asm volatile("fence.acq_rel.gpu;" ::: "memory");
            if (lane < 4) st_relaxed2(&prm.s->armed[cta * 4 + lane], tag % 3u + 1u, 0u);
            prefetch_map(&mCre);
            prefetch_map(&mCim);
            const char* src = reinterpret_cast<const char*>(prm.s->h) + (size_t)chunk * 524288;
            uint32_t slot = 32 % NST, hpar = 0, rpar = 0;
#pragma unroll 1
            for (int i = 32; i < NBIG; i++) {
                mbar_wait(hfull + 8 * slot, hpar);
                STAMPIF(i == 32 || i == 33, 14 + (i & 1));
                rpar = check_tile<16>(sb, sb + slot * SLOT, probe, src, tag, bar_retry, rpar, TN(T_RETRY));
                if (lane == 0) mbar_expect_tx(full + 8 * i, 2 * TILE);
                STAMPIF(i == 32 || i == 33, 16 + (i & 1));
                src += 2 * TILE;
                slot = slot == NST - 1 ? 0 : slot + 1;
                hpar ^= slot == 32 % NST;
            }
        } else if (warp == 14) {
            prefetch_map(&mPB);
            auto pf_c = [&](int k) { prefetch_slice(&mPC, 4 * (k >> 1), cta * 8 + (k & 1) * 4); };
            {
                const char* px = (const char*)prm.x + (rid * 16 + (lane >> 1)) * 2048 + (lane & 1) * 128;
                const char* pb = (const char*)((lane & 8) ? prm.b_im : prm.b_re) + (cta * 4 + ((lane >> 1) & 3)) * 2048 + (lane & 1) * 128;
#pragma unroll 1
                for (int k = 1; k < 8; k++) {
                    sleep_until(cstart + TN(PF0) + (k - 1) * TN(PF1));
                    prefetch_l2(px + k * 256);
                    if (lane < 16) prefetch_l2(pb + k * 256);
                }
            }
            named_bar(7, 160);
            mbar_wait(bar_base);
#pragma unroll 1
            for (int k = 0; k < 4; k++) {
                behind(TN(PB_E0) + TN(PB_STEP) * k);
                if (elect_one()) prefetch_slice(&mPB, 4 * k, 512 + cta * 4);
            }
#pragma unroll 1
            for (int k = 0; k < TN(PC_N); k++) {
                behind(min(TN(PC_E0) + TN(PC_STEP) * k / 2, 25));
                if (elect_one()) pf_c(k);
            }
            int pk = TN(PC_N), pe = TN(PC_E1);
            auto own_part = [&](int e) {
                if (!(TDBG & 16) && !mbar_test(bar_out + 8 * e, 0)) {
                    mbar_wait(bar_out + 8 * e);
                    sleep_until(clk32() + TN(T_OWN));
                    STAMP(11);
                }
            };
            const char* src = reinterpret_cast<const char*>(prm.s->h) + (size_t)chunk * 524288;
            uint32_t slot = 32 % NST;
#pragma unroll 1
            for (int i = 32; i < NBIG; i++) {
                if (!(i & 3)) own_part((i - 32) >> 2);
                mbar_wait(empty + 8 * (i - NST));
                PSTAMP(i);
                if (elect_one()) {
                    mbar_expect_tx(hfull + 8 * slot, 2 * TILE);
                    bulk_load(sb + slot * SLOT, src, 2 * TILE, hfull + 8 * slot);
                    tma5(sb + slot * SLOT + 2 * TILE, (i & 4) ? &mCim : &mCre, c_col(i), dt * 8, full + 8 * i);
                }
                if (i == pe && pk < 8) {
                    if (elect_one()) pf_c(pk);
                    pk++; pe += TN(PC_S1);
                }
                src += 2 * TILE;
                slot = slot == NST - 1 ? 0 : slot + 1;
            }
            src -= (NBIG - 32) * 2 * TILE;
#pragma unroll
            for (int k = 0; k < 2 * NSPL - 2; k++) {
                if (k == 0 || k == 2) own_part(6 + k / 2);
                mbar_wait(empty + 8 * (NBIG - NST + k));
                if (k >= 1 && k <= 4) {
                    if (elect_one()) {
#pragma unroll
                        for (int j = 2 * k - 2; j < 2 * k; j++)
                            tma5(sb + tail_c(j), ((NBIG + j) & 4) ? &mCim : &mCre, c_col(NBIG + j), dt * 8, full + 8 * (NBIG + j));
                    }
                }
                if (k == 4) continue;
                if (k == 2) mbar_wait(bar_dfree + 8);
                if (elect_one()) {
#pragma unroll
                    for (int n = k < 5 ? 2 * k : k + 2; n < (k < 3 ? 2 * k + 2 : k == 3 ? 7 : k + 3); n++) {
                        mbar_expect_tx(hfull + 8 * (NST + n % 7), TILE);
                        bulk_load(sb + tail_h(n), src + tail_src(n), TILE, hfull + 8 * (NST + n % 7));
                    }
                }
            }
        } else {
            if (elect_one()) {
#pragma unroll
                for (int i = 0; i < NST; i++) mbar_init(full + 8 * i, 1);
                fence_mbar_init();
            }
            __syncwarp();
            asm volatile("bar.arrive 5, 160;" ::: "memory");
            asm volatile("bar.arrive 0, 448;" ::: "memory");
#pragma unroll 1
            for (int i = 0; i < NST; i++) {
                if (elect_one()) {
                    mbar_expect_tx(full + 8 * i, SLOT);
                    tma5b(sb + i * SLOT, &mB, i * 64, dt * 4, full + 8 * i);
                    tma4(sb + i * SLOT + 2 * TILE, &mX, i * 64, chunk * 64, full + 8 * i);
                }
                STAMPIF(i == 0, 1);
            }
            STAMP(2);
            named_bar(6, 160);
            uint32_t dst = sb;
#pragma unroll 1
            for (int i = NST; i < 32; i++) {
                if (i == 2 * NST) mbar_wait(bar_base);
                if (lane == 0) mbar_expect_tx(full + 8 * i, SLOT);
                mbar_wait(empty + 8 * (i - NST));
                PSTAMP(i);
                if (elect_one()) {
                    tma5b(dst, &mB, (i & 15) * 64, (i >> 4) * 64 + dt * 4, full + 8 * i);
                    tma4(dst + 2 * TILE, &mX, (i & 15) * 64, chunk * 64, full + 8 * i);
                }
                dst = dst == sb + (NST - 1) * SLOT ? sb : dst + SLOT;
            }
        }
    }
}

typedef CUresult (*EncodeFn)(CUtensorMap*, CUtensorMapDataType, cuuint32_t, void*, const cuuint64_t*, const cuuint64_t*, const cuuint32_t*,
                             const cuuint32_t*, CUtensorMapInterleave, CUtensorMapSwizzle, CUtensorMapL2promotion, CUtensorMapFloatOOBfill);

bool encode(EncodeFn fn, CUtensorMap* m, const void* ptr, int rank, const cuuint64_t* dims, const cuuint64_t* strides, const cuuint32_t* box,
            CUtensorMapL2promotion promo = CU_TENSOR_MAP_L2_PROMOTION_NONE) {
    const cuuint32_t es[5] = {1, 1, 1, 1, 1};
    return fn(m, CU_TENSOR_MAP_DATA_TYPE_BFLOAT16, rank, const_cast<void*>(ptr), dims, strides, box, es, CU_TENSOR_MAP_INTERLEAVE_NONE,
              CU_TENSOR_MAP_SWIZZLE_128B, promo, CU_TENSOR_MAP_FLOAT_OOB_FILL_NONE) == CUDA_SUCCESS;
}

}

extern "C" void kernel_launch(void* const* d_in, const int* in_sizes, int n_in, void* d_out, int out_size) {
    (void)in_sizes; (void)n_in; (void)out_size;
    Params prm;
    prm.x = (const __nv_bfloat16*)d_in[0];
    prm.lam_re = (const __nv_bfloat16*)d_in[1];
    prm.lam_im = (const __nv_bfloat16*)d_in[2];
    prm.b_re = (const __nv_bfloat16*)d_in[3];
    prm.b_im = (const __nv_bfloat16*)d_in[4];
    prm.c_re = (const __nv_bfloat16*)d_in[5];
    prm.c_im = (const __nv_bfloat16*)d_in[6];
    prm.log_dt = (const __nv_bfloat16*)d_in[7];
    prm.dskip = (const __nv_bfloat16*)d_in[8];
    prm.w_r = (const __nv_bfloat16*)d_in[10];
    prm.gate_w = (const __nv_bfloat16*)d_in[14];
    prm.out = (float*)d_out;
    cudaGetSymbolAddress((void**)&prm.s, g_scratch);
    prm.swapped = prm.b_im < prm.b_re;

    void* fnp = nullptr;
    cudaDriverEntryPointQueryResult qr;
    cudaGetDriverEntryPoint("cuTensorMapEncodeTiled", &fnp, cudaEnableDefault, &qr);
    EncodeFn fn = (EncodeFn)fnp;
    cudaFuncSetAttribute(fused_kernel, cudaFuncAttributeMaxDynamicSharedMemorySize, SMEM_BYTES);

    CUtensorMap mX, mB, mCre, mCim, mWg, mWu, mWd, mXr, mPB, mPC, mXe;
    const cuuint64_t row = 2048;
    {
        const cuuint64_t dims[4] = {1024, 2, 4, 976}, st[3] = {row, 32 * row, 2 * row};
        const cuuint32_t box[4] = {64, 2, 4, 16};
        encode(fn, &mX, prm.x, 4, dims, st, box, PROMO);
    }
    {
        const char *lo = (const char*)(prm.swapped ? prm.b_im : prm.b_re), *hi = (const char*)(prm.swapped ? prm.b_re : prm.b_im);
        const cuuint64_t dims[5] = {1024, 8, 2, 96, 2}, st[4] = {row, (cuuint64_t)(hi - lo), 8 * row, 256 * row};
        const cuuint32_t box[5] = {64, 8, 2, 4, 2};
        encode(fn, &mB, lo, 5, dims, st, box, PROMO);
    }
    {
        const cuuint64_t dims[5] = {1024, 2, 4, 2, 64}, st[4] = {row, 4 * row, 2 * row, 16 * row};
        const cuuint32_t box[5] = {64, 2, 4, 2, 8};
        encode(fn, &mCre, prm.c_re, 5, dims, st, box);
        encode(fn, &mCim, prm.c_im, 5, dims, st, box);
    }
    {
        const cuuint64_t dims[2] = {F_, D_}, st[1] = {F_ * 2}, dimsd[2] = {D_, F_}, std_[1] = {row};
        const cuuint32_t box[2] = {64, 64};
        encode(fn, &mWg, d_in[11], 2, dims, st, box);
        encode(fn, &mWu, d_in[12], 2, dims, st, box);
        encode(fn, &mWd, d_in[13], 2, dimsd, std_, box);
    }
    for (int i = 0; i < 2; i++) {
        const char *p = (const char*)(i ? prm.c_re : prm.b_re), *q = (const char*)(i ? prm.c_im : prm.b_im);
        const cuuint64_t dims[4] = {64, 16, 1024, 2}, st[3] = {128, row, (cuuint64_t)(p < q ? q - p : p - q)};
        const cuuint32_t box[4] = {16, 4, 4, 2};
        encode(fn, i ? &mPC : &mPB, p < q ? p : q, 4, dims, st, box, CU_TENSOR_MAP_L2_PROMOTION_L2_128B);
    }
    {
        const cuuint64_t dims[3] = {D_ - 192, S_, 4}, st[2] = {row, 128};
        const cuuint32_t box[3] = {64, 16, 4};
        encode(fn, &mXr, prm.x, 3, dims, st, box);
    }
    {
        const cuuint64_t dims[5] = {1024, 2, 4, 4, S_ / 32}, st[4] = {4 * row, row, 8 * row, 32 * row};
        const cuuint32_t box[5] = {64, 2, 4, 2, 4};
        encode(fn, &mXe, prm.x, 5, dims, st, box);
    }
    fused_kernel<<<NCTA, 512, SMEM_BYTES, cudaStreamPerThread>>>(prm, mX, mB, mCre, mCim, mWg, mWu, mWd, mXr, mPB, mPC, mXe);
}
```

```cpp
#include <cuda_runtime.h>
#include <cuda_bf16.h>
#include <cuda.h>
#include <stdint.h>

namespace {

constexpr int S_ = 2048, D_ = 1024, F_ = 3584;
constexpr int NCTA = 128;
constexpr int NSPL = 9, NBIG = 64 - NSPL, NENT = NBIG + 2 * NSPL;
constexpr int NST = 5;
constexpr int NFT = 5;
constexpr uint32_t SLOT = 32768, TILE = 8192;
constexpr uint32_t OFF_FT = NST * SLOT;
constexpr uint32_t OFF_XS = OFF_FT + NFT * TILE;
constexpr uint32_t OFF_LIST = OFF_XS + 8192;
constexpr uint32_t OFF_RED = OFF_XS + 4096;
constexpr uint32_t OFF_CONST = OFF_XS + 16384;
constexpr uint32_t OFF_M = OFF_CONST + 8192;
constexpr uint32_t OFF_HID = OFF_CONST;
constexpr uint32_t OFF_G = OFF_M + 512;
constexpr uint32_t OFF_DK = OFF_G + 256;
constexpr uint32_t OFF_FULL = OFF_DK + 256;
constexpr uint32_t OFF_EMPTY = OFF_FULL + 103 * 8;
constexpr uint32_t OFF_KEYS = OFF_EMPTY + 87 * 8;
constexpr uint32_t OFF_SEL = OFF_KEYS + 32;
constexpr uint32_t OFF_EPOCH = OFF_SEL + 32;
constexpr uint32_t OFF_PROF = OFF_EPOCH + 16;
constexpr uint32_t SMEM_BYTES = OFF_PROF + 432;
static_assert(SMEM_BYTES <= 232448, "smem");

static_assert(NBIG % NST == 0, "tail layout");
__host__ __device__ constexpr uint32_t tail_c(int j) { return j < 8 ? SLOT + j * 2 * TILE : OFF_FT + 5 * TILE; }
__host__ __device__ constexpr uint32_t tail_h(int n) { return n % 7 < 4 ? n % 7 * TILE : OFF_FT + (n % 7 - 2) * TILE; }
__host__ __device__ constexpr uint32_t tail_src(int n) { return (n % NSPL + NBIG - 32) * 2 * TILE + n / NSPL * TILE; }
__host__ __device__ constexpr int c_col(int i) { return ((i & 3) + ((i >> 1) & 12)) * 64; }

constexpr uint32_t SPIN_LIMIT = 1u << 18;

struct Scratch {
    uint2 carry[16 * 1024];
    uint2 hid[NCTA * 128];
    uint32_t y[8 * 8 * D_];
    uint32_t key[NCTA * 8];
    uint32_t gate[S_];
    uint4 part[112 * 128];
    uint2 armed[NCTA * 4];
    unsigned int epoch[256];
    uint4 start[32 * 2];
    uint4 h[16 * 32 * 1024];
};
__device__ __align__(1024) Scratch g_scratch;
#define STAMPW_(cond, w) do {} while (0)
#define GSTAMP(cond, w) do {} while (0)
#define LSTAMP(cond, w) STAMPW_(cond, w)
#define LT 0
#define STAMPW(cond, w) STAMPW_(cond, w)
#define STAMPIF(cond, i) STAMPW(cond, 96 + (i))
#define STAMP(i) STAMPW(1, 96 + (i))
#define KSTAMP(i) STAMPW((threadIdx.x & 127) == 0, i)
#define PSTAMP(i) STAMPW((i) < 56 && (i) >= 32, 160 + (i))

struct Params {
    const __nv_bfloat16 *x, *b_re, *b_im, *lam_re, *lam_im, *c_re, *c_im, *log_dt, *dskip, *w_r, *gate_w;
    float* out;
    Scratch* s;
    int swapped;
};

__device__ __forceinline__ uint32_t smem_u32(const void* p) { return (uint32_t)__cvta_generic_to_shared(p); }
__device__ __forceinline__ void mbar_init(uint32_t bar, uint32_t cnt) { asm volatile("mbarrier.init.shared::cta.b64 [%0], %1;" ::"r"(bar), "r"(cnt) : "memory"); }
__device__ __forceinline__ void mbar_expect_tx(uint32_t bar, uint32_t bytes) { asm volatile("mbarrier.arrive.expect_tx.shared::cta.b64 _, [%0], %1;" ::"r"(bar), "r"(bytes) : "memory"); }
__device__ __forceinline__ void mbar_arrive(uint32_t bar) { asm volatile("mbarrier.arrive.shared::cta.b64 _, [%0];" ::"r"(bar) : "memory"); }
__device__ __forceinline__ bool mbar_test(uint32_t bar, uint32_t parity) {
    uint32_t ok;
    asm volatile("{ .reg .pred p; mbarrier.test_wait.parity.shared::cta.b64 p, [%1], %2; selp.u32 %0, 1, 0, p; }" : "=r"(ok) : "r"(bar), "r"(parity) : "memory");
    return __all_sync(0xffffffffu, ok);
}
__device__ __forceinline__ void mbar_wait(uint32_t bar, uint32_t parity = 0) {
    asm volatile("{ .reg .pred p; .reg .u32 n; mov.u32 n, 0;\nW%=: mbarrier.try_wait.parity.shared::cta.b64 p, [%0], %1; @p bra D%=;\n"
                 "add.u32 n, n, 0x4000; setp.ne.u32 p, n, 0; @p bra W%=; trap;\nD%=: }" ::"r"(bar), "r"(parity) : "memory");
}
__device__ __forceinline__ bool elect_one() {
    uint32_t pred;
    asm volatile("{ .reg .pred P; elect.sync _|P, 0xffffffff; selp.b32 %0, 1, 0, P; }" : "=r"(pred));
    return pred;
}
__device__ __forceinline__ void named_bar(int id, int n) { asm volatile("bar.sync %0, %1;" ::"r"(id), "r"(n) : "memory"); }
__device__ __forceinline__ void fence_mbar_init() { asm volatile("fence.mbarrier_init.release.cluster;" ::: "memory"); }
__device__ __forceinline__ void fence_async_smem() { asm volatile("fence.proxy.async.shared::cta;" ::: "memory"); }

__device__ __forceinline__ void bulk_load(uint32_t dst, const void* src, uint32_t bytes, uint32_t bar) {
    asm volatile("cp.async.bulk.shared::cluster.global.mbarrier::complete_tx::bytes [%0], [%1], %2, [%3];" ::"r"(dst), "l"(src), "r"(bytes), "r"(bar) : "memory");
}
__device__ __forceinline__ void cp_async16(uint32_t dst, const void* src) { asm volatile("cp.async.cg.shared.global [%0], [%1], 16;" ::"r"(dst), "l"(src) : "memory"); }
__device__ __forceinline__ void sts128(uint32_t a, uint32_t x, uint32_t y, uint32_t z, uint32_t w) {
    asm volatile("st.shared.v4.u32 [%0], {%1,%2,%3,%4};" ::"r"(a), "r"(x), "r"(y), "r"(z), "r"(w) : "memory");
}
__device__ __forceinline__ uint2 lds64(uint32_t a) {
    uint2 v;
    asm volatile("ld.shared.v2.u32 {%0,%1}, [%2];" : "=r"(v.x), "=r"(v.y) : "r"(a) : "memory");
    return v;
}
__device__ __forceinline__ uint32_t lds32(uint32_t a) {
    uint32_t v;
    asm volatile("ld.volatile.shared.u32 %0, [%1];" : "=r"(v) : "r"(a) : "memory");
    return v;
}
__device__ __forceinline__ void stg128(void* p, uint32_t x, uint32_t y, uint32_t z, uint32_t w) {
    asm volatile("st.global.v4.u32 [%0], {%1,%2,%3,%4};" ::"l"(p), "r"(x), "r"(y), "r"(z), "r"(w) : "memory");
}
__device__ __forceinline__ void st_relaxed(void* p, uint32_t x) { asm volatile("st.relaxed.gpu.global.b32 [%0], %1;" ::"l"(p), "r"(x) : "memory"); }
__device__ __forceinline__ void st_relaxed2(void* p, uint32_t x, uint32_t y) { asm volatile("st.relaxed.gpu.global.v2.b32 [%0], {%1, %2};" ::"l"(p), "r"(x), "r"(y) : "memory"); }
__device__ __forceinline__ void st_relaxed4(void* p, uint32_t x, uint32_t y, uint32_t z, uint32_t w) {
    asm volatile("st.relaxed.gpu.global.v4.b32 [%0], {%1, %2, %3, %4};" ::"l"(p), "r"(x), "r"(y), "r"(z), "r"(w) : "memory");
}
__device__ __forceinline__ uint32_t ld_relaxed(const void* p) {
    uint32_t v;
    asm volatile("ld.relaxed.gpu.global.b32 %0, [%1];" : "=r"(v) : "l"(p) : "memory");
    return v;
}
__device__ __forceinline__ uint2 ld_relaxed2(const void* p) {
    uint2 v;
    asm volatile("ld.relaxed.gpu.global.v2.b32 {%0, %1}, [%2];" : "=r"(v.x), "=r"(v.y) : "l"(p) : "memory");
    return v;
}
__device__ __forceinline__ uint4 ld_relaxed4(const void* p) {
    uint4 v;
    asm volatile("ld.relaxed.gpu.global.v4.b32 {%0, %1, %2, %3}, [%4];" : "=r"(v.x), "=r"(v.y), "=r"(v.z), "=r"(v.w) : "l"(p) : "memory");
    return v;
}
__device__ __forceinline__ uint32_t clk32() { uint32_t c; asm volatile("mov.u32 %0, %%clock;" : "=r"(c)); return c; }
__device__ __forceinline__ uint32_t gtime32() { uint32_t c; asm volatile("mov.u32 %0, %%globaltimer_lo;" : "=r"(c)); return c; }
__device__ __forceinline__ void sched_fence(uint32_t t) { while ((int)(clk32() - t) < 0) {} }
__device__ __forceinline__ void sleep_until(uint32_t t) { while ((int)(clk32() - t) < 0) __nanosleep(40); }

__device__ __forceinline__ void tma2(uint32_t dst, const CUtensorMap* m, int c0, int c1, uint32_t bar) {
    asm volatile("{ .reg .b64 pol; createpolicy.fractional.L2::evict_first.b64 pol;\n"
                 "cp.async.bulk.tensor.2d.shared::cluster.global.mbarrier::complete_tx::bytes.L2::cache_hint [%0], [%1, {%3, %4}], [%2], pol; }"
                 ::"r"(dst), "l"(m), "r"(bar), "r"(c0), "r"(c1) : "memory");
}
__device__ __forceinline__ void tma3(uint32_t dst, const CUtensorMap* m, int c0, int c1, uint32_t bar) {
    asm volatile("cp.async.bulk.tensor.3d.shared::cluster.global.mbarrier::complete_tx::bytes [%0], [%1, {%3, %4, %5}], [%2];"
                 ::"r"(dst), "l"(m), "r"(bar), "r"(c0), "r"(c1), "r"(0) : "memory");
}
__device__ __forceinline__ void tma4(uint32_t dst, const CUtensorMap* m, int c0, int c3, uint32_t bar) {
    asm volatile("cp.async.bulk.tensor.4d.shared::cluster.global.mbarrier::complete_tx::bytes [%0], [%1, {%3, %5, %5, %4}], [%2];"
                 ::"r"(dst), "l"(m), "r"(bar), "r"(c0), "r"(c3), "r"(0) : "memory");
}
__device__ __forceinline__ void tma5(uint32_t dst, const CUtensorMap* m, int c0, int c4, uint32_t bar) {
    asm volatile("cp.async.bulk.tensor.5d.shared::cluster.global.mbarrier::complete_tx::bytes [%0], [%1, {%3, %5, %5, %5, %4}], [%2];"
                 ::"r"(dst), "l"(m), "r"(bar), "r"(c0), "r"(c4), "r"(0) : "memory");
}
__device__ __forceinline__ void tma5b(uint32_t dst, const CUtensorMap* m, int c0, int c3, uint32_t bar) {
    asm volatile("cp.async.bulk.tensor.5d.shared::cluster.global.mbarrier::complete_tx::bytes [%0], [%1, {%3, %5, %5, %4, %5}], [%2];"
                 ::"r"(dst), "l"(m), "r"(bar), "r"(c0), "r"(c3), "r"(0) : "memory");
}
__device__ __forceinline__ void prefetch_l2(const void* p) { asm volatile("prefetch.global.L2 [%0];" ::"l"(p)); }
__device__ __forceinline__ void prefetch_slice(const CUtensorMap* m, int line, int row) {
    asm volatile("cp.async.bulk.prefetch.tensor.4d.L2.global [%0, {%3, %1, %2, %3}];" ::"l"(m), "r"(line), "r"(row), "r"(0) : "memory");
}
__device__ __forceinline__ void prefetch_map(const CUtensorMap* m) { asm volatile("prefetch.tensormap [%0];" ::"l"(m)); }
__device__ __forceinline__ uint32_t uni(uint32_t v) { return __shfl_sync(0xffffffffu, v, 0); }

__device__ __forceinline__ uint32_t make_desc(uint32_t addr) { return ((addr & 0x3FFFF) >> 4) | (1u << 16); }
__device__ __forceinline__ uint32_t make_desc_h(uint32_t addr) { return ((addr & 0x3FFFF) >> 4) | (32u << 16); }
template <int H> __device__ __forceinline__ uint64_t desc64(uint32_t lo) {
    uint64_t d;
    asm volatile("mov.b64 %0, {%1, %2};" : "=l"(d) : "r"(lo), "n"(64u | ((H ? 2u : 1u) << 30)));
    return d;
}
__device__ __forceinline__ void wgmma_fence() { asm volatile("wgmma.fence.sync.aligned;" ::: "memory"); }
__device__ __forceinline__ void wgmma_commit() { asm volatile("wgmma.commit_group.sync.aligned;" ::: "memory"); }
template <int N> __device__ __forceinline__ void wgmma_wait() { asm volatile("wgmma.wait_group.sync.aligned %0;" ::"n"(N) : "memory"); }

#define R8(d, i) "+f"(d[i]), "+f"(d[i + 1]), "+f"(d[i + 2]), "+f"(d[i + 3]), "+f"(d[i + 4]), "+f"(d[i + 5]), "+f"(d[i + 6]), "+f"(d[i + 7])
#define R64(d) R8(d, 0), R8(d, 8), R8(d, 16), R8(d, 24), R8(d, 32), R8(d, 40), R8(d, 48), R8(d, 56)
template <int TA>
__device__ __forceinline__ void wgmma_n128(float (&d)[64], uint64_t da, uint64_t db, int scale_d = 1) {
    asm volatile("{ .reg .pred p; setp.ne.b32 p, %66, 0;\n"
                 "wgmma.mma_async.sync.aligned.m64n128k16.f32.bf16.bf16 "
                 "{%0,%1,%2,%3,%4,%5,%6,%7,%8,%9,%10,%11,%12,%13,%14,%15,%16,%17,%18,%19,%20,%21,%22,%23,%24,%25,%26,%27,%28,%29,%30,%31,"
                 "%32,%33,%34,%35,%36,%37,%38,%39,%40,%41,%42,%43,%44,%45,%46,%47,%48,%49,%50,%51,%52,%53,%54,%55,%56,%57,%58,%59,%60,%61,%62,%63}, "
                 "%64, %65, p, 1, 1, %67, 0; }"
                 : R64(d)
                 : "l"(da), "l"(db), "r"(scale_d), "n"(TA));
}
__device__ __forceinline__ void pin4(float (&d)[4]) { asm volatile("" : "+f"(d[0]), "+f"(d[1]), "+f"(d[2]), "+f"(d[3])::"memory"); }
__device__ __forceinline__ void pin64(float (&d)[64]) { asm volatile("" : R64(d)::"memory"); }

template <int TA>
__device__ __forceinline__ void wgmma_n8(float (&d)[4], uint64_t da, uint64_t db, int scale_d = 1) {
    asm volatile("{ .reg .pred p; setp.ne.b32 p, %7, 0;\n"
                 "wgmma.mma_async.sync.aligned.m64n8k16.f32.bf16.bf16 {%0,%1,%2,%3}, %4, %5, p, 1, 1, %6, 0; }"
                 : "+f"(d[0]), "+f"(d[1]), "+f"(d[2]), "+f"(d[3])
                 : "l"(da), "l"(db), "n"(TA), "r"(scale_d));
}

__device__ __forceinline__ float bf_lo(uint32_t u) { return __uint_as_float(u << 16); }
__device__ __forceinline__ float bf_hi(uint32_t u) { return __uint_as_float(u & 0xFFFF0000u); }
__device__ __forceinline__ float rbf(float v) { return __bfloat162float(__float2bfloat16_rn(v)); }
__device__ __forceinline__ uint32_t pack_bf(float lo, float hi) {
    uint32_t r;
    asm("cvt.rn.bf16x2.f32 %0, %1, %2;" : "=r"(r) : "f"(hi), "f"(lo));
    return r;
}
__device__ __forceinline__ uint32_t mul_bf2(uint32_t a, uint32_t b) {
    uint32_t r;
    asm("mul.rn.bf16x2 %0, %1, %2;" : "=r"(r) : "r"(a), "r"(b));
    return r;
}
__device__ __forceinline__ uint32_t fma_bf2(uint32_t a, uint32_t b, uint32_t c) {
    uint32_t r;
    asm("fma.rn.bf16x2 %0, %1, %2, %3;" : "=r"(r) : "r"(a), "r"(b), "r"(c));
    return r;
}
__device__ __forceinline__ float2 cmul(float2 a, float2 b) { return make_float2(a.x * b.x - a.y * b.y, a.x * b.y + a.y * b.x); }
__device__ __forceinline__ float2 cfma(float2 a, float2 b, float2 c) {
    return make_float2(fmaf(a.x, b.x, fmaf(-a.y, b.y, c.x)), fmaf(a.x, b.y, fmaf(a.y, b.x, c.y)));
}
__device__ __forceinline__ float sigmoidf_(float v) { return __fdividef(1.0f, 1.0f + expf(-v)); }

#define SCHED_NAMES T_W0, T_INIT, T_SMALL, T_W3, PF0, PF1, RT0, RT1, RT2, RT3, T_BASE, G_NS, GT0, GL, GQ, GT1, G0, T_CP0, T_CP1, GAP0, GAP1, T_OWN, \
    T_RETRY, T_Y, RS_E, PB_E0, PB_STEP, PC_E0, PC_STEP, PC_N, PC_E1, PC_S1, GU_E0, W_NUM, GC0, GCS, GCS4, GCH, HG, DL0, DLS, DN_E0
enum { SCHED_NAMES, NTUNE };
constexpr int sched_default[NTUNE] = {
    600, 1000, 1000, 1000,
    1100, 400,
    2200, 2700, 3200, 3700,
    2500, 7,
    6200, 600, 1023, 7200,
    800, 900, 900,
    300, 300,
    1000, 200, 700,
    4,
    4, 1, 11, 4, 6, 50, 3,
    4, 8, 14, 8, 6, 11,
    43, 37, 8, 48};
template <int I> struct Sched { static constexpr int v = sched_default[I]; };
#define TN(i) (Sched<i>::v)
#define DBG 0
#define TDBG 0
#define X0 1
#define GE 8
#define PROMO CU_TENSOR_MAP_L2_PROMOTION_L2_256B

template <int TA, class H>
__device__ __forceinline__ void run_entry(uint32_t lo32, uint32_t prev, int accumulate, float (&accA)[64], float (&accB)[64], H inside) {
    const uint64_t da = desc64<TA>(lo32), db = TA ? desc64<0>(lo32 + (2 * TILE >> 4) - (31u << 16)) : da + (2 * TILE >> 4);
    wgmma_fence();
#pragma unroll
    for (int kk = 0; kk < 4; kk++) {
        wgmma_n128<TA>(accA, da + kk * (TA ? 128 : 2), db + kk * 2, kk > 0 ? 1 : accumulate);
        wgmma_n128<TA>(accB, da + 512 + kk * (TA ? 128 : 2), db + kk * 2, kk > 0 ? 1 : accumulate);
        if (kk == 1) {
            wgmma_commit();
            wgmma_wait<1>();
            if ((threadIdx.x & 31) == 0) mbar_arrive(prev);
            inside();
        }
    }
    wgmma_commit();
}
template <int TA, class H>
__device__ __forceinline__ void run_entries(uint32_t sb, int lo, int hi, int slot, float (&accA)[64], float (&accB)[64], H after) {
    const uint32_t da0 = TA ? make_desc_h(sb) : make_desc(sb), dlast = da0 + (NST - 1) * (SLOT >> 4);
    uint32_t prev = sb + OFF_FULL + 8 * 101, bar = sb + OFF_FULL + 8 * lo, lo32 = da0 + slot * (SLOT >> 4);
    int accumulate = 0;
#pragma unroll 1
    for (int i = lo; i < hi; i++) {
        mbar_wait(bar);
        KSTAMP(i);
        run_entry<TA>(lo32, prev, accumulate, accA, accB, []() {});
        prev = bar + (OFF_EMPTY - OFF_FULL);
        bar += 8;
        lo32 = lo32 == dlast ? da0 : lo32 + (SLOT >> 4);
        accumulate = 1;
        after(i);
    }
}

template <int TA>
__device__ __forceinline__ void small_tile(float (&acc)[4], uint32_t alo, uint32_t blo, bool first) {
    const uint64_t da = desc64<0>(alo), db = desc64<0>(blo);
#pragma unroll
    for (int kk = 0; kk < 4; kk++) wgmma_n8<TA>(acc, da + kk * (TA ? 128 : 2), db + kk * 2, kk > 0 || !first);
}

template <int N>
__device__ __forceinline__ uint32_t check_tile(uint32_t sb, uint32_t dst, uint32_t probe, const char* src, uint32_t par, uint32_t bar, uint32_t phase, uint32_t pause) {
    if (TDBG & 4) return phase;
#pragma unroll 1
    for (uint32_t it = 0; it < SPIN_LIMIT; it++) {
        uint32_t v[N], bad = 0;
#pragma unroll
        for (int u = 0; u < N; u++) v[u] = lds32(dst + probe + (u >> 1) * 2048 + (u & 1) * 256);
#pragma unroll
        for (int u = 0; u < N; u += 4)
            asm("{ .reg .b32 a, b; lop3.b32 a, %1, %2, %5, 0x7E; lop3.b32 b, %3, %4, %5, 0x7E; lop3.b32 %0, %0, a, b, 0xFE; }"
                : "+r"(bad) : "r"(v[u]), "r"(v[u + 1]), "r"(v[u + 2]), "r"(v[u + 3]), "r"(par));
        if (!__any_sync(0xffffffffu, bad & 1u)) return phase;
        STAMP(10);
        __nanosleep(pause);
        if (elect_one()) {
            mbar_expect_tx(bar, N * 1024);
            bulk_load(dst, src, N * 1024, bar);
        }
        mbar_wait(bar, phase);
        phase ^= 1;
    }
    __trap();
    return 0;
}

__global__ void __launch_bounds__(512, 1)
fused_kernel(const __grid_constant__ Params prm, const __grid_constant__ CUtensorMap mX, const __grid_constant__ CUtensorMap mB, const __grid_constant__ CUtensorMap mCre,
             const __grid_constant__ CUtensorMap mCim, const __grid_constant__ CUtensorMap mWg, const __grid_constant__ CUtensorMap mWu,
             const __grid_constant__ CUtensorMap mWd, const __grid_constant__ CUtensorMap mXr, const __grid_constant__ CUtensorMap mPB,
             const __grid_constant__ CUtensorMap mPC, const __grid_constant__ CUtensorMap mXe) {
    {
        const uint32_t t = threadIdx.x, b = blockIdx.x;
        const uint32_t row = t < 32 ? ((b & 60) * 2 + (b >> 6) * 4 + (b & 3)) * 16 + (t >> 1) : b * 4 + ((t >> 1) & 3);
        const char* base = (const char*)(t < 32 ? prm.x : t < 40 ? prm.b_re : prm.b_im);
        asm volatile("{ .reg .pred p; setp.lt.u32 p, %1, 48; @p prefetch.global.L2 [%0]; }" ::"l"(base + (row * 2048 + (t & 1) * 128)), "r"(t) : "memory");
    }
    extern __shared__ __align__(1024) uint8_t smem[];
    uint32_t sb;
    asm volatile("mov.u32 %0, %1;" : "=r"(sb) : "r"(smem_u32(smem)));
    const int tid = threadIdx.x, warp = __shfl_sync(0xffffffffu, tid >> 5, 0), lane = tid & 31;
    const int cta = blockIdx.x;
    const uint32_t cstart = clk32();
    const int chunk = (cta >> 2) & 15;
    const int dt = (cta >> 6) * 4 + (cta & 3);
    const int rid = chunk * 8 + dt;
    const int kslot = (rid & 3) * 32 + (rid >> 2);
    const bool owner = cta < 112;
    const uint32_t full = sb + OFF_FULL, empty = sb + OFF_EMPTY;
    const uint32_t bar_epoch = full + 8 * 73, dfull = full + 8 * 74, bar_retry = full + 8 * 81, bar_x = full + 8 * 82, ffull = full + 8 * 84,
                   hfull = full + 8 * 89, bar_base = full + 8 * 102;
    const uint32_t fempty = empty + 8 * 66, bar_order = empty + 8 * 71, bar_stored = empty + 8 * 73, bar_dfree = empty + 8 * 74,
                   bar_out = empty + 8 * 77, bar_g = empty + 8 * 85, bar_const = empty + 8 * 86;
    const int w = warp & 3, g = lane >> 2, c = lane & 3, at = tid & 127;

    const uint32_t probe = (lane >> 3) * 32 + (g & 1) * 144 + (c & 1) * 520 + (c >> 1) * 1028;

    LSTAMP(tid == 0, 96);
    GSTAMP(tid == 0, 94);
    auto init_barriers = [&](uint32_t base, uint32_t cnt, auto n) {
        if (elect_one()) {
#pragma unroll
            for (int i = 0; i < n(); i++) mbar_init(base + 8 * i, cnt);
            fence_mbar_init();
        }
        __syncwarp();
    };
    if (warp != 12) {
        if (warp == 15 && !(cta & 3) && lane < 8) st_relaxed((uint32_t*)&prm.s->start[cta >> 1] + lane, (lane & 1) ? gtime32() : cstart);
        if (warp < 12) sleep_until(cstart + (warp < 4 ? TN(T_W0) : TN(T_INIT)));
    }
    if (warp < 8) {
        if (warp < 4) init_barriers(warp == 0 ? full + 40 : warp == 3 ? full + 8 * 98 : empty + 40 * (warp - 1), (warp + 1) & 2 ? 4 : 1, []() { return 5; });
        else init_barriers(full + 80 + 176 * w, 1, []() { return 22; });
        asm volatile("setmaxnreg.inc.sync.aligned.u32 192;");
        if (warp < 4) {
            named_bar(5, 160);
            asm volatile("bar.arrive 0, 448;" ::: "memory");
            asm volatile("bar.arrive 6, 160;" ::: "memory");
            asm volatile("bar.arrive 7, 160;" ::: "memory");
        } else named_bar(0, 448);
        const int wg = warp >> 2;
        const int p = wg * 512 + dt * 32 + w * 8 + g;
        uint32_t cp = sb + OFF_CONST + 8 * (wg * 64 + w * 8 + g), cw = cp + 1024 * c, cm = sb + OFF_M + 4 * (wg * 64 + w * 8 + g);
        const int j1 = chunk - 1 - c;
        uint2* cq = &prm.s->carry[j1 * 1024 + p];
        char* hd = reinterpret_cast<char*>(prm.s->h) + (size_t)chunk * 524288 + wg * 262144 + (dt >> 1) * 16384 + ((dt & 1) * 4 + w) * 1024 + g * 64 + ((c ^ (g >> 1)) << 4);
        const bool never = uni(cstart == 0 && sb == 0);
        asm volatile("" : "+l"(cq), "+l"(hd), "+r"(cp), "+r"(cw), "+r"(cm));
        float2 a[2], a32[2], a64[2], a512[2], pw32[2], pw128[2];
        uint32_t mm[2], t2, par;
        auto constants = [&](int h) {
            if (h) { t2 = lds32(sb + OFF_EPOCH + 4); par = lds32(sb + OFF_EPOCH); }
            auto ldc = [](uint32_t a) { const uint2 v = lds64(a); return make_float2(__uint_as_float(v.x), __uint_as_float(v.y)); };
            a[h] = ldc(cp + 256 * h); a32[h] = ldc(cp + 256 * h + 1024); a64[h] = ldc(cp + 256 * h + 2048); a512[h] = ldc(cp + 256 * h + 7168);
            pw32[h] = ldc(cw + 256 * h);
            pw128[h] = ldc(cw + 256 * h + 3072);
            mm[h] = lds32(cm + 128 * h);
        };
        if (wg == 1) {
            const int pc = w * 256 + dt * 32 + lane;
            const float lr = __bfloat162float(prm.lam_re[pc]), li = __bfloat162float(prm.lam_im[pc]), ld = __bfloat162float(prm.log_dt[pc]);
            const uint32_t dk = __ldg(reinterpret_cast<const uint32_t*>(prm.dskip + dt * 128) + (at & 63));
            reinterpret_cast<uint32_t*>(smem + OFF_DK)[at & 63] = dk;
            const float dtv = rbf(expf(ld));
            const float er = expf(dtv * lr);
            float sn, cs;
            sincosf(dtv * li, &sn, &cs);
            const float ar = er * cs, ai = er * sn;
            const float nr = ar - 1.0f, ni = ai;
            const bool big = fabsf(lr) >= fabsf(li);
            const float t = (big ? li : lr) / (big ? lr : li), dn = big ? lr + li * t : lr * t + li;
            const float cr = (big ? nr + ni * t : nr * t + ni) / dn, ci = (big ? ni - nr * t : ni * t - nr) / dn;
            float2* ct = reinterpret_cast<float2*>(smem + OFF_CONST) + at;
            float2 pw = make_float2(ar, prm.swapped ? -ai : ai);
            ct[0] = pw;
            const float mx = prm.swapped ? -2.f * ci : 2.f * cr, my = prm.swapped ? 2.f * cr : -2.f * ci;
            reinterpret_cast<uint32_t*>(smem + OFF_M)[at] = pack_bf(mx, my);
#pragma unroll
            for (int i = 0; i < 5; i++) pw = cmul(pw, pw);
#pragma unroll
            for (int i = 0; i < 2; i++) {
                const float2 p2 = cmul(pw, pw);
                ct[128 + 384 * i] = pw; ct[256 + 384 * i] = p2; ct[384 + 384 * i] = cmul(p2, pw);
                pw = cmul(p2, p2);
            }
            ct[896] = pw;
            mbar_wait(bar_epoch);
            mbar_wait(empty + 8 * TN(RS_E));
            st_relaxed2(&prm.s->hid[cta * 128 + at], ~0u, ~0u);
            st_relaxed4(&prm.s->y[((at >> 4) * 8 + (cta >> 4)) * D_ + (cta & 15) * 64 + (at & 15) * 4], 0u, 0u, 0u, 0u);
            st_relaxed2(&prm.s->carry[chunk * 1024 + pc], 0u, 0u);
            __syncwarp();
            if (lane == 0) mbar_arrive(bar_const);
            STAMPIF(at == 0, 3);
            mbar_wait(bar_const);
            constants(0);
            constants(1);
            mbar_wait(bar_order);
        }

        float accA[64], accB[64];
        run_entries<0>(sb, wg * 16, wg * 16 + 15, wg, accA, accB, [&](int i) {
            if (i == GE - 1) {
                mbar_wait(bar_base);
                const uint32_t t = lds32(sb + OFF_EPOCH + 8) + TN(GT0);
                const int late = clk32() - t - TN(GL);
                sched_fence(late < 0 ? t : t + TN(GL) + 256 + (late | TN(GQ)));
            }
        });
        mbar_wait(full + 8 * (wg * 16 + 15));
        KSTAMP(wg * 16 + 15);
        if (wg == 0) {
            mbar_wait(bar_const);
            run_entry<0>(make_desc(sb), empty + 8 * 14, 1, accA, accB, [&]() { constants(0); constants(1); });
            if (lane == 0) mbar_arrive(bar_order);
        } else run_entry<0>(make_desc(sb + SLOT), empty + 8 * 30, 1, accA, accB, [&]() { if (lane == 0) mbar_arrive(bar_order + 8); });
        uint2 v[4];
#pragma unroll
        for (int m = 0; m < 4; m++) v[m] = make_uint2(t2, t2);
        wgmma_wait<0>();
        pin64(accA); pin64(accB);
        if (lane == 0) mbar_arrive(empty + 8 * (wg * 16 + 15));
        LSTAMP(at == 0, 96 + 30 + 10 * wg); GSTAMP(LT && at == 0, 193 + wg);

        auto cut = [&]() { if (never) sched_fence(cstart); };
        auto poll = [&](int h) {
#pragma unroll
            for (int m = 0; m < 4; m++)
                asm volatile("{ .reg .pred p; setp.ge.s32 p, %3, %4; @p ld.relaxed.gpu.global.v2.b32 {%0, %1}, [%2]; }"
                             : "+r"(v[m].x), "+r"(v[m].y) : "l"(cq + 256 * h - 4096 * m), "r"(j1), "r"(4 * m) : "memory");
        };
        auto valid = [&]() {
            uint32_t bad = 0;
#pragma unroll
            for (int m = 0; m < 4; m++) bad |= (v[m].x ^ t2) | (v[m].y ^ t2);
            return __all_sync(0xffffffffu, (bad & 3u) == 0);
        };
        float2 w0[2];
        uint32_t tp;
#pragma unroll
        for (int h = 0; h < 2; h++) {
            float (&acc)[64] = h ? accB : accA;
            float2 e = make_float2(acc[0], acc[2]);
#pragma unroll
            for (int s = 1; s < 32; s++) {
                const int i0 = 4 * (s >> 1) + (s & 1);
                e = cfma(a[h], e, make_float2(acc[i0], acc[i0 + 2]));
            }
            float2 y = make_float2(__shfl_up_sync(0xffffffffu, e.x, 1, 4), __shfl_up_sync(0xffffffffu, e.y, 1, 4));
            if (c >= 1) e = cfma(a32[h], y, e);
            y = make_float2(__shfl_up_sync(0xffffffffu, e.x, 2, 4), __shfl_up_sync(0xffffffffu, e.y, 2, 4));
            if (c >= 2) e = cfma(a64[h], y, e);
            if (c == 3) st_relaxed2(cq + 4096 + 256 * h, (__float_as_uint(e.x) & ~3u) | t2, (__float_as_uint(e.y) & ~3u) | t2);
            if (h == 0) tp = clk32();
            cut();
            w0[h] = make_float2(__shfl_up_sync(0xffffffffu, e.x, 1, 4), __shfl_up_sync(0xffffffffu, e.y, 1, 4));
            STAMPIF(at == 0, 31 + h + 10 * wg);
        }
        uint32_t sx[2][16], sy[2][16], mr[2][4];
        const uint32_t gap = wg ? TN(GAP1) : TN(GAP0);
#pragma unroll
        for (int h = 0; h < 2; h++) {
            const uint32_t sg = prm.swapped ? 0x80008000u : 0u;
            mr[h][0] = __byte_perm(mm[h], 0, 0x1010); mr[h][1] = __byte_perm(mm[h], 0, 0x3232);
            mr[h][2] = mr[h][1] ^ sg; mr[h][3] = mr[h][0] ^ sg ^ 0x80008000u;
        }
        auto put = [&](int e, int j) {
            uint32_t d[4];
#pragma unroll
            for (int u = 0; u < 4; u++) d[u] = fma_bf2(mr[e >> 1][2 * (e & 1)], sx[e >> 1][4 * j + u], mul_bf2(mr[e >> 1][2 * (e & 1) + 1], sy[e >> 1][4 * j + u]));
#pragma unroll
            for (int u = 0; u < 2; u++)
                asm("lop3.b32 %0, %0, %1, %2, 0xD8;" : "+r"(d[2 * (j & 1) + u]) : "r"(par), "r"((uint32_t)((w & 1) == u)));
            stg128(hd + e * 65536 + (j >> 1) * 8192 + (j & 1) * 512, d[0], d[1], d[2], d[3]);
            if (j == 3 && lane == 0) mbar_arrive(bar_out + 32 * wg + 8 * e);
        };
#pragma unroll
        for (int h = 0; h < 2; h++) {
            float (&acc)[64] = h ? accB : accA;
            uint32_t it = 0;
            if (h == 0) {
                sleep_until(tp + (wg ? TN(T_CP1) : TN(T_CP0)));
                poll(h);
            }
            while (!valid()) {
                if (++it > SPIN_LIMIT) __trap();
#pragma unroll
                for (int m = 0; m < 4; m++)
                    asm volatile("{ .reg .pred p; setp.ne.u32 p, %3, 0; @p ld.relaxed.gpu.global.v2.b32 {%0, %1}, [%2]; }"
                                 : "+r"(v[m].x), "+r"(v[m].y) : "l"(cq + 256 * h - 4096 * m), "r"(((v[m].x ^ t2) | (v[m].y ^ t2)) & 3u) : "memory");
            }
            float2 hin = make_float2(__uint_as_float(v[3].x), __uint_as_float(v[3].y));
#pragma unroll
            for (int m = 2; m >= 0; m--) hin = cfma(a512[h], hin, make_float2(__uint_as_float(v[m].x), __uint_as_float(v[m].y)));
            STAMPIF(at == 0 && it > 0 && h == 0, 39 + 10 * wg);
            if (c) hin = cmul(pw128[h], hin);
            hin.x += __shfl_xor_sync(0xffffffffu, hin.x, 1); hin.y += __shfl_xor_sync(0xffffffffu, hin.y, 1);
            hin.x += __shfl_xor_sync(0xffffffffu, hin.x, 2); hin.y += __shfl_xor_sync(0xffffffffu, hin.y, 2);
            float2 st = hin;
            if (c) st = cfma(pw32[h], hin, w0[h]);
            STAMPIF(at == 0, 33 + 3 * h + 10 * wg);
#pragma unroll
            for (int j = 0; j < 4; j++) {
#pragma unroll
                for (int u = 0; u < 4; u++) {
                    const int i0 = 16 * j + 4 * u;
                    const float2 y = cfma(a[h], st, make_float2(acc[i0], acc[i0 + 2]));
                    st = cfma(a[h], y, make_float2(acc[i0 + 1], acc[i0 + 3]));
                    sx[h][4 * j + u] = pack_bf(y.x, st.x); sy[h][4 * j + u] = pack_bf(y.y, st.y);
                }
                if (h) sleep_until(tp += gap);
                if (h == 0 && j == 1) poll(1);
                put(2 * h, j);
                cut();
            }
            STAMPIF(at == 0, 34 + 3 * h + 10 * wg);
            tp = clk32();
#pragma unroll
            for (int j = 0; j < 4; j++) {
                sleep_until(tp += gap);
                put(2 * h + 1, j);
            }
        }
        STAMPIF(at == 0, 38 + 10 * wg);

        if (wg == 1) {
            const char* src = reinterpret_cast<const char*>(prm.s->h) + (size_t)chunk * 524288;
            uint32_t rpar = 1;
#pragma unroll 1
            for (int n = w; n < 2 * NSPL; n += 4) {
                mbar_wait(empty + 8 * (NBIG - 7 + n));
                mbar_wait(hfull + 8 * (NST + n % 7), n / 7 & 1);
                const uint32_t dst = sb + tail_h(n);
                rpar = check_tile<8>(sb, dst, probe, src + tail_src(n), par, full + 8 * w, rpar, TN(T_RETRY));
                if (lane == 0) mbar_expect_tx(full + 8 * (NBIG + n), n < NSPL ? 2 * TILE : 0);
            }
        } else {
            asm volatile("setmaxnreg.inc.sync.aligned.u32 216;");
            const int tl = 64 * (w & 1) + 8 * (w >> 1) + g;
            float gf[4];
            float* op = prm.out + (size_t)(chunk * 128 + tl) * D_ + dt * 128 + 4 * c;
            const int xr = 2 * (g & 3) + (g >> 2);
            uint32_t xs = sb + (32 * (w & 1) + 8 * (w >> 1) + xr) * 128 + (((c >> 1) ^ xr) << 4) + (c & 1) * 8;
            uint32_t gs = sb + OFF_G + 2 * tl;
            asm volatile("" : "+r"(gs), "+l"(op), "+r"(xs));
            float outA[64], outB[64];
            STAMPIF(at == 0, 9);
            mbar_wait(bar_order + 8);
            STAMPIF(at == 0, 35);
            run_entries<1>(sb, 32, NBIG, 32 % NST, outA, outB, [](int) {});
            uint32_t gp[4], om[4];
            uint2 xt[4][8], dk[8];
            auto load_x = [&](int q, int j) {
#pragma unroll
                for (int r = 0; r < 2; r++) xt[2 * q + r][j] = lds64((xs ^ ((j & 3) << 5)) + (q ? tail_c(0) : OFF_FT) + (j >> 2) * TILE + r * 2048);
                if (q == 0) dk[j] = lds64(sb + OFF_DK + c * 8 + 32 * j);
            };
            auto term = [&](int q, int j) {
#pragma unroll
                for (int r = 2 * q; r < 2 * q + 2; r++) {
                    xt[r][j].x = mul_bf2(xt[r][j].x, fma_bf2(gp[r], dk[j].x, om[r]));
                    xt[r][j].y = mul_bf2(xt[r][j].y, fma_bf2(gp[r], dk[j].y, om[r]));
                }
            };
            auto store = [&](int q, int u0, int u1) {
                const float (&acc)[64] = q ? outB : outA;
#pragma unroll
                for (int u = u0; u < u1; u++) {
                    const int j = u >> 1, r = u & 1;
                    const int o = 8 * j + 2 * r;
                    const float gv = fabsf(gf[2 * q + r]);
                    const uint2 t = xt[2 * q + r][j];
                    stg128(op + (r * 32 + q * 16) * D_ + 16 * j, __float_as_uint(fmaf(gv, acc[o], bf_lo(t.x))), __float_as_uint(fmaf(gv, acc[o + 1], bf_hi(t.x))),
                           __float_as_uint(fmaf(gv, acc[o + 4], bf_lo(t.y))), __float_as_uint(fmaf(gv, acc[o + 5], bf_hi(t.y))));
                }
            };
            uint64_t dh = desc64<1>(make_desc_h(sb)), dc = desc64<0>(make_desc(sb));
#pragma unroll
            for (int n = 0; n < 2 * NSPL; n++) {
                const int j = n % NSPL;
                if (n == 0) mbar_wait(bar_g);
                if (n == X0 || n == 2 * NSPL - 1) mbar_wait(bar_x + (n == X0 ? 0 : 8));
                mbar_wait(full + 8 * (NBIG + n));
                KSTAMP(NBIG + n);
                asm volatile("mov.b64 %0, %0; mov.b64 %1, %1;" : "+l"(dh), "+l"(dc));
                const uint64_t da = dh + (tail_h(n) >> 4), db = dc + (tail_c(j) >> 4);
                const int xj = n - X0;
                wgmma_fence();
#pragma unroll
                for (int kk = 0; kk < 4; kk++) {
                    wgmma_n128<1>(n < NSPL ? outA : outB, da + kk * 128, db + kk * 2);
                    if (kk == 0 && n == 0) {
#pragma unroll
                        for (int r = 0; r < 4; r++) {
                            uint32_t u;
                            asm volatile("ld.shared.u16 %0, [%1];" : "=r"(u) : "r"(gs + (r & 1) * 64 + (r >> 1) * 32) : "memory");
                            gf[r] = bf_lo(u);
                        }
                    }
                    if (kk == 0 && xj >= 0 && xj < 8) load_x(0, xj);
                    if (kk == 0 && n == 2 * NSPL - 1) load_x(1, 0);
                }
                wgmma_commit();
                if (n <= 2 * NSPL - 7) {
                    wgmma_wait<1>();
                    if (lane == 0) mbar_arrive(empty + 8 * (NBIG + n - 1));
                    if (!j) { LSTAMP(at == 0, 96 + 12 + n / NSPL); GSTAMP(LT && at == 0, 195 + n / NSPL); }
                } else cut();
                if (n == 0) {
#pragma unroll
                    for (int r = 0; r < 4; r++) {
                        const bool routed = (int)__float_as_uint(gf[r]) < 0;
                        gp[r] = routed ? 0u : pack_bf(gf[r], gf[r]); om[r] = routed ? 0u : pack_bf(1.0f - gf[r], 1.0f - gf[r]);
                    }
                }
                if (xj >= 0 && xj < 8) term(0, xj);
                if (n == NSPL) pin64(outA);
                if (n >= NSPL) store(0, (j * 16 + 4) / NSPL, j == NSPL - 1 ? 16 : ((j + 1) * 16 + 4) / NSPL);
            }
            term(1, 0);
            cut();
            wgmma_wait<0>();
            pin64(outB);
            LSTAMP(at == 0, 96 + 51); GSTAMP(LT && at == 0, 197);
#pragma unroll
            for (int j = 1; j < 8; j++) load_x(1, j);
            store(1, 0, 2);
#pragma unroll
            for (int j = 1; j < 8; j++) {
                cut();
                term(1, j);
                store(1, 2 * j, 2 * j + 2);
            }
            __syncwarp();
            if (lane == 0) mbar_arrive(bar_stored);
            LSTAMP(at == 0, 96 + 52);
        }
    } else if (warp < 12) {
        asm volatile("setmaxnreg.dec.sync.aligned.u32 64;");
        init_barriers(empty + min(80 + 160 * w, 8 * 67), 4, []() { return 20; });
#pragma unroll
        for (int i = 0; i < 2; i++) sts128(sb + OFF_LIST + i * 2048 + at * 16, 0u, 0u, 0u, 0u);
        uint32_t* keys = reinterpret_cast<uint32_t*>(smem + OFF_KEYS);
        keys[4] = 0;
        named_bar(0, 448);
        if (at < 24) st_relaxed(at < 8 ? &prm.s->key[kslot * 8 + at] : &prm.s->gate[rid * 16 + at - 8], 0u);
        mbar_wait(bar_epoch);
        const uint32_t t2 = lds32(sb + OFF_EPOCH + 4);
        STAMPIF(at == 0, 20);
        float facc[4];
        const uint32_t dft = make_desc(sb + OFF_FT), dxs = make_desc(sb + OFF_XS);
#pragma unroll 1
        for (int u = 0; u < 4; u++) {
            mbar_wait(ffull + 8 * u);
            STAMPIF(at == 0, 4 + u);
            wgmma_fence();
            small_tile<0>(facc, dft + u * (TILE >> 4), dxs + u * 64, u == 0);
            wgmma_commit();
        }
        wgmma_wait<0>();
        pin4(facc);
        if (lane < 4) mbar_arrive(fempty + 8 * lane);
        auto gate_up = [&](auto rest) {
            uint32_t slot = 4, par = 0, prev = full + 8 * 101, e4 = 4 * TN(GC0);
#pragma unroll 1
            for (int j = 0; j < 14; j++) {
                if (j == 2) rest();
                STAMPW(at == 0, 75 + j);
                mbar_wait(ffull + 8 * slot, par);
                STAMPW(at == 0, 160 + j);
                mbar_wait(empty + 8 * (e4 >> 2));
                e4 += j < 8 ? TN(GCS) : TN(GCS4);
                wgmma_fence();
                small_tile<1>(facc, dft + slot * (TILE >> 4), dxs + j * 64, j == 0);
                wgmma_commit();
                wgmma_wait<1>();
                if (lane == 0) mbar_arrive(prev);
                prev = fempty + 8 * slot;
                if (++slot == NFT) { slot = 0; par ^= 1; }
            }
            wgmma_wait<0>();
            if (lane == 0) mbar_arrive(prev);
            pin4(facc);
        };
        auto help = [&]() {
            uint32_t slot = 4, par = 0, e4 = 4 * TN(GC0);
#pragma unroll 1
            for (int u = 0; u < 7; u++) {
                const uint32_t slot2 = slot == NFT - 1 ? 0 : slot + 1;
                mbar_wait(ffull + 8 * slot, par);
                par ^= slot2 == 0;
                mbar_wait(ffull + 8 * slot2, par);
                mbar_wait(empty + 8 * (e4 >> 2));
                e4 += TN(GCH);
                wgmma_fence();
                small_tile<1>(facc, dft + slot * (TILE >> 4), dxs, true);
                small_tile<1>(facc, dft + slot2 * (TILE >> 4), dxs + 64, false);
                wgmma_commit();
                wgmma_wait<0>();
                pin4(facc);
                if (lane < 2) mbar_arrive(fempty + 8 * (lane ? slot2 : slot));
                st_relaxed4(&prm.s->part[((cta - 112) * 7 + u) * 128 + at], (__float_as_uint(facc[0]) & ~3u) | t2, __float_as_uint(facc[1]),
                            __float_as_uint(facc[2]), __float_as_uint(facc[3]));
                slot = slot2 == NFT - 1 ? 0 : slot2 + 1;
                par ^= slot == 0;
            }
        };
        auto down = [&]() {
            const uint32_t dhid = make_desc(sb + OFF_HID);
#pragma unroll 1
            for (int j = 0; j < 7; j++) {
                mbar_wait(dfull + 8 * j);
                wgmma_fence();
                small_tile<1>(facc, dft + j * (TILE >> 4), dhid + j * 64, j == 0);
                wgmma_commit();
                if ((0x52 >> j) & 1) {
                    wgmma_wait<0>();
                    if (lane == 0) mbar_arrive(bar_dfree + 8 * (j / 3));
                }
            }
            wgmma_wait<0>();
            pin4(facc);
        };
        if ((c & 1) == (w >> 1)) {
            float* red = reinterpret_cast<float*>(smem + OFF_RED) + w * 32 + (c >> 1) * 16 + g;
            red[0] = (w & 1) ? facc[1] : facc[0];
            red[8] = (w & 1) ? facc[3] : facc[2];
        }
        named_bar(2, 128);
        STAMPIF(at == 0, 21);
        const uint32_t tpub = clk32();
        if (w < 2) {
            const float* red = reinterpret_cast<const float*>(smem + OFF_RED) + w * 16 + (lane & 15);
            const float v = rbf((red[0] + red[32]) + (red[64] + red[96]));
            if (w == 0) {
                uint32_t k = __float_as_uint(v);
                k = ((k ^ ((uint32_t)((int)k >> 31) | 0x80000000u)) & 0xFFFF0000u) | (t2 << 11) | (2047u - (uint32_t)(rid * 16 + (lane & 15)));
                int rank = 0;
#pragma unroll
                for (int i = 0; i < 8; i++) rank += __shfl_sync(0xffffffffu, k, (lane >> 4) * 8 + i) > k;
                rank += __shfl_xor_sync(0xffffffffu, rank, 16);
                if (rank < 8) st_relaxed(&prm.s->key[kslot * 8 + rank], k);
            } else if (lane < 16) st_relaxed(&prm.s->gate[rid * 16 + lane], __float_as_uint(rbf(sigmoidf_(v))) | t2);
            __syncwarp();
        }
        uint32_t it = 0;
        uint4 ka, kb4;
        mbar_wait(bar_base);
        sleep_until(lds32(sb + OFF_EPOCH + 8) + TN(GT1));
        sleep_until(tpub + TN(G0));
        bool bad = true;
        while (true) {
            if (bad) {
                ka = ld_relaxed4(&prm.s->key[at * 8]);
                kb4 = ld_relaxed4(&prm.s->key[at * 8 + 4]);
            }
            bad = (((ka.x ^ (t2 << 11)) | (kb4.x ^ (t2 << 11))) & 0x1800u) != 0;
            if (!__any_sync(0xffffffffu, bad)) break;
            if (++it > SPIN_LIMIT) __trap();
            __nanosleep(TN(T_RETRY));
        }
        STAMPIF(at == 0, 22);
        STAMPIF(at == 0 && it > 0, 23);
        const uint32_t m1 = __reduce_max_sync(0xffffffffu, ka.x), m2 = __reduce_max_sync(0xffffffffu, ka.x == m1 ? ka.y : ka.x);
        if (lane == 0) keys[w] = m2;
        named_bar(2, 128);
        const uint4 th4 = *reinterpret_cast<const uint4*>(keys);
        const uint32_t th = min(min(th4.x, th4.y), min(th4.z, th4.w));
        {
            const uint32_t k8[8] = {ka.x, ka.y, ka.z, ka.w, kb4.x, kb4.y, kb4.z, kb4.w};
            auto append = [&](int lo, int hi) {
                uint32_t n = 0, pos = 0;
#pragma unroll
                for (int i = lo; i < hi; i++) n += k8[i] >= th;
                asm volatile("{ .reg .pred p; setp.ne.u32 p, %2, 0; @p atom.shared.add.u32 %0, [%1], %2; }" : "+r"(pos) : "r"(sb + OFF_KEYS + 16), "r"(n) : "memory");
#pragma unroll
                for (int i = lo; i < hi; i++)
                    if (k8[i] >= th) reinterpret_cast<uint32_t*>(smem + OFF_LIST)[pos + i - lo] = k8[i];
            };
            append(0, 2);
            if (__any_sync(0xffffffffu, k8[2] >= th)) append(2, 8);
        }
        named_bar(2, 128);
        {
            const uint32_t* list = reinterpret_cast<const uint32_t*>(smem + OFF_LIST);
            const int n = (int)keys[4];
#pragma unroll 1
            for (int i0 = w * 32; i0 < n; i0 += 128) {
                const uint32_t k = list[i0 + lane];
                int rank = 0;
#pragma unroll 2
                for (int o = 0; o < n; o += 4) {
                    const uint4 l4 = *reinterpret_cast<const uint4*>(list + o);
                    rank += (l4.x > k) + (l4.y > k) + (l4.z > k) + (l4.w > k);
                }
                if (rank < 8) reinterpret_cast<uint32_t*>(smem + OFF_SEL)[rank] = k;
            }
        }
        named_bar(2, 128);
        STAMPIF(at == 0, 24);
        const uint32_t* sel = reinterpret_cast<const uint32_t*>(smem + OFF_SEL);
        auto gates = [&]() {
            uint32_t gv;
            it = 0;
            while (true) {
                gv = ld_relaxed(&prm.s->gate[chunk * 128 + at]);
                const uint32_t ar = ld_relaxed(&prm.s->armed[((cta >> 4) * 14 + min(lane, 13)) * 4]);
                if (__all_sync(0xffffffffu, (gv & 3u) == t2 && ar == t2)) break;
                if (++it > SPIN_LIMIT) __trap();
            }
            asm volatile("fence.acquire.gpu;" ::: "memory");
#pragma unroll
            for (int s = 0; s < 8; s++)
                if ((~sel[s] & 2047u) == (uint32_t)(chunk * 128 + at)) gv |= 0x80000000u;
            reinterpret_cast<uint16_t*>(smem + OFF_G)[at] = (uint16_t)(gv >> 16);
            __syncwarp();
            if (lane == 0) mbar_arrive(bar_g);
        };
        {
            const int tk = (at >> 3) & 7;
            const char* xt = (const char*)prm.x + (~sel[tk] & 2047u) * 2048 + (owner ? 256 : 0) + (at >> 6) * 128 + (at & 7) * 16;
#pragma unroll
            for (int i = 0; i < 7; i++) {
                if (i == 0 || owner) cp_async16(sb + OFF_XS + (2 * i + (at >> 6)) * 1024 + tk * 128 + (((at & 7) ^ tk) << 4), xt + i * 256);
                if (i == 0 || i == 6) asm volatile("cp.async.commit_group;" ::: "memory");
            }
            asm volatile("cp.async.wait_group 1;" ::: "memory");
            fence_async_smem();
            named_bar(2, 128);
            STAMPIF(at == 0, 25);
        }
        if (!owner) help();
        else {
            gate_up([&]() {
                asm volatile("cp.async.wait_all;" ::: "memory");
                fence_async_smem();
                named_bar(2, 128);
            });
            it = 0;
            while (true) {
                const uint4 v = ld_relaxed4(&prm.s->part[cta * 128 + at]);
                if (__all_sync(0xffffffffu, (v.x & 3u) == t2)) {
                    facc[0] += __uint_as_float(v.x); facc[1] += __uint_as_float(v.y); facc[2] += __uint_as_float(v.z); facc[3] += __uint_as_float(v.w);
                    break;
                }
                if (++it > SPIN_LIMIT) __trap();
                __nanosleep(TN(T_RETRY));
            }
            if (!(cta & 1)) {
#pragma unroll
                for (int u = 0; u < 4; u++) {
                    const float v = rbf(facc[u]);
                    facc[u] = __fdividef(v, 1.0f + __expf(-v));
                }
            }
            st_relaxed2(&prm.s->hid[cta * 128 + at], pack_bf(facc[0], facc[1]), pack_bf(facc[2], facc[3]));
        }
        STAMPIF(at == 0, 26);
        gates();
        uint32_t mine = __ballot_sync(0xffffffffu, lane < 8 && (int)((~sel[lane & 7] & 2047u) >> 7) == chunk), tr;
        uint2 xr, xd;
        float gr, rs;
        auto skip = [&](int n) {
#pragma unroll 1
            for (int i = 0; i < n; i++) mine &= mine - 1;
            if (mine) {
                const uint32_t key = sel[__ffs(mine) - 1], kb = key >> 16;
                tr = ~key & 2047u;
                xr = __ldg(reinterpret_cast<const uint2*>(prm.x + (size_t)tr * D_ + dt * 128) + lane);
                rs = rbf(sigmoidf_(bf_lo((kb & 0x8000u) ? (kb & 0x7FFFu) : (~kb & 0xFFFFu))));
                gr = fabsf(__bfloat162float(reinterpret_cast<const __nv_bfloat16*>(smem + OFF_G)[tr & 127]));
                xd = lds64(sb + OFF_DK + 8 * lane);
            }
        };
        mbar_wait(bar_g);
        skip(w);
        {
            mbar_wait(empty + 8 * max(TN(HG), 31));
            const uint2* hp = &prm.s->hid[(cta >> 4) * 14 * 128 + at];
            uint32_t hv[16];
            it = 0;
            while (true) {
                uint32_t top = 0;
#pragma unroll
                for (int j = 0; j < 7; j++) {
                    const uint2 hg = ld_relaxed2(hp + 256 * j), hu = ld_relaxed2(hp + 256 * j + 128);
                    top = max(top, max(hg.x, hu.x));
                    hv[2 * j] = mul_bf2(hg.x, hu.x); hv[2 * j + 1] = mul_bf2(hg.y, hu.y);
                }
                if (__all_sync(0xffffffffu, top != ~0u)) break;
                do {
                    if (++it > SPIN_LIMIT) __trap();
                } while (!__all_sync(0xffffffffu, ld_relaxed(hp + min(lane, 13) * 128 - lane) != ~0u));
            }
            STAMPIF(at == 0 && it > 0, 61);
            hv[14] = hv[15] = 0;
#pragma unroll
            for (int j = 0; j < 4; j++)
                asm volatile("stmatrix.sync.aligned.m8n8.x4.trans.shared.b16 [%0], {%1, %2, %3, %4};" ::"r"(
                                 sb + OFF_HID + (2 * j + (lane >> 4)) * 1024 + (lane & 7) * 128 + (((2 * w + ((lane >> 3) & 1)) ^ (lane & 7)) << 4)),
                             "r"(hv[4 * j]), "r"(hv[4 * j + 1]), "r"(hv[4 * j + 2]), "r"(hv[4 * j + 3]) : "memory");
        }
        fence_async_smem();
        named_bar(2, 128);
        STAMPIF(at == 0, 27);
        down();
#pragma unroll
        for (int u = 0; u < 4; u++)
            st_relaxed(&prm.s->y[((2 * c + (u & 1)) * 8 + (cta >> 4)) * D_ + (cta & 15) * 64 + w * 16 + g + 8 * (u >> 1)], (__float_as_uint(facc[u]) & ~3u) | t2);
        STAMPIF(at == 0, 28);
        sleep_until(clk32() + TN(T_Y));
        while (mine) {
            const uint32_t* yp = &prm.s->y[(__ffs(mine) - 1) * 8 * D_ + dt * 128 + 4 * lane];
            float y[4];
            it = 0;
            while (true) {
                uint32_t bad = 0;
                y[0] = y[1] = y[2] = y[3] = 0.f;
#pragma unroll
                for (int ks = 0; ks < 8; ks++) {
                    const uint4 v = ld_relaxed4(yp + ks * D_);
                    bad |= v.x ^ t2;
                    y[0] += __uint_as_float(v.x); y[1] += __uint_as_float(v.y); y[2] += __uint_as_float(v.z); y[3] += __uint_as_float(v.w);
                }
                if (__all_sync(0xffffffffu, (bad & 3u) == 0)) break;
                if (++it > SPIN_LIMIT) __trap();
            }
            STAMPIF(lane == 0 && it, 62);
#pragma unroll
            for (int u = 0; u < 4; u++) {
                const uint32_t x2 = (u & 2) ? xr.y : xr.x, d2 = mul_bf2(x2, (u & 2) ? xd.y : xd.x);
                y[u] = fmaf(gr, (u & 1) ? bf_hi(d2) : bf_lo(d2), rbf(rbf(1.0f - gr) * rbf(((u & 1) ? bf_hi(x2) : bf_lo(x2)) + rbf(rbf(y[u]) * rs))));
            }
            STAMPIF(lane == 0, 50);
            mbar_wait(bar_stored);
            asm volatile("red.global.add.v4.f32 [%0], {%1, %2, %3, %4};" ::"l"(prm.out + (size_t)tr * D_ + dt * 128 + 4 * lane), "f"(y[0]), "f"(y[1]), "f"(y[2]), "f"(y[3]) : "memory");
            skip(4);
        }
        LSTAMP(lane == 0, 96 + 29);
    } else {
        asm volatile("setmaxnreg.dec.sync.aligned.u32 40;");
        if (warp != 12) sleep_until(cstart + (warp == 13 ? TN(T_SMALL) : warp == 14 ? TN(PF0) - 250 : TN(T_W3)));
        auto behind = [&](int e) { mbar_wait(empty + 8 * e); };
        if (warp == 15) {
            prefetch_map(&mXr);
            named_bar(0, 448);
            asm volatile("bar.arrive 1, 64;" ::: "memory");
#pragma unroll 1
            for (int u = 0; u < 4; u++) {
                if (lane == 0) mbar_expect_tx(ffull + 8 * u, TILE);
                sleep_until(cstart + (u == 0 ? TN(RT0) : u == 1 ? TN(RT1) : u == 2 ? TN(RT2) : TN(RT3)));
                if (elect_one()) tma3(sb + OFF_FT + u * TILE, &mXr, u * 256, rid * 16, ffull + 8 * u);
                STAMP(53 + u);
            }
            if (sb & 1023) __trap();
            prefetch_map(&mWg);
            prefetch_map(&mWu);
            prefetch_map(&mWd);
            uint32_t slot = 4, par = 1;
#pragma unroll 1
            for (int j = 0; j < (DBG != 1 ? 14 : 0); j++) {
                const int o = owner ? cta : (cta - 112) * 7 + (j >> 1);
                mbar_wait(fempty + 8 * slot, par);
                if (lane == 0) mbar_expect_tx(ffull + 8 * slot, TILE);
                if (j < NFT) behind(TN(GU_E0) + j * TN(W_NUM) / 4);
                STAMPW(1, 176 + j);
                if (elect_one()) tma2(sb + OFF_FT + slot * TILE, (o & 1) ? &mWu : &mWg, (o >> 1) * 64, (owner ? j + 2 : j & 1) * 64, ffull + 8 * slot);
                if (++slot == NFT) { slot = 0; par ^= 1; }
            }
            if (lane < 9) mbar_expect_tx(lane < 7 ? dfull + 8 * lane : bar_x + 8 * (lane - 7), lane < 7 ? TILE : 2 * TILE);
#pragma unroll 1
            for (int j = 0; j < (DBG != 1 ? 7 : 0); j++) {
                if (j < 3) mbar_wait(fempty + 8 * j, 1);
                behind(min(TN(DL0) + j * TN(DLS) / 4, NBIG - 2));
                if (elect_one()) tma2(sb + OFF_FT + j * TILE, &mWd, (cta & 15) * 64, (cta >> 4) * 448 + j * 64, dfull + 8 * j);
            }
            prefetch_map(&mXe);
#pragma unroll 1
            for (int u = 0; u < 4; u++) {
                if (u == 2) {
                    mbar_wait(bar_dfree + 16);
                    if (elect_one()) tma5(sb + tail_c(8), &mCim, c_col(63), dt * 8, full + 8 * (NBIG + 8));
                }
                mbar_wait(bar_dfree);
                behind(u < 2 ? TN(DN_E0) + u : NBIG + NSPL);
                if (elect_one())
                    asm volatile("cp.async.bulk.tensor.5d.shared::cluster.global.mbarrier::complete_tx::bytes [%0], [%1, {%3, %6, %6, %4, %5}], [%2];"
                                 ::"r"(sb + (u < 2 ? OFF_FT : tail_c(0)) + (u & 1) * TILE), "l"(&mXe), "r"(bar_x + 4 * (u & 2)), "r"(dt * 128 + (u & 1) * 64),
                                 "r"(u & 2), "r"(chunk * 4), "r"(0) : "memory");
                if (u < 2) {
                    if (elect_one())
                        asm volatile("cp.async.bulk.prefetch.tensor.5d.L2.global [%0, {%1, %4, %4, %2, %3}];" ::"l"(&mXe), "r"(dt * 128 + u * 64), "r"(2), "r"(chunk * 4), "r"(0) : "memory");
                }
            }
        } else if (warp == 13) {
#pragma unroll
            for (int u = 0; u < 8; u++) {
                const int row = (u >> 2) * 4 + (lane >> 3);
                cp_async16(sb + OFF_XS + (u & 3) * 1024 + row * 128 + (((lane & 7) ^ row) << 4), (const char*)(u < 4 ? prm.w_r : prm.gate_w) + (u & 3) * 512 + lane * 16);
            }
            STAMP(57);
            const uint32_t tag = ld_relaxed(&prm.s->epoch[cta]) + 1;
            named_bar(1, 64);
            *reinterpret_cast<uint2*>(smem + OFF_EPOCH) = make_uint2(tag, tag % 3u + 1u);
            STAMPIF(tag, 58);
            asm volatile("cp.async.wait_all;" ::: "memory");
            STAMP(59);
            fence_async_smem();
            __syncwarp();
            if (lane == 0) {
                mbar_arrive(bar_epoch);
                prm.s->epoch[cta] = tag;
            }
            sleep_until(cstart + TN(T_BASE));
            {
                const uint2 st = ld_relaxed2(&prm.s->start[2 * lane]);
                const uint32_t d = st.x - cstart + 512u, age = gtime32() - st.y;
                const uint32_t m = __reduce_max_sync(0xffffffffu, d < 1024u && age < 4096u ? (d << 12) | age : 0u);
                const uint32_t late = (m & 4095u) - __reduce_min_sync(0xffffffffu, age);
                *reinterpret_cast<volatile uint32_t*>(smem + OFF_EPOCH + 8) = cstart + (m ? (m >> 12) - 512u + min(late, 256u) * TN(G_NS) / 4 : 0u);
                __syncwarp();
                if (lane == 0) mbar_arrive(bar_base);
                STAMP(60);
            }
            mbar_wait(bar_const);
            asm volatile("fence.acq_rel.gpu;" ::: "memory");
            if (lane < 4) st_relaxed2(&prm.s->armed[cta * 4 + lane], tag % 3u + 1u, 0u);
            prefetch_map(&mCre);
            prefetch_map(&mCim);
            const char* src = reinterpret_cast<const char*>(prm.s->h) + (size_t)chunk * 524288;
            uint32_t slot = 32 % NST, hpar = 0, rpar = 0;
#pragma unroll 1
            for (int i = 32; i < NBIG; i++) {
                mbar_wait(hfull + 8 * slot, hpar);
                STAMPIF(i == 32 || i == 33, 14 + (i & 1));
                rpar = check_tile<16>(sb, sb + slot * SLOT, probe, src, tag, bar_retry, rpar, TN(T_RETRY));
                if (lane == 0) mbar_expect_tx(full + 8 * i, 2 * TILE);
                STAMPIF(i == 32 || i == 33, 16 + (i & 1));
                src += 2 * TILE;
                slot = slot == NST - 1 ? 0 : slot + 1;
                hpar ^= slot == 32 % NST;
            }
        } else if (warp == 14) {
            prefetch_map(&mPB);
            auto pf_c = [&](int k) { prefetch_slice(&mPC, 4 * (k >> 1), cta * 8 + (k & 1) * 4); };
            {
                const char* px = (const char*)prm.x + (rid * 16 + (lane >> 1)) * 2048 + (lane & 1) * 128;
                const char* pb = (const char*)((lane & 8) ? prm.b_im : prm.b_re) + (cta * 4 + ((lane >> 1) & 3)) * 2048 + (lane & 1) * 128;
#pragma unroll 1
                for (int k = 1; k < 8; k++) {
                    sleep_until(cstart + TN(PF0) + (k - 1) * TN(PF1));
                    prefetch_l2(px + k * 256);
                    if (lane < 16) prefetch_l2(pb + k * 256);
                }
            }
            named_bar(7, 160);
            mbar_wait(bar_base);
#pragma unroll 1
            for (int k = 0; k < 4; k++) {
                behind(TN(PB_E0) + TN(PB_STEP) * k);
                if (elect_one()) prefetch_slice(&mPB, 4 * k, 512 + cta * 4);
            }
#pragma unroll 1
            for (int k = 0; k < TN(PC_N); k++) {
                behind(min(TN(PC_E0) + TN(PC_STEP) * k / 2, 25));
                if (elect_one()) pf_c(k);
            }
            int pk = TN(PC_N), pe = TN(PC_E1);
            auto own_part = [&](int e) {
                if (!(TDBG & 16) && !mbar_test(bar_out + 8 * e, 0)) {
                    mbar_wait(bar_out + 8 * e);
                    sleep_until(clk32() + TN(T_OWN));
                    STAMP(11);
                }
            };
            const char* src = reinterpret_cast<const char*>(prm.s->h) + (size_t)chunk * 524288;
            uint32_t slot = 32 % NST;
#pragma unroll 1
            for (int i = 32; i < NBIG; i++) {
                if (!(i & 3)) own_part((i - 32) >> 2);
                mbar_wait(empty + 8 * (i - NST));
                PSTAMP(i);
                if (elect_one()) {
                    mbar_expect_tx(hfull + 8 * slot, 2 * TILE);
                    bulk_load(sb + slot * SLOT, src, 2 * TILE, hfull + 8 * slot);
                    tma5(sb + slot * SLOT + 2 * TILE, (i & 4) ? &mCim : &mCre, c_col(i), dt * 8, full + 8 * i);
                }
                if (i == pe && pk < 8) {
                    if (elect_one()) pf_c(pk);
                    pk++; pe += TN(PC_S1);
                }
                src += 2 * TILE;
                slot = slot == NST - 1 ? 0 : slot + 1;
            }
            src -= (NBIG - 32) * 2 * TILE;
#pragma unroll
            for (int k = 0; k < 2 * NSPL - 2; k++) {
                if (k == 0 || k == 2) own_part(6 + k / 2);
                mbar_wait(empty + 8 * (NBIG - NST + k));
                if (k >= 1 && k <= 4) {
                    if (elect_one()) {
#pragma unroll
                        for (int j = 2 * k - 2; j < 2 * k; j++)
                            tma5(sb + tail_c(j), ((NBIG + j) & 4) ? &mCim : &mCre, c_col(NBIG + j), dt * 8, full + 8 * (NBIG + j));
                    }
                }
                if (k == 4) continue;
                if (k == 2) mbar_wait(bar_dfree + 8);
                if (elect_one()) {
#pragma unroll
                    for (int n = k < 5 ? 2 * k : k + 2; n < (k < 3 ? 2 * k + 2 : k == 3 ? 7 : k + 3); n++) {
                        mbar_expect_tx(hfull + 8 * (NST + n % 7), TILE);
                        bulk_load(sb + tail_h(n), src + tail_src(n), TILE, hfull + 8 * (NST + n % 7));
                    }
                }
            }
        } else {
            if (elect_one()) {
#pragma unroll
                for (int i = 0; i < NST; i++) mbar_init(full + 8 * i, 1);
                fence_mbar_init();
            }
            __syncwarp();
            asm volatile("bar.arrive 5, 160;" ::: "memory");
            asm volatile("bar.arrive 0, 448;" ::: "memory");
#pragma unroll 1
            for (int i = 0; i < NST; i++) {
                if (elect_one()) {
                    mbar_expect_tx(full + 8 * i, SLOT);
                    tma5b(sb + i * SLOT, &mB, i * 64, dt * 4, full + 8 * i);
                    tma4(sb + i * SLOT + 2 * TILE, &mX, i * 64, chunk * 64, full + 8 * i);
                }
                STAMPIF(i == 0, 1);
            }
            STAMP(2);
            named_bar(6, 160);
            uint32_t dst = sb;
#pragma unroll 1
            for (int i = NST; i < 32; i++) {
                if (i == 2 * NST) mbar_wait(bar_base);
                if (lane == 0) mbar_expect_tx(full + 8 * i, SLOT);
                mbar_wait(empty + 8 * (i - NST));
                PSTAMP(i);
                if (elect_one()) {
                    tma5b(dst, &mB, (i & 15) * 64, (i >> 4) * 64 + dt * 4, full + 8 * i);
                    tma4(dst + 2 * TILE, &mX, (i & 15) * 64, chunk * 64, full + 8 * i);
                }
                dst = dst == sb + (NST - 1) * SLOT ? sb : dst + SLOT;
            }
        }
    }
}

typedef CUresult (*EncodeFn)(CUtensorMap*, CUtensorMapDataType, cuuint32_t, void*, const cuuint64_t*, const cuuint64_t*, const cuuint32_t*,
                             const cuuint32_t*, CUtensorMapInterleave, CUtensorMapSwizzle, CUtensorMapL2promotion, CUtensorMapFloatOOBfill);

bool encode(EncodeFn fn, CUtensorMap* m, const void* ptr, int rank, const cuuint64_t* dims, const cuuint64_t* strides, const cuuint32_t* box,
            CUtensorMapL2promotion promo = CU_TENSOR_MAP_L2_PROMOTION_NONE) {
    const cuuint32_t es[5] = {1, 1, 1, 1, 1};
    return fn(m, CU_TENSOR_MAP_DATA_TYPE_BFLOAT16, rank, const_cast<void*>(ptr), dims, strides, box, es, CU_TENSOR_MAP_INTERLEAVE_NONE,
              CU_TENSOR_MAP_SWIZZLE_128B, promo, CU_TENSOR_MAP_FLOAT_OOB_FILL_NONE) == CUDA_SUCCESS;
}

}

extern "C" void kernel_launch(void* const* d_in, const int* in_sizes, int n_in, void* d_out, int out_size) {
    (void)in_sizes; (void)n_in; (void)out_size;
    Params prm;
    prm.x = (const __nv_bfloat16*)d_in[0];
    prm.lam_re = (const __nv_bfloat16*)d_in[1];
    prm.lam_im = (const __nv_bfloat16*)d_in[2];
    prm.b_re = (const __nv_bfloat16*)d_in[3];
    prm.b_im = (const __nv_bfloat16*)d_in[4];
    prm.c_re = (const __nv_bfloat16*)d_in[5];
    prm.c_im = (const __nv_bfloat16*)d_in[6];
    prm.log_dt = (const __nv_bfloat16*)d_in[7];
    prm.dskip = (const __nv_bfloat16*)d_in[8];
    prm.w_r = (const __nv_bfloat16*)d_in[10];
    prm.gate_w = (const __nv_bfloat16*)d_in[14];
    prm.out = (float*)d_out;
    cudaGetSymbolAddress((void**)&prm.s, g_scratch);
    prm.swapped = prm.b_im < prm.b_re;

    void* fnp = nullptr;
    cudaDriverEntryPointQueryResult qr;
    cudaGetDriverEntryPoint("cuTensorMapEncodeTiled", &fnp, cudaEnableDefault, &qr);
    EncodeFn fn = (EncodeFn)fnp;
    cudaFuncSetAttribute(fused_kernel, cudaFuncAttributeMaxDynamicSharedMemorySize, SMEM_BYTES);

    CUtensorMap mX, mB, mCre, mCim, mWg, mWu, mWd, mXr, mPB, mPC, mXe;
    const cuuint64_t row = 2048;
    {
        const cuuint64_t dims[4] = {1024, 2, 4, 976}, st[3] = {row, 32 * row, 2 * row};
        const cuuint32_t box[4] = {64, 2, 4, 16};
        encode(fn, &mX, prm.x, 4, dims, st, box, PROMO);
    }
    {
        const char *lo = (const char*)(prm.swapped ? prm.b_im : prm.b_re), *hi = (const char*)(prm.swapped ? prm.b_re : prm.b_im);
        const cuuint64_t dims[5] = {1024, 8, 2, 96, 2}, st[4] = {row, (cuuint64_t)(hi - lo), 8 * row, 256 * row};
        const cuuint32_t box[5] = {64, 8, 2, 4, 2};
        encode(fn, &mB, lo, 5, dims, st, box, PROMO);
    }
    {
        const cuuint64_t dims[5] = {1024, 2, 4, 2, 64}, st[4] = {row, 4 * row, 2 * row, 16 * row};
        const cuuint32_t box[5] = {64, 2, 4, 2, 8};
        encode(fn, &mCre, prm.c_re, 5, dims, st, box);
        encode(fn, &mCim, prm.c_im, 5, dims, st, box);
    }
    {
        const cuuint64_t dims[2] = {F_, D_}, st[1] = {F_ * 2}, dimsd[2] = {D_, F_}, std_[1] = {row};
        const cuuint32_t box[2] = {64, 64};
        encode(fn, &mWg, d_in[11], 2, dims, st, box);
        encode(fn, &mWu, d_in[12], 2, dims, st, box);
        encode(fn, &mWd, d_in[13], 2, dimsd, std_, box);
    }
    for (int i = 0; i < 2; i++) {
        const char *p = (const char*)(i ? prm.c_re : prm.b_re), *q = (const char*)(i ? prm.c_im : prm.b_im);
        const cuuint64_t dims[4] = {64, 16, 1024, 2}, st[3] = {128, row, (cuuint64_t)(p < q ? q - p : p - q)};
        const cuuint32_t box[4] = {16, 4, 4, 2};
        encode(fn, i ? &mPC : &mPB, p < q ? p : q, 4, dims, st, box, CU_TENSOR_MAP_L2_PROMOTION_L2_128B);
    }
    {
        const cuuint64_t dims[3] = {D_ - 192, S_, 4}, st[2] = {row, 128};
        const cuuint32_t box[3] = {64, 16, 4};
        encode(fn, &mXr, prm.x, 3, dims, st, box);
    }
    {
        const cuuint64_t dims[5] = {1024, 2, 4, 4, S_ / 32}, st[4] = {4 * row, row, 8 * row, 32 * row};
        const cuuint32_t box[5] = {64, 2, 4, 2, 4};
        encode(fn, &mXe, prm.x, 5, dims, st, box);
    }
    fused_kernel<<<NCTA, 512, SMEM_BYTES, cudaStreamPerThread>>>(prm, mX, mB, mCre, mCim, mWg, mWu, mWd, mXr, mPB, mPC, mXe);
}
```

```cpp
#include <cuda_runtime.h>
#include <cuda_bf16.h>
#include <cuda.h>
#include <stdint.h>

namespace {

constexpr int S_ = 2048, D_ = 1024, F_ = 3584;
constexpr int NCTA = 128;
constexpr int NSPL = 9, NBIG = 64 - NSPL, NENT = NBIG + 2 * NSPL;
constexpr int NST = 5;
constexpr int NFT = 5;
constexpr uint32_t SLOT = 32768, TILE = 8192;
constexpr uint32_t OFF_FT = NST * SLOT;
constexpr uint32_t OFF_XS = OFF_FT + NFT * TILE;
constexpr uint32_t OFF_LIST = OFF_XS + 8192;
constexpr uint32_t OFF_RED = OFF_XS + 4096;
constexpr uint32_t OFF_CONST = OFF_XS + 16384;
constexpr uint32_t OFF_M = OFF_CONST + 8192;
constexpr uint32_t OFF_HID = OFF_CONST;
constexpr uint32_t OFF_G = OFF_M + 512;
constexpr uint32_t OFF_DK = OFF_G + 256;
constexpr uint32_t OFF_FULL = OFF_DK + 256;
constexpr uint32_t OFF_EMPTY = OFF_FULL + 103 * 8;
constexpr uint32_t OFF_KEYS = OFF_EMPTY + 87 * 8;
constexpr uint32_t OFF_SEL = OFF_KEYS + 32;
constexpr uint32_t OFF_EPOCH = OFF_SEL + 32;
constexpr uint32_t OFF_PROF = OFF_EPOCH + 16;
constexpr uint32_t SMEM_BYTES = OFF_PROF + 432;
static_assert(SMEM_BYTES <= 232448, "smem");

static_assert(NBIG % NST == 0, "tail layout");
__host__ __device__ constexpr uint32_t tail_c(int j) { return j < 8 ? SLOT + j * 2 * TILE : OFF_FT + 5 * TILE; }
__host__ __device__ constexpr uint32_t tail_h(int n) { return n % 7 < 4 ? n % 7 * TILE : OFF_FT + (n % 7 - 2) * TILE; }
__host__ __device__ constexpr uint32_t tail_src(int n) { return (n % NSPL + NBIG - 32) * 2 * TILE + n / NSPL * TILE; }
__host__ __device__ constexpr int c_col(int i) { return ((i & 3) + ((i >> 1) & 12)) * 64; }

constexpr uint32_t SPIN_LIMIT = 1u << 18;

struct Scratch {
    uint2 carry[16 * 1024];
    uint2 hid[NCTA * 128];
    uint32_t y[8 * 8 * D_];
    uint32_t key[NCTA * 8];
    uint32_t gate[S_];
    uint4 part[112 * 128];
    uint2 armed[NCTA * 4];
    unsigned int epoch[256];
    uint4 start[32 * 2];
    uint4 h[16 * 32 * 1024];
};
__device__ __align__(1024) Scratch g_scratch;
#define STAMPW_(cond, w) do {} while (0)
#define GSTAMP(cond, w) do {} while (0)
#define LSTAMP(cond, w) STAMPW_(cond, w)
#define LT 0
#define STAMPW(cond, w) STAMPW_(cond, w)
#define STAMPIF(cond, i) STAMPW(cond, 96 + (i))
#define STAMP(i) STAMPW(1, 96 + (i))
#define KSTAMP(i) STAMPW((threadIdx.x & 127) == 0, i)
#define PSTAMP(i) STAMPW((i) < 56 && (i) >= 32, 160 + (i))

struct Params {
    const __nv_bfloat16 *x, *b_re, *b_im, *lam_re, *lam_im, *c_re, *c_im, *log_dt, *dskip, *w_r, *gate_w;
    float* out;
    Scratch* s;
    int swapped;
};

__device__ __forceinline__ uint32_t smem_u32(const void* p) { return (uint32_t)__cvta_generic_to_shared(p); }
__device__ __forceinline__ void mbar_init(uint32_t bar, uint32_t cnt) { asm volatile("mbarrier.init.shared::cta.b64 [%0], %1;" ::"r"(bar), "r"(cnt) : "memory"); }
__device__ __forceinline__ void mbar_expect_tx(uint32_t bar, uint32_t bytes) { asm volatile("mbarrier.arrive.expect_tx.shared::cta.b64 _, [%0], %1;" ::"r"(bar), "r"(bytes) : "memory"); }
__device__ __forceinline__ void mbar_arrive(uint32_t bar) { asm volatile("mbarrier.arrive.shared::cta.b64 _, [%0];" ::"r"(bar) : "memory"); }
__device__ __forceinline__ bool mbar_test(uint32_t bar, uint32_t parity) {
    uint32_t ok;
    asm volatile("{ .reg .pred p; mbarrier.test_wait.parity.shared::cta.b64 p, [%1], %2; selp.u32 %0, 1, 0, p; }" : "=r"(ok) : "r"(bar), "r"(parity) : "memory");
    return __all_sync(0xffffffffu, ok);
}
__device__ __forceinline__ void mbar_wait(uint32_t bar, uint32_t parity = 0) {
    asm volatile("{ .reg .pred p; .reg .u32 n; mov.u32 n, 0;\nW%=: mbarrier.try_wait.parity.shared::cta.b64 p, [%0], %1; @p bra D%=;\n"
                 "add.u32 n, n, 0x4000; setp.ne.u32 p, n, 0; @p bra W%=; trap;\nD%=: }" ::"r"(bar), "r"(parity) : "memory");
}
__device__ __forceinline__ bool elect_one() {
    uint32_t pred;
    asm volatile("{ .reg .pred P; elect.sync _|P, 0xffffffff; selp.b32 %0, 1, 0, P; }" : "=r"(pred));
    return pred;
}
__device__ __forceinline__ void named_bar(int id, int n) { asm volatile("bar.sync %0, %1;" ::"r"(id), "r"(n) : "memory"); }
__device__ __forceinline__ void fence_mbar_init() { asm volatile("fence.mbarrier_init.release.cluster;" ::: "memory"); }
__device__ __forceinline__ void fence_async_smem() { asm volatile("fence.proxy.async.shared::cta;" ::: "memory"); }

__device__ __forceinline__ void bulk_load(uint32_t dst, const void* src, uint32_t bytes, uint32_t bar) {
    asm volatile("cp.async.bulk.shared::cluster.global.mbarrier::complete_tx::bytes [%0], [%1], %2, [%3];" ::"r"(dst), "l"(src), "r"(bytes), "r"(bar) : "memory");
}
__device__ __forceinline__ void cp_async16(uint32_t dst, const void* src) { asm volatile("cp.async.cg.shared.global [%0], [%1], 16;" ::"r"(dst), "l"(src) : "memory"); }
__device__ __forceinline__ void sts128(uint32_t a, uint32_t x, uint32_t y, uint32_t z, uint32_t w) {
    asm volatile("st.shared.v4.u32 [%0], {%1,%2,%3,%4};" ::"r"(a), "r"(x), "r"(y), "r"(z), "r"(w) : "memory");
}
__device__ __forceinline__ uint2 lds64(uint32_t a) {
    uint2 v;
    asm volatile("ld.shared.v2.u32 {%0,%1}, [%2];" : "=r"(v.x), "=r"(v.y) : "r"(a) : "memory");
    return v;
}
__device__ __forceinline__ uint32_t lds32(uint32_t a) {
    uint32_t v;
    asm volatile("ld.volatile.shared.u32 %0, [%1];" : "=r"(v) : "r"(a) : "memory");
    return v;
}
__device__ __forceinline__ void stg128(void* p, uint32_t x, uint32_t y, uint32_t z, uint32_t w) {
    asm volatile("st.global.v4.u32 [%0], {%1,%2,%3,%4};" ::"l"(p), "r"(x), "r"(y), "r"(z), "r"(w) : "memory");
}
__device__ __forceinline__ void st_relaxed(void* p, uint32_t x) { asm volatile("st.relaxed.gpu.global.b32 [%0], %1;" ::"l"(p), "r"(x) : "memory"); }
__device__ __forceinline__ void st_relaxed2(void* p, uint32_t x, uint32_t y) { asm volatile("st.relaxed.gpu.global.v2.b32 [%0], {%1, %2};" ::"l"(p), "r"(x), "r"(y) : "memory"); }
__device__ __forceinline__ void st_relaxed4(void* p, uint32_t x, uint32_t y, uint32_t z, uint32_t w) {
    asm volatile("st.relaxed.gpu.global.v4.b32 [%0], {%1, %2, %3, %4};" ::"l"(p), "r"(x), "r"(y), "r"(z), "r"(w) : "memory");
}
__device__ __forceinline__ uint32_t ld_relaxed(const void* p) {
    uint32_t v;
    asm volatile("ld.relaxed.gpu.global.b32 %0, [%1];" : "=r"(v) : "l"(p) : "memory");
    return v;
}
__device__ __forceinline__ uint2 ld_relaxed2(const void* p) {
    uint2 v;
    asm volatile("ld.relaxed.gpu.global.v2.b32 {%0, %1}, [%2];" : "=r"(v.x), "=r"(v.y) : "l"(p) : "memory");
    return v;
}
__device__ __forceinline__ uint4 ld_relaxed4(const void* p) {
    uint4 v;
    asm volatile("ld.relaxed.gpu.global.v4.b32 {%0, %1, %2, %3}, [%4];" : "=r"(v.x), "=r"(v.y), "=r"(v.z), "=r"(v.w) : "l"(p) : "memory");
    return v;
}
__device__ __forceinline__ uint32_t clk32() { uint32_t c; asm volatile("mov.u32 %0, %%clock;" : "=r"(c)); return c; }
__device__ __forceinline__ uint32_t gtime32() { uint32_t c; asm volatile("mov.u32 %0, %%globaltimer_lo;" : "=r"(c)); return c; }
__device__ __forceinline__ void sched_fence(uint32_t t) { while ((int)(clk32() - t) < 0) {} }
__device__ __forceinline__ void sleep_until(uint32_t t) { while ((int)(clk32() - t) < 0) __nanosleep(40); }

__device__ __forceinline__ void tma2(uint32_t dst, const CUtensorMap* m, int c0, int c1, uint32_t bar) {
    asm volatile("{ .reg .b64 pol; createpolicy.fractional.L2::evict_first.b64 pol;\n"
                 "cp.async.bulk.tensor.2d.shared::cluster.global.mbarrier::complete_tx::bytes.L2::cache_hint [%0], [%1, {%3, %4}], [%2], pol; }"
                 ::"r"(dst), "l"(m), "r"(bar), "r"(c0), "r"(c1) : "memory");
}
__device__ __forceinline__ void tma3(uint32_t dst, const CUtensorMap* m, int c0, int c1, uint32_t bar) {
    asm volatile("cp.async.bulk.tensor.3d.shared::cluster.global.mbarrier::complete_tx::bytes [%0], [%1, {%3, %4, %5}], [%2];"
                 ::"r"(dst), "l"(m), "r"(bar), "r"(c0), "r"(c1), "r"(0) : "memory");
}
__device__ __forceinline__ void tma4(uint32_t dst, const CUtensorMap* m, int c0, int c3, uint32_t bar) {
    asm volatile("cp.async.bulk.tensor.4d.shared::cluster.global.mbarrier::complete_tx::bytes [%0], [%1, {%3, %5, %5, %4}], [%2];"
                 ::"r"(dst), "l"(m), "r"(bar), "r"(c0), "r"(c3), "r"(0) : "memory");
}
__device__ __forceinline__ void tma5(uint32_t dst, const CUtensorMap* m, int c0, int c4, uint32_t bar) {
    asm volatile("cp.async.bulk.tensor.5d.shared::cluster.global.mbarrier::complete_tx::bytes [%0], [%1, {%3, %5, %5, %5, %4}], [%2];"
                 ::"r"(dst), "l"(m), "r"(bar), "r"(c0), "r"(c4), "r"(0) : "memory");
}
__device__ __forceinline__ void tma5b(uint32_t dst, const CUtensorMap* m, int c0, int c3, uint32_t bar) {
    asm volatile("cp.async.bulk.tensor.5d.shared::cluster.global.mbarrier::complete_tx::bytes [%0], [%1, {%3, %5, %5, %4, %5}], [%2];"
                 ::"r"(dst), "l"(m), "r"(bar), "r"(c0), "r"(c3), "r"(0) : "memory");
}
__device__ __forceinline__ void prefetch_l2(const void* p) { asm volatile("prefetch.global.L2 [%0];" ::"l"(p)); }
__device__ __forceinline__ void prefetch_map(const CUtensorMap* m) { asm volatile("prefetch.tensormap [%0];" ::"l"(m)); }
__device__ __forceinline__ uint32_t uni(uint32_t v) { return __shfl_sync(0xffffffffu, v, 0); }

__device__ __forceinline__ uint32_t make_desc(uint32_t addr) { return ((addr & 0x3FFFF) >> 4) | (1u << 16); }
__device__ __forceinline__ uint32_t make_desc_h(uint32_t addr) { return ((addr & 0x3FFFF) >> 4) | (32u << 16); }
template <int H> __device__ __forceinline__ uint64_t desc64(uint32_t lo) {
    uint64_t d;
    asm volatile("mov.b64 %0, {%1, %2};" : "=l"(d) : "r"(lo), "n"(64u | ((H ? 2u : 1u) << 30)));
    return d;
}
__device__ __forceinline__ void wgmma_fence() { asm volatile("wgmma.fence.sync.aligned;" ::: "memory"); }
__device__ __forceinline__ void wgmma_commit() { asm volatile("wgmma.commit_group.sync.aligned;" ::: "memory"); }
template <int N> __device__ __forceinline__ void wgmma_wait() { asm volatile("wgmma.wait_group.sync.aligned %0;" ::"n"(N) : "memory"); }

#define R8(d, i) "+f"(d[i]), "+f"(d[i + 1]), "+f"(d[i + 2]), "+f"(d[i + 3]), "+f"(d[i + 4]), "+f"(d[i + 5]), "+f"(d[i + 6]), "+f"(d[i + 7])
#define R64(d) R8(d, 0), R8(d, 8), R8(d, 16), R8(d, 24), R8(d, 32), R8(d, 40), R8(d, 48), R8(d, 56)
template <int TA>
__device__ __forceinline__ void wgmma_n128(float (&d)[64], uint64_t da, uint64_t db, int scale_d = 1) {
    asm volatile("{ .reg .pred p; setp.ne.b32 p, %66, 0;\n"
                 "wgmma.mma_async.sync.aligned.m64n128k16.f32.bf16.bf16 "
                 "{%0,%1,%2,%3,%4,%5,%6,%7,%8,%9,%10,%11,%12,%13,%14,%15,%16,%17,%18,%19,%20,%21,%22,%23,%24,%25,%26,%27,%28,%29,%30,%31,"
                 "%32,%33,%34,%35,%36,%37,%38,%39,%40,%41,%42,%43,%44,%45,%46,%47,%48,%49,%50,%51,%52,%53,%54,%55,%56,%57,%58,%59,%60,%61,%62,%63}, "
                 "%64, %65, p, 1, 1, %67, 0; }"
                 : R64(d)
                 : "l"(da), "l"(db), "r"(scale_d), "n"(TA));
}
__device__ __forceinline__ void pin4(float (&d)[4]) { asm volatile("" : "+f"(d[0]), "+f"(d[1]), "+f"(d[2]), "+f"(d[3])::"memory"); }
__device__ __forceinline__ void pin64(float (&d)[64]) { asm volatile("" : R64(d)::"memory"); }

template <int TA>
__device__ __forceinline__ void wgmma_n8(float (&d)[4], uint64_t da, uint64_t db, int scale_d = 1) {
    asm volatile("{ .reg .pred p; setp.ne.b32 p, %7, 0;\n"
                 "wgmma.mma_async.sync.aligned.m64n8k16.f32.bf16.bf16 {%0,%1,%2,%3}, %4, %5, p, 1, 1, %6, 0; }"
                 : "+f"(d[0]), "+f"(d[1]), "+f"(d[2]), "+f"(d[3])
                 : "l"(da), "l"(db), "n"(TA), "r"(scale_d));
}

__device__ __forceinline__ float bf_lo(uint32_t u) { return __uint_as_float(u << 16); }
__device__ __forceinline__ float bf_hi(uint32_t u) { return __uint_as_float(u & 0xFFFF0000u); }
__device__ __forceinline__ float rbf(float v) { return __bfloat162float(__float2bfloat16_rn(v)); }
__device__ __forceinline__ uint32_t pack_bf(float lo, float hi) {
    uint32_t r;
    asm("cvt.rn.bf16x2.f32 %0, %1, %2;" : "=r"(r) : "f"(hi), "f"(lo));
    return r;
}
__device__ __forceinline__ uint32_t mul_bf2(uint32_t a, uint32_t b) {
    uint32_t r;
    asm("mul.rn.bf16x2 %0, %1, %2;" : "=r"(r) : "r"(a), "r"(b));
    return r;
}
__device__ __forceinline__ uint32_t fma_bf2(uint32_t a, uint32_t b, uint32_t c) {
    uint32_t r;
    asm("fma.rn.bf16x2 %0, %1, %2, %3;" : "=r"(r) : "r"(a), "r"(b), "r"(c));
    return r;
}
__device__ __forceinline__ float2 cmul(float2 a, float2 b) { return make_float2(a.x * b.x - a.y * b.y, a.x * b.y + a.y * b.x); }
__device__ __forceinline__ float2 cfma(float2 a, float2 b, float2 c) {
    return make_float2(fmaf(a.x, b.x, fmaf(-a.y, b.y, c.x)), fmaf(a.x, b.y, fmaf(a.y, b.x, c.y)));
}
__device__ __forceinline__ float sigmoidf_(float v) { return __fdividef(1.0f, 1.0f + expf(-v)); }

#define SCHED_NAMES T_W0, T_INIT, T_SMALL, T_W3, PF0, PF1, RT0, RT1, RT2, RT3, T_BASE, G_NS, GT0, GL, GQ, GT1, G0, T_CP0, T_CP1, GAP0, GAP1, T_OWN, \
    T_RETRY, T_Y, RS_E, PB_E0, PB_STEP, PC_E0, PC_STEP, PC_N, PC_E1, PC_S1, GU_E0, W_NUM, GC0, GCS, GCS4, GCH, HG, DL0, DLS, DN_E0
enum { SCHED_NAMES, NTUNE };
constexpr int sched_default[NTUNE] = {
    600, 1000, 1000, 1000,
    1100, 400,
    2200, 2700, 3200, 3700,
    2500, 7,
    6200, 600, 1023, 7200,
    800, 900, 900,
    270, 300,
    1000, 200, 700,
    4,
    4, 2, 12, 4, 6, 50, 3,
    4, 8, 14, 8, 6, 11,
    43, 37, 8, 48};
template <int I> struct Sched { static constexpr int v = sched_default[I]; };
#define TN(i) (Sched<i>::v)
#define DBG 0
#define TDBG 0
#define X0 1
#define GE 8
#define PROMO CU_TENSOR_MAP_L2_PROMOTION_L2_256B

template <int TA, class H>
__device__ __forceinline__ void run_entry(uint32_t lo32, uint32_t prev, int accumulate, float (&accA)[64], float (&accB)[64], H inside) {
    const uint64_t da = desc64<TA>(lo32), db = TA ? desc64<0>(lo32 + (2 * TILE >> 4) - (31u << 16)) : da + (2 * TILE >> 4);
    wgmma_fence();
#pragma unroll
    for (int kk = 0; kk < 4; kk++) {
        wgmma_n128<TA>(accA, da + kk * (TA ? 128 : 2), db + kk * 2, kk > 0 ? 1 : accumulate);
        wgmma_n128<TA>(accB, da + 512 + kk * (TA ? 128 : 2), db + kk * 2, kk > 0 ? 1 : accumulate);
        if (kk == 1) {
            wgmma_commit();
            wgmma_wait<1>();
            if ((threadIdx.x & 31) == 0) mbar_arrive(prev);
            inside();
        }
    }
    wgmma_commit();
}
template <int TA, class H>
__device__ __forceinline__ void run_entries(uint32_t sb, int lo, int hi, int slot, float (&accA)[64], float (&accB)[64], H after) {
    const uint32_t da0 = TA ? make_desc_h(sb) : make_desc(sb), dlast = da0 + (NST - 1) * (SLOT >> 4);
    uint32_t prev = sb + OFF_FULL + 8 * 101, bar = sb + OFF_FULL + 8 * lo, lo32 = da0 + slot * (SLOT >> 4);
    int accumulate = 0;
#pragma unroll 1
    for (int i = lo; i < hi; i++) {
        mbar_wait(bar);
        KSTAMP(i);
        run_entry<TA>(lo32, prev, accumulate, accA, accB, []() {});
        prev = bar + (OFF_EMPTY - OFF_FULL);
        bar += 8;
        lo32 = lo32 == dlast ? da0 : lo32 + (SLOT >> 4);
        accumulate = 1;
        after(i);
    }
}

template <int TA>
__device__ __forceinline__ void small_tile(float (&acc)[4], uint32_t alo, uint32_t blo, bool first) {
    const uint64_t da = desc64<0>(alo), db = desc64<0>(blo);
#pragma unroll
    for (int kk = 0; kk < 4; kk++) wgmma_n8<TA>(acc, da + kk * (TA ? 128 : 2), db + kk * 2, kk > 0 || !first);
}

template <int N>
__device__ __forceinline__ uint32_t check_tile(uint32_t sb, uint32_t dst, uint32_t probe, const char* src, uint32_t par, uint32_t bar, uint32_t phase, uint32_t pause) {
    if (TDBG & 4) return phase;
#pragma unroll 1
    for (uint32_t it = 0; it < SPIN_LIMIT; it++) {
        uint32_t v[N], bad = 0;
#pragma unroll
        for (int u = 0; u < N; u++) v[u] = lds32(dst + probe + (u >> 1) * 2048 + (u & 1) * 256);
#pragma unroll
        for (int u = 0; u < N; u += 4)
            asm("{ .reg .b32 a, b; lop3.b32 a, %1, %2, %5, 0x7E; lop3.b32 b, %3, %4, %5, 0x7E; lop3.b32 %0, %0, a, b, 0xFE; }"
                : "+r"(bad) : "r"(v[u]), "r"(v[u + 1]), "r"(v[u + 2]), "r"(v[u + 3]), "r"(par));
        if (!__any_sync(0xffffffffu, bad & 1u)) return phase;
        STAMP(10);
        __nanosleep(pause);
        if (elect_one()) {
            mbar_expect_tx(bar, N * 1024);
            bulk_load(dst, src, N * 1024, bar);
        }
        mbar_wait(bar, phase);
        phase ^= 1;
    }
    __trap();
    return 0;
}

__global__ void __launch_bounds__(512, 1)
fused_kernel(const __grid_constant__ Params prm, const __grid_constant__ CUtensorMap mX, const __grid_constant__ CUtensorMap mB, const __grid_constant__ CUtensorMap mCre,
             const __grid_constant__ CUtensorMap mCim, const __grid_constant__ CUtensorMap mWg, const __grid_constant__ CUtensorMap mWu,
             const __grid_constant__ CUtensorMap mWd, const __grid_constant__ CUtensorMap mXr,
             const __grid_constant__ CUtensorMap mXe) {
    {
        const uint32_t t = threadIdx.x, b = blockIdx.x;
        const uint32_t row = t < 32 ? ((b & 60) * 2 + (b >> 6) * 4 + (b & 3)) * 16 + (t >> 1) : b * 4 + ((t >> 1) & 3);
        const char* base = (const char*)(t < 32 ? prm.x : t < 40 ? prm.b_re : prm.b_im);
        asm volatile("{ .reg .pred p; setp.lt.u32 p, %1, 48; @p prefetch.global.L2 [%0]; }" ::"l"(base + (row * 2048 + (t & 1) * 128)), "r"(t) : "memory");
    }
    extern __shared__ __align__(1024) uint8_t smem[];
    uint32_t sb;
    asm volatile("mov.u32 %0, %1;" : "=r"(sb) : "r"(smem_u32(smem)));
    const int tid = threadIdx.x, warp = __shfl_sync(0xffffffffu, tid >> 5, 0), lane = tid & 31;
    const int cta = blockIdx.x;
    const uint32_t cstart = clk32();
    const int chunk = (cta >> 2) & 15;
    const int dt = (cta >> 6) * 4 + (cta & 3);
    const int rid = chunk * 8 + dt;
    const int kslot = (rid & 3) * 32 + (rid >> 2);
    const bool owner = cta < 112;
    const uint32_t full = sb + OFF_FULL, empty = sb + OFF_EMPTY;
    const uint32_t bar_epoch = full + 8 * 73, dfull = full + 8 * 74, bar_retry = full + 8 * 81, bar_x = full + 8 * 82, ffull = full + 8 * 84,
                   hfull = full + 8 * 89, bar_base = full + 8 * 102;
    const uint32_t fempty = empty + 8 * 66, bar_order = empty + 8 * 71, bar_stored = empty + 8 * 73, bar_dfree = empty + 8 * 74,
                   bar_out = empty + 8 * 77, bar_g = empty + 8 * 85, bar_const = empty + 8 * 86;
    const int w = warp & 3, g = lane >> 2, c = lane & 3, at = tid & 127;

    const uint32_t probe = (lane >> 3) * 32 + (g & 1) * 144 + (c & 1) * 520 + (c >> 1) * 1028;

    LSTAMP(tid == 0, 96);
    GSTAMP(tid == 0, 94);
    auto init_barriers = [&](uint32_t base, uint32_t cnt, auto n) {
        if (elect_one()) {
#pragma unroll
            for (int i = 0; i < n(); i++) mbar_init(base + 8 * i, cnt);
            fence_mbar_init();
        }
        __syncwarp();
    };
    if (warp != 12) {
        if (warp == 15 && !(cta & 3) && lane < 8) st_relaxed((uint32_t*)&prm.s->start[cta >> 1] + lane, (lane & 1) ? gtime32() : cstart);
        if (warp < 12) sleep_until(cstart + (warp < 4 ? TN(T_W0) : TN(T_INIT)));
    }
    if (warp < 8) {
        if (warp < 4) init_barriers(warp == 0 ? full + 40 : warp == 3 ? full + 8 * 98 : empty + 40 * (warp - 1), (warp + 1) & 2 ? 4 : 1, []() { return 5; });
        else init_barriers(full + 80 + 176 * w, 1, []() { return 22; });
        asm volatile("setmaxnreg.inc.sync.aligned.u32 192;");
        if (warp < 4) {
            named_bar(5, 160);
            asm volatile("bar.arrive 0, 448;" ::: "memory");
            asm volatile("bar.arrive 6, 160;" ::: "memory");
            asm volatile("bar.arrive 7, 160;" ::: "memory");
        } else named_bar(0, 448);
        const int wg = warp >> 2;
        const int p = wg * 512 + dt * 32 + w * 8 + g;
        uint32_t cp = sb + OFF_CONST + 8 * (wg * 64 + w * 8 + g), cw = cp + 1024 * c, cm = sb + OFF_M + 4 * (wg * 64 + w * 8 + g);
        const int j1 = chunk - 1 - c;
        uint2* cq = &prm.s->carry[j1 * 1024 + p];
        char* hd = reinterpret_cast<char*>(prm.s->h) + (size_t)chunk * 524288 + wg * 262144 + (dt >> 1) * 16384 + ((dt & 1) * 4 + w) * 1024 + g * 64 + ((c ^ (g >> 1)) << 4);
        const bool never = uni(cstart == 0 && sb == 0);
        asm volatile("" : "+l"(cq), "+l"(hd), "+r"(cp), "+r"(cw), "+r"(cm));
        float2 a[2], a32[2], a64[2], a512[2], pw32[2], pw128[2];
        uint32_t mm[2], t2, par;
        auto constants = [&](int h) {
            if (h) { t2 = lds32(sb + OFF_EPOCH + 4); par = lds32(sb + OFF_EPOCH); }
            auto ldc = [](uint32_t a) { const uint2 v = lds64(a); return make_float2(__uint_as_float(v.x), __uint_as_float(v.y)); };
            a[h] = ldc(cp + 256 * h); a32[h] = ldc(cp + 256 * h + 1024); a64[h] = ldc(cp + 256 * h + 2048); a512[h] = ldc(cp + 256 * h + 7168);
            pw32[h] = ldc(cw + 256 * h);
            pw128[h] = ldc(cw + 256 * h + 3072);
            mm[h] = lds32(cm + 128 * h);
        };
        if (wg == 1) {
            const int pc = w * 256 + dt * 32 + lane;
            const float lr = __bfloat162float(prm.lam_re[pc]), li = __bfloat162float(prm.lam_im[pc]), ld = __bfloat162float(prm.log_dt[pc]);
            const uint32_t dk = __ldg(reinterpret_cast<const uint32_t*>(prm.dskip + dt * 128) + (at & 63));
            reinterpret_cast<uint32_t*>(smem + OFF_DK)[at & 63] = dk;
            const float dtv = rbf(expf(ld));
            const float er = expf(dtv * lr);
            float sn, cs;
            sincosf(dtv * li, &sn, &cs);
            const float ar = er * cs, ai = er * sn;
            const float nr = ar - 1.0f, ni = ai;
            const bool big = fabsf(lr) >= fabsf(li);
            const float t = (big ? li : lr) / (big ? lr : li), dn = big ? lr + li * t : lr * t + li;
            const float cr = (big ? nr + ni * t : nr * t + ni) / dn, ci = (big ? ni - nr * t : ni * t - nr) / dn;
            float2* ct = reinterpret_cast<float2*>(smem + OFF_CONST) + at;
            float2 pw = make_float2(ar, prm.swapped ? -ai : ai);
            ct[0] = pw;
            const float mx = prm.swapped ? -2.f * ci : 2.f * cr, my = prm.swapped ? 2.f * cr : -2.f * ci;
            reinterpret_cast<uint32_t*>(smem + OFF_M)[at] = pack_bf(mx, my);
#pragma unroll
            for (int i = 0; i < 5; i++) pw = cmul(pw, pw);
#pragma unroll
            for (int i = 0; i < 2; i++) {
                const float2 p2 = cmul(pw, pw);
                ct[128 + 384 * i] = pw; ct[256 + 384 * i] = p2; ct[384 + 384 * i] = cmul(p2, pw);
                pw = cmul(p2, p2);
            }
            ct[896] = pw;
            mbar_wait(bar_epoch);
            mbar_wait(empty + 8 * TN(RS_E));
            st_relaxed2(&prm.s->hid[cta * 128 + at], ~0u, ~0u);
            st_relaxed4(&prm.s->y[((at >> 4) * 8 + (cta >> 4)) * D_ + (cta & 15) * 64 + (at & 15) * 4], 0u, 0u, 0u, 0u);
            st_relaxed2(&prm.s->carry[chunk * 1024 + pc], 0u, 0u);
            __syncwarp();
            if (lane == 0) mbar_arrive(bar_const);
            STAMPIF(at == 0, 3);
            mbar_wait(bar_const);
            constants(0);
            constants(1);
            mbar_wait(bar_order);
        }

        float accA[64], accB[64];
        run_entries<0>(sb, wg * 16, wg * 16 + 15, wg, accA, accB, [&](int i) {
            if (i == GE - 1) {
                mbar_wait(bar_base);
                const uint32_t t = lds32(sb + OFF_EPOCH + 8) + TN(GT0);
                const int late = clk32() - t - TN(GL);
                sched_fence(late < 0 ? t : t + TN(GL) + 256 + (late | TN(GQ)));
            }
        });
        mbar_wait(full + 8 * (wg * 16 + 15));
        KSTAMP(wg * 16 + 15);
        if (wg == 0) {
            mbar_wait(bar_const);
            run_entry<0>(make_desc(sb), empty + 8 * 14, 1, accA, accB, [&]() { constants(0); constants(1); });
            if (lane == 0) mbar_arrive(bar_order);
        } else run_entry<0>(make_desc(sb + SLOT), empty + 8 * 30, 1, accA, accB, [&]() { if (lane == 0) mbar_arrive(bar_order + 8); });
        uint2 v[4];
#pragma unroll
        for (int m = 0; m < 4; m++) v[m] = make_uint2(t2, t2);
        wgmma_wait<0>();
        pin64(accA); pin64(accB);
        if (lane == 0) mbar_arrive(empty + 8 * (wg * 16 + 15));
        LSTAMP(at == 0, 96 + 30 + 10 * wg); GSTAMP(LT && at == 0, 193 + wg);

        auto cut = [&]() { if (never) sched_fence(cstart); };
        auto poll = [&](int h) {
#pragma unroll
            for (int m = 0; m < 4; m++)
                asm volatile("{ .reg .pred p; setp.ge.s32 p, %3, %4; @p ld.relaxed.gpu.global.v2.b32 {%0, %1}, [%2]; }"
                             : "+r"(v[m].x), "+r"(v[m].y) : "l"(cq + 256 * h - 4096 * m), "r"(j1), "r"(4 * m) : "memory");
        };
        auto valid = [&]() {
            uint32_t bad = 0;
#pragma unroll
            for (int m = 0; m < 4; m++) bad |= (v[m].x ^ t2) | (v[m].y ^ t2);
            return __all_sync(0xffffffffu, (bad & 3u) == 0);
        };
        float2 w0[2];
        uint32_t tp;
#pragma unroll
        for (int h = 0; h < 2; h++) {
            float (&acc)[64] = h ? accB : accA;
            float2 e = make_float2(acc[0], acc[2]);
#pragma unroll
            for (int s = 1; s < 32; s++) {
                const int i0 = 4 * (s >> 1) + (s & 1);
                e = cfma(a[h], e, make_float2(acc[i0], acc[i0 + 2]));
            }
            float2 y = make_float2(__shfl_up_sync(0xffffffffu, e.x, 1, 4), __shfl_up_sync(0xffffffffu, e.y, 1, 4));
            if (c >= 1) e = cfma(a32[h], y, e);
            y = make_float2(__shfl_up_sync(0xffffffffu, e.x, 2, 4), __shfl_up_sync(0xffffffffu, e.y, 2, 4));
            if (c >= 2) e = cfma(a64[h], y, e);
            if (c == 3) st_relaxed2(cq + 4096 + 256 * h, (__float_as_uint(e.x) & ~3u) | t2, (__float_as_uint(e.y) & ~3u) | t2);
            if (h == 0) tp = clk32();
            cut();
            w0[h] = make_float2(__shfl_up_sync(0xffffffffu, e.x, 1, 4), __shfl_up_sync(0xffffffffu, e.y, 1, 4));
            STAMPIF(at == 0, 31 + h + 10 * wg);
        }
        uint32_t sx[2][16], sy[2][16], mr[2][4];
        const uint32_t gap = wg ? TN(GAP1) : TN(GAP0);
#pragma unroll
        for (int h = 0; h < 2; h++) {
            const uint32_t sg = prm.swapped ? 0x80008000u : 0u;
            mr[h][0] = __byte_perm(mm[h], 0, 0x1010); mr[h][1] = __byte_perm(mm[h], 0, 0x3232);
            mr[h][2] = mr[h][1] ^ sg; mr[h][3] = mr[h][0] ^ sg ^ 0x80008000u;
        }
        auto put = [&](int e, int j) {
            uint32_t d[4];
#pragma unroll
            for (int u = 0; u < 4; u++) d[u] = fma_bf2(mr[e >> 1][2 * (e & 1)], sx[e >> 1][4 * j + u], mul_bf2(mr[e >> 1][2 * (e & 1) + 1], sy[e >> 1][4 * j + u]));
#pragma unroll
            for (int u = 0; u < 2; u++)
                asm("lop3.b32 %0, %0, %1, %2, 0xD8;" : "+r"(d[2 * (j & 1) + u]) : "r"(par), "r"((uint32_t)((w & 1) == u)));
            stg128(hd + e * 65536 + (j >> 1) * 8192 + (j & 1) * 512, d[0], d[1], d[2], d[3]);
            if (j == 3 && lane == 0) mbar_arrive(bar_out + 32 * wg + 8 * e);
        };
#pragma unroll
        for (int h = 0; h < 2; h++) {
            float (&acc)[64] = h ? accB : accA;
            uint32_t it = 0;
            if (h == 0) {
                sleep_until(tp + (wg ? TN(T_CP1) : TN(T_CP0)));
                poll(h);
            }
            while (!valid()) {
                if (++it > SPIN_LIMIT) __trap();
#pragma unroll
                for (int m = 0; m < 4; m++)
                    asm volatile("{ .reg .pred p; setp.ne.u32 p, %3, 0; @p ld.relaxed.gpu.global.v2.b32 {%0, %1}, [%2]; }"
                                 : "+r"(v[m].x), "+r"(v[m].y) : "l"(cq + 256 * h - 4096 * m), "r"(((v[m].x ^ t2) | (v[m].y ^ t2)) & 3u) : "memory");
            }
            float2 hin = make_float2(__uint_as_float(v[3].x), __uint_as_float(v[3].y));
#pragma unroll
            for (int m = 2; m >= 0; m--) hin = cfma(a512[h], hin, make_float2(__uint_as_float(v[m].x), __uint_as_float(v[m].y)));
            STAMPIF(at == 0 && it > 0 && h == 0, 39 + 10 * wg);
            if (c) hin = cmul(pw128[h], hin);
            hin.x += __shfl_xor_sync(0xffffffffu, hin.x, 1); hin.y += __shfl_xor_sync(0xffffffffu, hin.y, 1);
            hin.x += __shfl_xor_sync(0xffffffffu, hin.x, 2); hin.y += __shfl_xor_sync(0xffffffffu, hin.y, 2);
            float2 st = hin;
            if (c) st = cfma(pw32[h], hin, w0[h]);
            STAMPIF(at == 0, 33 + 3 * h + 10 * wg);
#pragma unroll
            for (int j = 0; j < 4; j++) {
#pragma unroll
                for (int u = 0; u < 4; u++) {
                    const int i0 = 16 * j + 4 * u;
                    const float2 y = cfma(a[h], st, make_float2(acc[i0], acc[i0 + 2]));
                    st = cfma(a[h], y, make_float2(acc[i0 + 1], acc[i0 + 3]));
                    sx[h][4 * j + u] = pack_bf(y.x, st.x); sy[h][4 * j + u] = pack_bf(y.y, st.y);
                }
                if (h) sleep_until(tp += gap);
                if (h == 0 && j == 1) poll(1);
                put(2 * h, j);
                cut();
            }
            STAMPIF(at == 0, 34 + 3 * h + 10 * wg);
            tp = clk32();
#pragma unroll
            for (int j = 0; j < 4; j++) {
                sleep_until(tp += gap);
                put(2 * h + 1, j);
            }
        }
        STAMPIF(at == 0, 38 + 10 * wg);

        if (wg == 1) {
            const char* src = reinterpret_cast<const char*>(prm.s->h) + (size_t)chunk * 524288;
            uint32_t rpar = 1;
#pragma unroll 1
            for (int n = w; n < 2 * NSPL; n += 4) {
                mbar_wait(empty + 8 * (NBIG - 7 + n));
                mbar_wait(hfull + 8 * (NST + n % 7), n / 7 & 1);
                const uint32_t dst = sb + tail_h(n);
                rpar = check_tile<8>(sb, dst, probe, src + tail_src(n), par, full + 8 * w, rpar, TN(T_RETRY));
                if (lane == 0) mbar_expect_tx(full + 8 * (NBIG + n), n < NSPL ? 2 * TILE : 0);
            }
        } else {
            asm volatile("setmaxnreg.inc.sync.aligned.u32 216;");
            const int tl = 64 * (w & 1) + 8 * (w >> 1) + g;
            float gf[4];
            float* op = prm.out + (size_t)(chunk * 128 + tl) * D_ + dt * 128 + 4 * c;
            const int xr = 2 * (g & 3) + (g >> 2);
            uint32_t xs = sb + (32 * (w & 1) + 8 * (w >> 1) + xr) * 128 + (((c >> 1) ^ xr) << 4) + (c & 1) * 8;
            uint32_t gs = sb + OFF_G + 2 * tl;
            asm volatile("" : "+r"(gs), "+l"(op), "+r"(xs));
            float outA[64], outB[64];
            STAMPIF(at == 0, 9);
            mbar_wait(bar_order + 8);
            STAMPIF(at == 0, 35);
            run_entries<1>(sb, 32, NBIG, 32 % NST, outA, outB, [](int) {});
            uint32_t gp[4], om[4];
            uint2 xt[4][8], dk[8];
            auto load_x = [&](int q, int j) {
#pragma unroll
                for (int r = 0; r < 2; r++) xt[2 * q + r][j] = lds64((xs ^ ((j & 3) << 5)) + (q ? tail_c(0) : OFF_FT) + (j >> 2) * TILE + r * 2048);
                if (q == 0) dk[j] = lds64(sb + OFF_DK + c * 8 + 32 * j);
            };
            auto term = [&](int q, int j) {
#pragma unroll
                for (int r = 2 * q; r < 2 * q + 2; r++) {
                    xt[r][j].x = mul_bf2(xt[r][j].x, fma_bf2(gp[r], dk[j].x, om[r]));
                    xt[r][j].y = mul_bf2(xt[r][j].y, fma_bf2(gp[r], dk[j].y, om[r]));
                }
            };
            auto store = [&](int q, int u0, int u1) {
                const float (&acc)[64] = q ? outB : outA;
#pragma unroll
                for (int u = u0; u < u1; u++) {
                    const int j = u >> 1, r = u & 1;
                    const int o = 8 * j + 2 * r;
                    const float gv = fabsf(gf[2 * q + r]);
                    const uint2 t = xt[2 * q + r][j];
                    stg128(op + (r * 32 + q * 16) * D_ + 16 * j, __float_as_uint(fmaf(gv, acc[o], bf_lo(t.x))), __float_as_uint(fmaf(gv, acc[o + 1], bf_hi(t.x))),
                           __float_as_uint(fmaf(gv, acc[o + 4], bf_lo(t.y))), __float_as_uint(fmaf(gv, acc[o + 5], bf_hi(t.y))));
                }
            };
            uint64_t dh = desc64<1>(make_desc_h(sb)), dc = desc64<0>(make_desc(sb));
#pragma unroll
            for (int n = 0; n < 2 * NSPL; n++) {
                const int j = n % NSPL;
                if (n == 0) mbar_wait(bar_g);
                if (n == X0) mbar_wait(bar_x);
                mbar_wait(full + 8 * (NBIG + n));
                KSTAMP(NBIG + n);
                asm volatile("mov.b64 %0, %0; mov.b64 %1, %1;" : "+l"(dh), "+l"(dc));
                const uint64_t da = dh + (tail_h(n) >> 4), db = dc + (tail_c(j) >> 4);
                const int xj = n - X0;
                wgmma_fence();
#pragma unroll
                for (int kk = 0; kk < 4; kk++) {
                    wgmma_n128<1>(n < NSPL ? outA : outB, da + kk * 128, db + kk * 2);
                    if (kk == 0 && n == 0) {
#pragma unroll
                        for (int r = 0; r < 4; r++) {
                            uint32_t u;
                            asm volatile("ld.shared.u16 %0, [%1];" : "=r"(u) : "r"(gs + (r & 1) * 64 + (r >> 1) * 32) : "memory");
                            gf[r] = bf_lo(u);
                        }
                    }
                    if (kk == 0 && xj >= 0 && xj < 8) load_x(0, xj);
                }
                wgmma_commit();
                if (n <= 2 * NSPL - 7) {
                    wgmma_wait<1>();
                    if (lane == 0) mbar_arrive(empty + 8 * (NBIG + n - 1));
                    if (!j) { LSTAMP(at == 0, 96 + 12 + n / NSPL); GSTAMP(LT && at == 0, 195 + n / NSPL); }
                } else if (n == 2 * NSPL - 1) {
                    mbar_wait(bar_x + 8);
                    load_x(1, 0);
                } else cut();
                if (n == 0) {
#pragma unroll
                    for (int r = 0; r < 4; r++) {
                        const bool routed = (int)__float_as_uint(gf[r]) < 0;
                        gp[r] = routed ? 0u : pack_bf(gf[r], gf[r]); om[r] = routed ? 0u : pack_bf(1.0f - gf[r], 1.0f - gf[r]);
                    }
                }
                if (xj >= 0 && xj < 8) term(0, xj);
                if (n == NSPL) pin64(outA);
                if (n >= NSPL) store(0, (j * 16 + 4) / NSPL, j == NSPL - 1 ? 16 : ((j + 1) * 16 + 4) / NSPL);
            }
            term(1, 0);
            cut();
            wgmma_wait<0>();
            pin64(outB);
            LSTAMP(at == 0, 96 + 51); GSTAMP(LT && at == 0, 197);
#pragma unroll
            for (int j = 1; j < 8; j++) load_x(1, j);
            store(1, 0, 2);
#pragma unroll
            for (int j = 1; j < 8; j++) {
                cut();
                term(1, j);
                store(1, 2 * j, 2 * j + 2);
            }
            __syncwarp();
            if (lane == 0) mbar_arrive(bar_stored);
            LSTAMP(at == 0, 96 + 52);
        }
    } else if (warp < 12) {
        asm volatile("setmaxnreg.dec.sync.aligned.u32 64;");
        init_barriers(empty + min(80 + 160 * w, 8 * 67), 4, []() { return 20; });
#pragma unroll
        for (int i = 0; i < 2; i++) sts128(sb + OFF_LIST + i * 2048 + at * 16, 0u, 0u, 0u, 0u);
        uint32_t* keys = reinterpret_cast<uint32_t*>(smem + OFF_KEYS);
        keys[4] = 0;
        named_bar(0, 448);
        if (at < 24) st_relaxed(at < 8 ? &prm.s->key[kslot * 8 + at] : &prm.s->gate[rid * 16 + at - 8], 0u);
        mbar_wait(bar_epoch);
        const uint32_t t2 = lds32(sb + OFF_EPOCH + 4);
        STAMPIF(at == 0, 20);
        float facc[4];
        const uint32_t dft = make_desc(sb + OFF_FT), dxs = make_desc(sb + OFF_XS);
#pragma unroll 1
        for (int u = 0; u < 4; u++) {
            mbar_wait(ffull + 8 * u);
            STAMPIF(at == 0, 4 + u);
            wgmma_fence();
            small_tile<0>(facc, dft + u * (TILE >> 4), dxs + u * 64, u == 0);
            wgmma_commit();
        }
        wgmma_wait<0>();
        pin4(facc);
        if (lane < 4) mbar_arrive(fempty + 8 * lane);
        auto gate_up = [&](auto rest) {
            uint32_t slot = 4, par = 0, prev = full + 8 * 101, e4 = 4 * TN(GC0);
#pragma unroll 1
            for (int j = 0; j < 14; j++) {
                if (j == 2) rest();
                STAMPW(at == 0, 75 + j);
                mbar_wait(ffull + 8 * slot, par);
                STAMPW(at == 0, 160 + j);
                mbar_wait(empty + 8 * (e4 >> 2));
                e4 += j < 8 ? TN(GCS) : TN(GCS4);
                wgmma_fence();
                small_tile<1>(facc, dft + slot * (TILE >> 4), dxs + j * 64, j == 0);
                wgmma_commit();
                wgmma_wait<1>();
                if (lane == 0) mbar_arrive(prev);
                prev = fempty + 8 * slot;
                if (++slot == NFT) { slot = 0; par ^= 1; }
            }
            wgmma_wait<0>();
            if (lane == 0) mbar_arrive(prev);
            pin4(facc);
        };
        auto help = [&]() {
            uint32_t slot = 4, par = 0, e4 = 4 * TN(GC0);
#pragma unroll 1
            for (int u = 0; u < 7; u++) {
                const uint32_t slot2 = slot == NFT - 1 ? 0 : slot + 1;
                mbar_wait(ffull + 8 * slot, par);
                par ^= slot2 == 0;
                mbar_wait(ffull + 8 * slot2, par);
                mbar_wait(empty + 8 * (e4 >> 2));
                e4 += TN(GCH);
                wgmma_fence();
                small_tile<1>(facc, dft + slot * (TILE >> 4), dxs, true);
                small_tile<1>(facc, dft + slot2 * (TILE >> 4), dxs + 64, false);
                wgmma_commit();
                wgmma_wait<0>();
                pin4(facc);
                if (lane < 2) mbar_arrive(fempty + 8 * (lane ? slot2 : slot));
                st_relaxed4(&prm.s->part[((cta - 112) * 7 + u) * 128 + at], (__float_as_uint(facc[0]) & ~3u) | t2, __float_as_uint(facc[1]),
                            __float_as_uint(facc[2]), __float_as_uint(facc[3]));
                slot = slot2 == NFT - 1 ? 0 : slot2 + 1;
                par ^= slot == 0;
            }
        };
        auto down = [&]() {
            const uint32_t dhid = make_desc(sb + OFF_HID);
#pragma unroll 1
            for (int j = 0; j < 7; j++) {
                mbar_wait(dfull + 8 * j);
                wgmma_fence();
                small_tile<1>(facc, dft + j * (TILE >> 4), dhid + j * 64, j == 0);
                wgmma_commit();
                if ((0x52 >> j) & 1) {
                    wgmma_wait<0>();
                    if (lane == 0) mbar_arrive(bar_dfree + 8 * (j / 3));
                }
            }
            wgmma_wait<0>();
            pin4(facc);
        };
        if ((c & 1) == (w >> 1)) {
            float* red = reinterpret_cast<float*>(smem + OFF_RED) + w * 32 + (c >> 1) * 16 + g;
            red[0] = (w & 1) ? facc[1] : facc[0];
            red[8] = (w & 1) ? facc[3] : facc[2];
        }
        named_bar(2, 128);
        STAMPIF(at == 0, 21);
        const uint32_t tpub = clk32();
        if (w < 2) {
            const float* red = reinterpret_cast<const float*>(smem + OFF_RED) + w * 16 + (lane & 15);
            const float v = rbf((red[0] + red[32]) + (red[64] + red[96]));
            if (w == 0) {
                uint32_t k = __float_as_uint(v);
                k = ((k ^ ((uint32_t)((int)k >> 31) | 0x80000000u)) & 0xFFFF0000u) | (t2 << 11) | (2047u - (uint32_t)(rid * 16 + (lane & 15)));
                int rank = 0;
#pragma unroll
                for (int i = 0; i < 8; i++) rank += __shfl_sync(0xffffffffu, k, (lane >> 4) * 8 + i) > k;
                rank += __shfl_xor_sync(0xffffffffu, rank, 16);
                if (rank < 8) st_relaxed(&prm.s->key[kslot * 8 + rank], k);
            } else if (lane < 16) st_relaxed(&prm.s->gate[rid * 16 + lane], __float_as_uint(rbf(sigmoidf_(v))) | t2);
            __syncwarp();
        }
        uint32_t it = 0;
        uint4 ka, kb4;
        mbar_wait(bar_base);
        sleep_until(lds32(sb + OFF_EPOCH + 8) + TN(GT1));
        sleep_until(tpub + TN(G0));
        bool bad = true;
        while (true) {
            if (bad) {
                ka = ld_relaxed4(&prm.s->key[at * 8]);
                kb4 = ld_relaxed4(&prm.s->key[at * 8 + 4]);
            }
            bad = (((ka.x ^ (t2 << 11)) | (kb4.x ^ (t2 << 11))) & 0x1800u) != 0;
            if (!__any_sync(0xffffffffu, bad)) break;
            if (++it > SPIN_LIMIT) __trap();
            __nanosleep(TN(T_RETRY));
        }
        STAMPIF(at == 0, 22);
        STAMPIF(at == 0 && it > 0, 23);
        const uint32_t m1 = __reduce_max_sync(0xffffffffu, ka.x), m2 = __reduce_max_sync(0xffffffffu, ka.x == m1 ? ka.y : ka.x);
        if (lane == 0) keys[w] = m2;
        named_bar(2, 128);
        const uint4 th4 = *reinterpret_cast<const uint4*>(keys);
        const uint32_t th = min(min(th4.x, th4.y), min(th4.z, th4.w));
        {
            const uint32_t k8[8] = {ka.x, ka.y, ka.z, ka.w, kb4.x, kb4.y, kb4.z, kb4.w};
            auto append = [&](int lo, int hi) {
                uint32_t n = 0, pos = 0;
#pragma unroll
                for (int i = lo; i < hi; i++) n += k8[i] >= th;
                asm volatile("{ .reg .pred p; setp.ne.u32 p, %2, 0; @p atom.shared.add.u32 %0, [%1], %2; }" : "+r"(pos) : "r"(sb + OFF_KEYS + 16), "r"(n) : "memory");
#pragma unroll
                for (int i = lo; i < hi; i++)
                    if (k8[i] >= th) reinterpret_cast<uint32_t*>(smem + OFF_LIST)[pos + i - lo] = k8[i];
            };
            append(0, 2);
            if (__any_sync(0xffffffffu, k8[2] >= th)) append(2, 8);
        }
        named_bar(2, 128);
        {
            const uint32_t* list = reinterpret_cast<const uint32_t*>(smem + OFF_LIST);
            const int n = (int)keys[4];
#pragma unroll 1
            for (int i0 = w * 32; i0 < n; i0 += 128) {
                const uint32_t k = list[i0 + lane];
                int rank = 0;
#pragma unroll 2
                for (int o = 0; o < n; o += 4) {
                    const uint4 l4 = *reinterpret_cast<const uint4*>(list + o);
                    rank += (l4.x > k) + (l4.y > k) + (l4.z > k) + (l4.w > k);
                }
                if (rank < 8) reinterpret_cast<uint32_t*>(smem + OFF_SEL)[rank] = k;
            }
        }
        named_bar(2, 128);
        STAMPIF(at == 0, 24);
        const uint32_t* sel = reinterpret_cast<const uint32_t*>(smem + OFF_SEL);
        auto gates = [&]() {
            uint32_t gv;
            it = 0;
            while (true) {
                gv = ld_relaxed(&prm.s->gate[chunk * 128 + at]);
                const uint32_t ar = ld_relaxed(&prm.s->armed[((cta >> 4) * 14 + min(lane, 13)) * 4]);
                if (__all_sync(0xffffffffu, (gv & 3u) == t2 && ar == t2)) break;
                if (++it > SPIN_LIMIT) __trap();
            }
            asm volatile("fence.acquire.gpu;" ::: "memory");
#pragma unroll
            for (int s = 0; s < 8; s++)
                if ((~sel[s] & 2047u) == (uint32_t)(chunk * 128 + at)) gv |= 0x80000000u;
            reinterpret_cast<uint16_t*>(smem + OFF_G)[at] = (uint16_t)(gv >> 16);
            __syncwarp();
            if (lane == 0) mbar_arrive(bar_g);
        };
        {
            const int tk = (at >> 3) & 7;
            const char* xt = (const char*)prm.x + (~sel[tk] & 2047u) * 2048 + (owner ? 256 : 0) + (at >> 6) * 128 + (at & 7) * 16;
#pragma unroll
            for (int i = 0; i < 7; i++) {
                if (i == 0 || owner) cp_async16(sb + OFF_XS + (2 * i + (at >> 6)) * 1024 + tk * 128 + (((at & 7) ^ tk) << 4), xt + i * 256);
                if (i == 0 || i == 6) asm volatile("cp.async.commit_group;" ::: "memory");
            }
            asm volatile("cp.async.wait_group 1;" ::: "memory");
            fence_async_smem();
            named_bar(2, 128);
            STAMPIF(at == 0, 25);
        }
        if (!owner) help();
        else {
            gate_up([&]() {
                asm volatile("cp.async.wait_all;" ::: "memory");
                fence_async_smem();
                named_bar(2, 128);
            });
            it = 0;
            while (true) {
                const uint4 v = ld_relaxed4(&prm.s->part[cta * 128 + at]);
                if (__all_sync(0xffffffffu, (v.x & 3u) == t2)) {
                    facc[0] += __uint_as_float(v.x); facc[1] += __uint_as_float(v.y); facc[2] += __uint_as_float(v.z); facc[3] += __uint_as_float(v.w);
                    break;
                }
                if (++it > SPIN_LIMIT) __trap();
                __nanosleep(TN(T_RETRY));
            }
            if (!(cta & 1)) {
#pragma unroll
                for (int u = 0; u < 4; u++) {
                    const float v = rbf(facc[u]);
                    facc[u] = __fdividef(v, 1.0f + __expf(-v));
                }
            }
            st_relaxed2(&prm.s->hid[cta * 128 + at], pack_bf(facc[0], facc[1]), pack_bf(facc[2], facc[3]));
        }
        STAMPIF(at == 0, 26);
        gates();
        uint32_t mine = __ballot_sync(0xffffffffu, lane < 8 && (int)((~sel[lane & 7] & 2047u) >> 7) == chunk), tr;
        uint2 xr, xd;
        float gr, rs;
        auto skip = [&](int n) {
#pragma unroll 1
            for (int i = 0; i < n; i++) mine &= mine - 1;
            if (mine) {
                const uint32_t key = sel[__ffs(mine) - 1], kb = key >> 16;
                tr = ~key & 2047u;
                xr = __ldg(reinterpret_cast<const uint2*>(prm.x + (size_t)tr * D_ + dt * 128) + lane);
                rs = rbf(sigmoidf_(bf_lo((kb & 0x8000u) ? (kb & 0x7FFFu) : (~kb & 0xFFFFu))));
                gr = fabsf(__bfloat162float(reinterpret_cast<const __nv_bfloat16*>(smem + OFF_G)[tr & 127]));
                xd = lds64(sb + OFF_DK + 8 * lane);
            }
        };
        mbar_wait(bar_g);
        skip(w);
        {
            mbar_wait(empty + 8 * max(TN(HG), 31));
            const uint2* hp = &prm.s->hid[(cta >> 4) * 14 * 128 + at];
            uint32_t hv[16];
            it = 0;
            while (true) {
                uint32_t top = 0;
#pragma unroll
                for (int j = 0; j < 7; j++) {
                    const uint2 hg = ld_relaxed2(hp + 256 * j), hu = ld_relaxed2(hp + 256 * j + 128);
                    top = max(top, max(hg.x, hu.x));
                    hv[2 * j] = mul_bf2(hg.x, hu.x); hv[2 * j + 1] = mul_bf2(hg.y, hu.y);
                }
                if (__all_sync(0xffffffffu, top != ~0u)) break;
                do {
                    if (++it > SPIN_LIMIT) __trap();
                } while (!__all_sync(0xffffffffu, ld_relaxed(hp + min(lane, 13) * 128 - lane) != ~0u));
            }
            STAMPIF(at == 0 && it > 0, 61);
            hv[14] = hv[15] = 0;
#pragma unroll
            for (int j = 0; j < 4; j++)
                asm volatile("stmatrix.sync.aligned.m8n8.x4.trans.shared.b16 [%0], {%1, %2, %3, %4};" ::"r"(
                                 sb + OFF_HID + (2 * j + (lane >> 4)) * 1024 + (lane & 7) * 128 + (((2 * w + ((lane >> 3) & 1)) ^ (lane & 7)) << 4)),
                             "r"(hv[4 * j]), "r"(hv[4 * j + 1]), "r"(hv[4 * j + 2]), "r"(hv[4 * j + 3]) : "memory");
        }
        fence_async_smem();
        named_bar(2, 128);
        STAMPIF(at == 0, 27);
        down();
#pragma unroll
        for (int u = 0; u < 4; u++)
            st_relaxed(&prm.s->y[((2 * c + (u & 1)) * 8 + (cta >> 4)) * D_ + (cta & 15) * 64 + w * 16 + g + 8 * (u >> 1)], (__float_as_uint(facc[u]) & ~3u) | t2);
        STAMPIF(at == 0, 28);
        sleep_until(clk32() + TN(T_Y));
        while (mine) {
            const uint32_t* yp = &prm.s->y[(__ffs(mine) - 1) * 8 * D_ + dt * 128 + 4 * lane];
            float y[4];
            it = 0;
            while (true) {
                uint32_t bad = 0;
                y[0] = y[1] = y[2] = y[3] = 0.f;
#pragma unroll
                for (int ks = 0; ks < 8; ks++) {
                    const uint4 v = ld_relaxed4(yp + ks * D_);
                    bad |= v.x ^ t2;
                    y[0] += __uint_as_float(v.x); y[1] += __uint_as_float(v.y); y[2] += __uint_as_float(v.z); y[3] += __uint_as_float(v.w);
                }
                if (__all_sync(0xffffffffu, (bad & 3u) == 0)) break;
                if (++it > SPIN_LIMIT) __trap();
            }
            STAMPIF(lane == 0 && it, 62);
#pragma unroll
            for (int u = 0; u < 4; u++) {
                const uint32_t x2 = (u & 2) ? xr.y : xr.x, d2 = mul_bf2(x2, (u & 2) ? xd.y : xd.x);
                y[u] = fmaf(gr, (u & 1) ? bf_hi(d2) : bf_lo(d2), rbf(rbf(1.0f - gr) * rbf(((u & 1) ? bf_hi(x2) : bf_lo(x2)) + rbf(rbf(y[u]) * rs))));
            }
            STAMPIF(lane == 0, 50);
            mbar_wait(bar_stored);
            asm volatile("red.global.add.v4.f32 [%0], {%1, %2, %3, %4};" ::"l"(prm.out + (size_t)tr * D_ + dt * 128 + 4 * lane), "f"(y[0]), "f"(y[1]), "f"(y[2]), "f"(y[3]) : "memory");
            skip(4);
        }
        LSTAMP(lane == 0, 96 + 29);
    } else {
        asm volatile("setmaxnreg.dec.sync.aligned.u32 40;");
        if (warp != 12) sleep_until(cstart + (warp == 13 ? TN(T_SMALL) : warp == 14 ? TN(PF0) - 250 : TN(T_W3)));
        auto behind = [&](int e) { mbar_wait(empty + 8 * e); };
        if (warp == 15) {
            prefetch_map(&mXr);
            named_bar(0, 448);
            asm volatile("bar.arrive 1, 64;" ::: "memory");
#pragma unroll 1
            for (int u = 0; u < 4; u++) {
                if (lane == 0) mbar_expect_tx(ffull + 8 * u, TILE);
                sleep_until(cstart + (u == 0 ? TN(RT0) : u == 1 ? TN(RT1) : u == 2 ? TN(RT2) : TN(RT3)));
                if (elect_one()) tma3(sb + OFF_FT + u * TILE, &mXr, u * 256, rid * 16, ffull + 8 * u);
                STAMP(53 + u);
            }
            if (sb & 1023) __trap();
            prefetch_map(&mWg);
            prefetch_map(&mWu);
            prefetch_map(&mWd);
            uint32_t slot = 4, par = 1;
#pragma unroll 1
            for (int j = 0; j < (DBG != 1 ? 14 : 0); j++) {
                const int o = owner ? cta : (cta - 112) * 7 + (j >> 1);
                mbar_wait(fempty + 8 * slot, par);
                if (lane == 0) mbar_expect_tx(ffull + 8 * slot, TILE);
                if (j < NFT) behind(TN(GU_E0) + j * TN(W_NUM) / 4);
                STAMPW(1, 176 + j);
                if (elect_one()) tma2(sb + OFF_FT + slot * TILE, (o & 1) ? &mWu : &mWg, (o >> 1) * 64, (owner ? j + 2 : j & 1) * 64, ffull + 8 * slot);
                if (++slot == NFT) { slot = 0; par ^= 1; }
            }
            if (lane < 9) mbar_expect_tx(lane < 7 ? dfull + 8 * lane : bar_x + 8 * (lane - 7), lane < 7 ? TILE : 2 * TILE);
#pragma unroll 1
            for (int j = 0; j < (DBG != 1 ? 7 : 0); j++) {
                if (j < 3) mbar_wait(fempty + 8 * j, 1);
                behind(min(TN(DL0) + j * TN(DLS) / 4, NBIG - 2));
                if (elect_one()) tma2(sb + OFF_FT + j * TILE, &mWd, (cta & 15) * 64, (cta >> 4) * 448 + j * 64, dfull + 8 * j);
            }
            prefetch_map(&mXe);
#pragma unroll 1
            for (int u = 0; u < 4; u++) {
                if (u == 2) {
                    mbar_wait(bar_dfree + 16);
                    if (elect_one()) tma5(sb + tail_c(8), &mCim, c_col(63), dt * 8, full + 8 * (NBIG + 8));
                }
                mbar_wait(bar_dfree);
                behind(u < 2 ? TN(DN_E0) + u : NBIG + NSPL);
                if (elect_one())
                    asm volatile("cp.async.bulk.tensor.5d.shared::cluster.global.mbarrier::complete_tx::bytes [%0], [%1, {%3, %6, %6, %4, %5}], [%2];"
                                 ::"r"(sb + (u < 2 ? OFF_FT : tail_c(0)) + (u & 1) * TILE), "l"(&mXe), "r"(bar_x + 4 * (u & 2)), "r"(dt * 128 + (u & 1) * 64),
                                 "r"(u & 2), "r"(chunk * 4), "r"(0) : "memory");
            }
        } else if (warp == 13) {
#pragma unroll
            for (int u = 0; u < 8; u++) {
                const int row = (u >> 2) * 4 + (lane >> 3);
                cp_async16(sb + OFF_XS + (u & 3) * 1024 + row * 128 + (((lane & 7) ^ row) << 4), (const char*)(u < 4 ? prm.w_r : prm.gate_w) + (u & 3) * 512 + lane * 16);
            }
            STAMP(57);
            const uint32_t tag = ld_relaxed(&prm.s->epoch[cta]) + 1;
            named_bar(1, 64);
            *reinterpret_cast<uint2*>(smem + OFF_EPOCH) = make_uint2(tag, tag % 3u + 1u);
            STAMPIF(tag, 58);
            asm volatile("cp.async.wait_all;" ::: "memory");
            STAMP(59);
            fence_async_smem();
            __syncwarp();
            if (lane == 0) {
                mbar_arrive(bar_epoch);
                prm.s->epoch[cta] = tag;
            }
            sleep_until(cstart + TN(T_BASE));
            {
                const uint2 st = ld_relaxed2(&prm.s->start[2 * lane]);
                const uint32_t d = st.x - cstart + 512u, age = gtime32() - st.y;
                const uint32_t m = __reduce_max_sync(0xffffffffu, d < 1024u && age < 4096u ? (d << 12) | age : 0u);
                const uint32_t late = (m & 4095u) - __reduce_min_sync(0xffffffffu, age);
                *reinterpret_cast<volatile uint32_t*>(smem + OFF_EPOCH + 8) = cstart + (m ? (m >> 12) - 512u + min(late, 256u) * TN(G_NS) / 4 : 0u);
                __syncwarp();
                if (lane == 0) mbar_arrive(bar_base);
                STAMP(60);
            }
            mbar_wait(bar_const);
            asm volatile("fence.acq_rel.gpu;" ::: "memory");
            if (lane < 4) st_relaxed2(&prm.s->armed[cta * 4 + lane], tag % 3u + 1u, 0u);
            prefetch_map(&mCre);
            prefetch_map(&mCim);
            const char* src = reinterpret_cast<const char*>(prm.s->h) + (size_t)chunk * 524288;
            uint32_t slot = 32 % NST, hpar = 0, rpar = 0;
#pragma unroll 1
            for (int i = 32; i < NBIG; i++) {
                mbar_wait(hfull + 8 * slot, hpar);
                STAMPIF(i == 32 || i == 33, 14 + (i & 1));
                rpar = check_tile<16>(sb, sb + slot * SLOT, probe, src, tag, bar_retry, rpar, TN(T_RETRY));
                if (lane == 0) mbar_expect_tx(full + 8 * i, 2 * TILE);
                STAMPIF(i == 32 || i == 33, 16 + (i & 1));
                src += 2 * TILE;
                slot = slot == NST - 1 ? 0 : slot + 1;
                hpar ^= slot == 32 % NST;
            }
        } else if (warp == 14) {
            const char* pc = (const char*)((lane & 16) ? prm.c_im : prm.c_re) + (cta * 8 + (g & 3)) * 2048 + c * 128;
            auto pf_c = [&](int k) { prefetch_l2(pc + (k >> 1) * 512 + (k & 1) * 8192); };
            {
                const char* px = (const char*)prm.x + (rid * 16 + (lane >> 1)) * 2048 + (lane & 1) * 128;
                const char* pb = (const char*)((lane & 8) ? prm.b_im : prm.b_re) + (cta * 4 + ((lane >> 1) & 3)) * 2048 + (lane & 1) * 128;
#pragma unroll 1
                for (int k = 1; k < 8; k++) {
                    sleep_until(cstart + TN(PF0) + (k - 1) * TN(PF1));
                    prefetch_l2(px + k * 256);
                    if (lane < 16) prefetch_l2(pb + k * 256);
                }
            }
            named_bar(7, 160);
            mbar_wait(bar_base);
#pragma unroll 1
            for (int k = 0; k < 4; k++) {
                behind(TN(PB_E0) + TN(PB_STEP) * k);
                prefetch_l2((const char*)((lane & 16) ? prm.b_im : prm.b_re) + (512 + cta * 4 + (g & 3)) * 2048 + c * 128 + k * 512);
            }
#pragma unroll 1
            for (int k = 0; k < TN(PC_N); k++) {
                behind(min(TN(PC_E0) + TN(PC_STEP) * k / 2, 25));
                pf_c(k);
            }
            int pk = TN(PC_N), pe = TN(PC_E1);
            auto own_part = [&](int e) {
                if (!(TDBG & 16) && !mbar_test(bar_out + 8 * e, 0)) {
                    mbar_wait(bar_out + 8 * e);
                    sleep_until(clk32() + TN(T_OWN));
                    STAMP(11);
                }
            };
            const char* src = reinterpret_cast<const char*>(prm.s->h) + (size_t)chunk * 524288;
            uint32_t slot = 32 % NST;
#pragma unroll 1
            for (int i = 32; i < NBIG; i++) {
                if (!(i & 3)) own_part((i - 32) >> 2);
                mbar_wait(empty + 8 * (i - NST));
                PSTAMP(i);
                if (elect_one()) {
                    mbar_expect_tx(hfull + 8 * slot, 2 * TILE);
                    bulk_load(sb + slot * SLOT, src, 2 * TILE, hfull + 8 * slot);
                    tma5(sb + slot * SLOT + 2 * TILE, (i & 4) ? &mCim : &mCre, c_col(i), dt * 8, full + 8 * i);
                }
                if (i == pe && pk < 8) {
                    pf_c(pk);
                    pk++; pe += TN(PC_S1);
                }
                src += 2 * TILE;
                slot = slot == NST - 1 ? 0 : slot + 1;
            }
            src -= (NBIG - 32) * 2 * TILE;
#pragma unroll
            for (int k = 0; k < 2 * NSPL - 2; k++) {
                if (k == 0 || k == 2) own_part(6 + k / 2);
                mbar_wait(empty + 8 * (NBIG - NST + k));
                if (k >= 1 && k <= 4) {
                    if (elect_one()) {
#pragma unroll
                        for (int j = 2 * k - 2; j < 2 * k; j++)
                            tma5(sb + tail_c(j), ((NBIG + j) & 4) ? &mCim : &mCre, c_col(NBIG + j), dt * 8, full + 8 * (NBIG + j));
                    }
                }
                if (k == 4) continue;
                if (k == 2) mbar_wait(bar_dfree + 8);
                if (elect_one()) {
#pragma unroll
                    for (int n = k < 5 ? 2 * k : k + 2; n < (k < 3 ? 2 * k + 2 : k == 3 ? 7 : k + 3); n++) {
                        mbar_expect_tx(hfull + 8 * (NST + n % 7), TILE);
                        bulk_load(sb + tail_h(n), src + tail_src(n), TILE, hfull + 8 * (NST + n % 7));
                    }
                }
            }
        } else {
            if (elect_one()) {
#pragma unroll
                for (int i = 0; i < NST; i++) mbar_init(full + 8 * i, 1);
                fence_mbar_init();
            }
            __syncwarp();
            asm volatile("bar.arrive 5, 160;" ::: "memory");
            asm volatile("bar.arrive 0, 448;" ::: "memory");
#pragma unroll 1
            for (int i = 0; i < NST; i++) {
                if (elect_one()) {
                    mbar_expect_tx(full + 8 * i, SLOT);
                    tma5b(sb + i * SLOT, &mB, i * 64, dt * 4, full + 8 * i);
                    tma4(sb + i * SLOT + 2 * TILE, &mX, i * 64, chunk * 64, full + 8 * i);
                }
                STAMPIF(i == 0, 1);
            }
            STAMP(2);
            named_bar(6, 160);
            uint32_t dst = sb;
#pragma unroll 1
            for (int i = NST; i < 32; i++) {
                if (i == 2 * NST) mbar_wait(bar_base);
                if (lane == 0) mbar_expect_tx(full + 8 * i, SLOT);
                mbar_wait(empty + 8 * (i - NST));
                PSTAMP(i);
                if (elect_one()) {
                    tma5b(dst, &mB, (i & 15) * 64, (i >> 4) * 64 + dt * 4, full + 8 * i);
                    tma4(dst + 2 * TILE, &mX, (i & 15) * 64, chunk * 64, full + 8 * i);
                }
                dst = dst == sb + (NST - 1) * SLOT ? sb : dst + SLOT;
            }
        }
    }
}

typedef CUresult (*EncodeFn)(CUtensorMap*, CUtensorMapDataType, cuuint32_t, void*, const cuuint64_t*, const cuuint64_t*, const cuuint32_t*,
                             const cuuint32_t*, CUtensorMapInterleave, CUtensorMapSwizzle, CUtensorMapL2promotion, CUtensorMapFloatOOBfill);

bool encode(EncodeFn fn, CUtensorMap* m, const void* ptr, int rank, const cuuint64_t* dims, const cuuint64_t* strides, const cuuint32_t* box,
            CUtensorMapL2promotion promo = CU_TENSOR_MAP_L2_PROMOTION_NONE) {
    const cuuint32_t es[5] = {1, 1, 1, 1, 1};
    return fn(m, CU_TENSOR_MAP_DATA_TYPE_BFLOAT16, rank, const_cast<void*>(ptr), dims, strides, box, es, CU_TENSOR_MAP_INTERLEAVE_NONE,
              CU_TENSOR_MAP_SWIZZLE_128B, promo, CU_TENSOR_MAP_FLOAT_OOB_FILL_NONE) == CUDA_SUCCESS;
}

}

extern "C" void kernel_launch(void* const* d_in, const int* in_sizes, int n_in, void* d_out, int out_size) {
    (void)in_sizes; (void)n_in; (void)out_size;
    Params prm;
    prm.x = (const __nv_bfloat16*)d_in[0];
    prm.lam_re = (const __nv_bfloat16*)d_in[1];
    prm.lam_im = (const __nv_bfloat16*)d_in[2];
    prm.b_re = (const __nv_bfloat16*)d_in[3];
    prm.b_im = (const __nv_bfloat16*)d_in[4];
    prm.c_re = (const __nv_bfloat16*)d_in[5];
    prm.c_im = (const __nv_bfloat16*)d_in[6];
    prm.log_dt = (const __nv_bfloat16*)d_in[7];
    prm.dskip = (const __nv_bfloat16*)d_in[8];
    prm.w_r = (const __nv_bfloat16*)d_in[10];
    prm.gate_w = (const __nv_bfloat16*)d_in[14];
    prm.out = (float*)d_out;
    cudaGetSymbolAddress((void**)&prm.s, g_scratch);
    prm.swapped = prm.b_im < prm.b_re;

    void* fnp = nullptr;
    cudaDriverEntryPointQueryResult qr;
    cudaGetDriverEntryPoint("cuTensorMapEncodeTiled", &fnp, cudaEnableDefault, &qr);
    EncodeFn fn = (EncodeFn)fnp;
    cudaFuncSetAttribute(fused_kernel, cudaFuncAttributeMaxDynamicSharedMemorySize, SMEM_BYTES);

    CUtensorMap mX, mB, mCre, mCim, mWg, mWu, mWd, mXr, mXe;
    const cuuint64_t row = 2048;
    {
        const cuuint64_t dims[4] = {1024, 2, 4, 976}, st[3] = {row, 32 * row, 2 * row};
        const cuuint32_t box[4] = {64, 2, 4, 16};
        encode(fn, &mX, prm.x, 4, dims, st, box, PROMO);
    }
    {
        const char *lo = (const char*)(prm.swapped ? prm.b_im : prm.b_re), *hi = (const char*)(prm.swapped ? prm.b_re : prm.b_im);
        const cuuint64_t dims[5] = {1024, 8, 2, 96, 2}, st[4] = {row, (cuuint64_t)(hi - lo), 8 * row, 256 * row};
        const cuuint32_t box[5] = {64, 8, 2, 4, 2};
        encode(fn, &mB, lo, 5, dims, st, box, PROMO);
    }
    {
        const cuuint64_t dims[5] = {1024, 2, 4, 2, 64}, st[4] = {row, 4 * row, 2 * row, 16 * row};
        const cuuint32_t box[5] = {64, 2, 4, 2, 8};
        encode(fn, &mCre, prm.c_re, 5, dims, st, box);
        encode(fn, &mCim, prm.c_im, 5, dims, st, box);
    }
    {
        const cuuint64_t dims[2] = {F_, D_}, st[1] = {F_ * 2}, dimsd[2] = {D_, F_}, std_[1] = {row};
        const cuuint32_t box[2] = {64, 64};
        encode(fn, &mWg, d_in[11], 2, dims, st, box);
        encode(fn, &mWu, d_in[12], 2, dims, st, box);
        encode(fn, &mWd, d_in[13], 2, dimsd, std_, box);
    }
    {
        const cuuint64_t dims[3] = {D_ - 192, S_, 4}, st[2] = {row, 128};
        const cuuint32_t box[3] = {64, 16, 4};
        encode(fn, &mXr, prm.x, 3, dims, st, box);
    }
    {
        const cuuint64_t dims[5] = {1024, 2, 4, 4, S_ / 32}, st[4] = {4 * row, row, 8 * row, 32 * row};
        const cuuint32_t box[5] = {64, 2, 4, 2, 4};
        encode(fn, &mXe, prm.x, 5, dims, st, box);
    }
    fused_kernel<<<NCTA, 512, SMEM_BYTES, cudaStreamPerThread>>>(prm, mX, mB, mCre, mCim, mWg, mWu, mWd, mXr, mXe);
}
```

```cpp
#include <cuda_runtime.h>
#include <cuda_bf16.h>
#include <cuda.h>
#include <stdint.h>

namespace {

constexpr int S_ = 2048, D_ = 1024, F_ = 3584;
constexpr int NCTA = 128;
constexpr int NSPL = 9, NBIG = 64 - NSPL, NENT = NBIG + 2 * NSPL;
constexpr int NST = 5;
constexpr int NFT = 5;
constexpr uint32_t SLOT = 32768, TILE = 8192;
constexpr uint32_t OFF_FT = NST * SLOT;
constexpr uint32_t OFF_XS = OFF_FT + NFT * TILE;
constexpr uint32_t OFF_LIST = OFF_XS + 8192;
constexpr uint32_t OFF_RED = OFF_XS + 4096;
constexpr uint32_t OFF_CONST = OFF_XS + 16384;
constexpr uint32_t OFF_M = OFF_CONST + 8192;
constexpr uint32_t OFF_HID = OFF_CONST;
constexpr uint32_t OFF_G = OFF_M + 512;
constexpr uint32_t OFF_DK = OFF_G + 256;
constexpr uint32_t OFF_FULL = OFF_DK + 256;
constexpr uint32_t OFF_EMPTY = OFF_FULL + 103 * 8;
constexpr uint32_t OFF_KEYS = OFF_EMPTY + 87 * 8;
constexpr uint32_t OFF_SEL = OFF_KEYS + 32;
constexpr uint32_t OFF_EPOCH = OFF_SEL + 32;
constexpr uint32_t OFF_PROF = OFF_EPOCH + 16;
constexpr uint32_t SMEM_BYTES = OFF_PROF + 432;
static_assert(SMEM_BYTES <= 232448, "smem");

static_assert(NBIG % NST == 0, "tail layout");
__host__ __device__ constexpr uint32_t tail_c(int j) { return j < 8 ? SLOT + j * 2 * TILE : OFF_FT + 5 * TILE; }
__host__ __device__ constexpr uint32_t tail_h(int n) { return n % 7 < 4 ? n % 7 * TILE : OFF_FT + (n % 7 - 2) * TILE; }
__host__ __device__ constexpr uint32_t tail_src(int n) { return (n % NSPL + NBIG - 32) * 2 * TILE + n / NSPL * TILE; }
__host__ __device__ constexpr int c_col(int i) { return ((i & 3) + ((i >> 1) & 12)) * 64; }

constexpr uint32_t SPIN_LIMIT = 1u << 18;

struct Scratch {
    uint2 carry[16 * 1024];
    uint2 hid[NCTA * 128];
    uint32_t y[8 * 8 * D_];
    uint32_t key[NCTA * 8];
    uint32_t gate[S_];
    uint4 part[112 * 128];
    uint2 armed[NCTA * 4];
    unsigned int epoch[256];
    uint4 start[32 * 2];
    uint4 h[16 * 32 * 1024];
};
__device__ __align__(1024) Scratch g_scratch;
#define STAMPW_(cond, w) do {} while (0)
#define GSTAMP(cond, w) do {} while (0)
#define LSTAMP(cond, w) STAMPW_(cond, w)
#define LT 0
#define STAMPW(cond, w) STAMPW_(cond, w)
#define STAMPIF(cond, i) STAMPW(cond, 96 + (i))
#define STAMP(i) STAMPW(1, 96 + (i))
#define KSTAMP(i) STAMPW((threadIdx.x & 127) == 0, i)
#define PSTAMP(i) STAMPW((i) < 56 && (i) >= 32, 160 + (i))

struct Params {
    const __nv_bfloat16 *x, *b_re, *b_im, *lam_re, *lam_im, *c_re, *c_im, *log_dt, *dskip, *w_r, *gate_w;
    float* out;
    Scratch* s;
    int swapped;
};

__device__ __forceinline__ uint32_t smem_u32(const void* p) { return (uint32_t)__cvta_generic_to_shared(p); }
__device__ __forceinline__ void mbar_init(uint32_t bar, uint32_t cnt) { asm volatile("mbarrier.init.shared::cta.b64 [%0], %1;" ::"r"(bar), "r"(cnt) : "memory"); }
__device__ __forceinline__ void mbar_expect_tx(uint32_t bar, uint32_t bytes) { asm volatile("mbarrier.arrive.expect_tx.shared::cta.b64 _, [%0], %1;" ::"r"(bar), "r"(bytes) : "memory"); }
__device__ __forceinline__ void mbar_arrive(uint32_t bar) { asm volatile("mbarrier.arrive.shared::cta.b64 _, [%0];" ::"r"(bar) : "memory"); }
__device__ __forceinline__ bool mbar_test(uint32_t bar, uint32_t parity) {
    uint32_t ok;
    asm volatile("{ .reg .pred p; mbarrier.test_wait.parity.shared::cta.b64 p, [%1], %2; selp.u32 %0, 1, 0, p; }" : "=r"(ok) : "r"(bar), "r"(parity) : "memory");
    return __all_sync(0xffffffffu, ok);
}
__device__ __forceinline__ void mbar_wait(uint32_t bar, uint32_t parity = 0) {
    asm volatile("{ .reg .pred p; .reg .u32 n; mov.u32 n, 0;\nW%=: mbarrier.try_wait.parity.shared::cta.b64 p, [%0], %1; @p bra D%=;\n"
                 "add.u32 n, n, 0x4000; setp.ne.u32 p, n, 0; @p bra W%=; trap;\nD%=: }" ::"r"(bar), "r"(parity) : "memory");
}
__device__ __forceinline__ bool elect_one() {
    uint32_t pred;
    asm volatile("{ .reg .pred P; elect.sync _|P, 0xffffffff; selp.b32 %0, 1, 0, P; }" : "=r"(pred));
    return pred;
}
__device__ __forceinline__ void named_bar(int id, int n) { asm volatile("bar.sync %0, %1;" ::"r"(id), "r"(n) : "memory"); }
__device__ __forceinline__ void fence_mbar_init() { asm volatile("fence.mbarrier_init.release.cluster;" ::: "memory"); }
__device__ __forceinline__ void fence_async_smem() { asm volatile("fence.proxy.async.shared::cta;" ::: "memory"); }

__device__ __forceinline__ void bulk_load(uint32_t dst, const void* src, uint32_t bytes, uint32_t bar) {
    asm volatile("cp.async.bulk.shared::cluster.global.mbarrier::complete_tx::bytes [%0], [%1], %2, [%3];" ::"r"(dst), "l"(src), "r"(bytes), "r"(bar) : "memory");
}
__device__ __forceinline__ void cp_async16(uint32_t dst, const void* src) { asm volatile("cp.async.cg.shared.global [%0], [%1], 16;" ::"r"(dst), "l"(src) : "memory"); }
__device__ __forceinline__ void sts128(uint32_t a, uint32_t x, uint32_t y, uint32_t z, uint32_t w) {
    asm volatile("st.shared.v4.u32 [%0], {%1,%2,%3,%4};" ::"r"(a), "r"(x), "r"(y), "r"(z), "r"(w) : "memory");
}
__device__ __forceinline__ uint2 lds64(uint32_t a) {
    uint2 v;
    asm volatile("ld.shared.v2.u32 {%0,%1}, [%2];" : "=r"(v.x), "=r"(v.y) : "r"(a) : "memory");
    return v;
}
__device__ __forceinline__ uint32_t lds32(uint32_t a) {
    uint32_t v;
    asm volatile("ld.volatile.shared.u32 %0, [%1];" : "=r"(v) : "r"(a) : "memory");
    return v;
}
__device__ __forceinline__ void stg128(void* p, uint32_t x, uint32_t y, uint32_t z, uint32_t w) {
    asm volatile("st.global.v4.u32 [%0], {%1,%2,%3,%4};" ::"l"(p), "r"(x), "r"(y), "r"(z), "r"(w) : "memory");
}
__device__ __forceinline__ void st_relaxed(void* p, uint32_t x) { asm volatile("st.relaxed.gpu.global.b32 [%0], %1;" ::"l"(p), "r"(x) : "memory"); }
__device__ __forceinline__ void st_relaxed2(void* p, uint32_t x, uint32_t y) { asm volatile("st.relaxed.gpu.global.v2.b32 [%0], {%1, %2};" ::"l"(p), "r"(x), "r"(y) : "memory"); }
__device__ __forceinline__ void st_relaxed4(void* p, uint32_t x, uint32_t y, uint32_t z, uint32_t w) {
    asm volatile("st.relaxed.gpu.global.v4.b32 [%0], {%1, %2, %3, %4};" ::"l"(p), "r"(x), "r"(y), "r"(z), "r"(w) : "memory");
}
__device__ __forceinline__ uint32_t ld_relaxed(const void* p) {
    uint32_t v;
    asm volatile("ld.relaxed.gpu.global.b32 %0, [%1];" : "=r"(v) : "l"(p) : "memory");
    return v;
}
__device__ __forceinline__ uint2 ld_relaxed2(const void* p) {
    uint2 v;
    asm volatile("ld.relaxed.gpu.global.v2.b32 {%0, %1}, [%2];" : "=r"(v.x), "=r"(v.y) : "l"(p) : "memory");
    return v;
}
__device__ __forceinline__ uint4 ld_relaxed4(const void* p) {
    uint4 v;
    asm volatile("ld.relaxed.gpu.global.v4.b32 {%0, %1, %2, %3}, [%4];" : "=r"(v.x), "=r"(v.y), "=r"(v.z), "=r"(v.w) : "l"(p) : "memory");
    return v;
}
__device__ __forceinline__ uint32_t clk32() { uint32_t c; asm volatile("mov.u32 %0, %%clock;" : "=r"(c)); return c; }
__device__ __forceinline__ uint32_t gtime32() { uint32_t c; asm volatile("mov.u32 %0, %%globaltimer_lo;" : "=r"(c)); return c; }
__device__ __forceinline__ void sched_fence(uint32_t t) { while ((int)(clk32() - t) < 0) {} }
__device__ __forceinline__ void sleep_until(uint32_t t) { while ((int)(clk32() - t) < 0) __nanosleep(40); }

__device__ __forceinline__ void tma2(uint32_t dst, const CUtensorMap* m, int c0, int c1, uint32_t bar) {
    asm volatile("{ .reg .b64 pol; createpolicy.fractional.L2::evict_first.b64 pol;\n"
                 "cp.async.bulk.tensor.2d.shared::cluster.global.mbarrier::complete_tx::bytes.L2::cache_hint [%0], [%1, {%3, %4}], [%2], pol; }"
                 ::"r"(dst), "l"(m), "r"(bar), "r"(c0), "r"(c1) : "memory");
}
__device__ __forceinline__ void tma3(uint32_t dst, const CUtensorMap* m, int c0, int c1, uint32_t bar) {
    asm volatile("cp.async.bulk.tensor.3d.shared::cluster.global.mbarrier::complete_tx::bytes [%0], [%1, {%3, %4, %5}], [%2];"
                 ::"r"(dst), "l"(m), "r"(bar), "r"(c0), "r"(c1), "r"(0) : "memory");
}
__device__ __forceinline__ void tma4(uint32_t dst, const CUtensorMap* m, int c0, int c3, uint32_t bar) {
    asm volatile("cp.async.bulk.tensor.4d.shared::cluster.global.mbarrier::complete_tx::bytes [%0], [%1, {%3, %5, %5, %4}], [%2];"
                 ::"r"(dst), "l"(m), "r"(bar), "r"(c0), "r"(c3), "r"(0) : "memory");
}
__device__ __forceinline__ void tma5(uint32_t dst, const CUtensorMap* m, int c0, int c4, uint32_t bar) {
    asm volatile("cp.async.bulk.tensor.5d.shared::cluster.global.mbarrier::complete_tx::bytes [%0], [%1, {%3, %5, %5, %5, %4}], [%2];"
                 ::"r"(dst), "l"(m), "r"(bar), "r"(c0), "r"(c4), "r"(0) : "memory");
}
__device__ __forceinline__ void tma5b(uint32_t dst, const CUtensorMap* m, int c0, int c3, uint32_t bar) {
    asm volatile("cp.async.bulk.tensor.5d.shared::cluster.global.mbarrier::complete_tx::bytes [%0], [%1, {%3, %5, %5, %4, %5}], [%2];"
                 ::"r"(dst), "l"(m), "r"(bar), "r"(c0), "r"(c3), "r"(0) : "memory");
}
__device__ __forceinline__ void prefetch_l2(const void* p) { asm volatile("prefetch.global.L2 [%0];" ::"l"(p)); }
__device__ __forceinline__ void prefetch_map(const CUtensorMap* m) { asm volatile("prefetch.tensormap [%0];" ::"l"(m)); }
__device__ __forceinline__ uint32_t uni(uint32_t v) { return __shfl_sync(0xffffffffu, v, 0); }

__device__ __forceinline__ uint32_t make_desc(uint32_t addr) { return ((addr & 0x3FFFF) >> 4) | (1u << 16); }
__device__ __forceinline__ uint32_t make_desc_h(uint32_t addr) { return ((addr & 0x3FFFF) >> 4) | (32u << 16); }
template <int H> __device__ __forceinline__ uint64_t desc64(uint32_t lo) {
    uint64_t d;
    asm volatile("mov.b64 %0, {%1, %2};" : "=l"(d) : "r"(lo), "n"(64u | ((H ? 2u : 1u) << 30)));
    return d;
}
__device__ __forceinline__ void wgmma_fence() { asm volatile("wgmma.fence.sync.aligned;" ::: "memory"); }
__device__ __forceinline__ void wgmma_commit() { asm volatile("wgmma.commit_group.sync.aligned;" ::: "memory"); }
template <int N> __device__ __forceinline__ void wgmma_wait() { asm volatile("wgmma.wait_group.sync.aligned %0;" ::"n"(N) : "memory"); }

#define R8(d, i) "+f"(d[i]), "+f"(d[i + 1]), "+f"(d[i + 2]), "+f"(d[i + 3]), "+f"(d[i + 4]), "+f"(d[i + 5]), "+f"(d[i + 6]), "+f"(d[i + 7])
#define R64(d) R8(d, 0), R8(d, 8), R8(d, 16), R8(d, 24), R8(d, 32), R8(d, 40), R8(d, 48), R8(d, 56)
template <int TA>
__device__ __forceinline__ void wgmma_n128(float (&d)[64], uint64_t da, uint64_t db, int scale_d = 1) {
    asm volatile("{ .reg .pred p; setp.ne.b32 p, %66, 0;\n"
                 "wgmma.mma_async.sync.aligned.m64n128k16.f32.bf16.bf16 "
                 "{%0,%1,%2,%3,%4,%5,%6,%7,%8,%9,%10,%11,%12,%13,%14,%15,%16,%17,%18,%19,%20,%21,%22,%23,%24,%25,%26,%27,%28,%29,%30,%31,"
                 "%32,%33,%34,%35,%36,%37,%38,%39,%40,%41,%42,%43,%44,%45,%46,%47,%48,%49,%50,%51,%52,%53,%54,%55,%56,%57,%58,%59,%60,%61,%62,%63}, "
                 "%64, %65, p, 1, 1, %67, 0; }"
                 : R64(d)
                 : "l"(da), "l"(db), "r"(scale_d), "n"(TA));
}
__device__ __forceinline__ void pin4(float (&d)[4]) { asm volatile("" : "+f"(d[0]), "+f"(d[1]), "+f"(d[2]), "+f"(d[3])::"memory"); }
__device__ __forceinline__ void pin64(float (&d)[64]) { asm volatile("" : R64(d)::"memory"); }

template <int TA>
__device__ __forceinline__ void wgmma_n8(float (&d)[4], uint64_t da, uint64_t db, int scale_d = 1) {
    asm volatile("{ .reg .pred p; setp.ne.b32 p, %7, 0;\n"
                 "wgmma.mma_async.sync.aligned.m64n8k16.f32.bf16.bf16 {%0,%1,%2,%3}, %4, %5, p, 1, 1, %6, 0; }"
                 : "+f"(d[0]), "+f"(d[1]), "+f"(d[2]), "+f"(d[3])
                 : "l"(da), "l"(db), "n"(TA), "r"(scale_d));
}

__device__ __forceinline__ float bf_lo(uint32_t u) { return __uint_as_float(u << 16); }
__device__ __forceinline__ float bf_hi(uint32_t u) { return __uint_as_float(u & 0xFFFF0000u); }
__device__ __forceinline__ float rbf(float v) { return __bfloat162float(__float2bfloat16_rn(v)); }
__device__ __forceinline__ uint32_t pack_bf(float lo, float hi) {
    uint32_t r;
    asm("cvt.rn.bf16x2.f32 %0, %1, %2;" : "=r"(r) : "f"(hi), "f"(lo));
    return r;
}
__device__ __forceinline__ uint32_t mul_bf2(uint32_t a, uint32_t b) {
    uint32_t r;
    asm("mul.rn.bf16x2 %0, %1, %2;" : "=r"(r) : "r"(a), "r"(b));
    return r;
}
__device__ __forceinline__ uint32_t fma_bf2(uint32_t a, uint32_t b, uint32_t c) {
    uint32_t r;
    asm("fma.rn.bf16x2 %0, %1, %2, %3;" : "=r"(r) : "r"(a), "r"(b), "r"(c));
    return r;
}
__device__ __forceinline__ float2 cmul(float2 a, float2 b) { return make_float2(a.x * b.x - a.y * b.y, a.x * b.y + a.y * b.x); }
__device__ __forceinline__ float2 cfma(float2 a, float2 b, float2 c) {
    return make_float2(fmaf(a.x, b.x, fmaf(-a.y, b.y, c.x)), fmaf(a.x, b.y, fmaf(a.y, b.x, c.y)));
}
__device__ __forceinline__ float sigmoidf_(float v) { return __fdividef(1.0f, 1.0f + expf(-v)); }

#define SCHED_NAMES T_W0, T_INIT, T_SMALL, T_W3, PF0, PF1, RT0, RT1, RT2, RT3, T_BASE, G_NS, GT0, GL, GQ, GT1, GS, G0, T_CP0, T_CP1, GAP0, GAP1, T_OWN, \
    T_RETRY, T_Y, RS_E, PB_E0, PB_STEP, PC_E0, PC_STEP, PC_N, PC_E1, PC_S1, GU_E0, W_NUM, GC0, GCS, GCS4, GCH, HG, DL0, DLS, DN_E0
enum { SCHED_NAMES, NTUNE };
constexpr int sched_default[NTUNE] = {
    600, 1000, 1000, 1000,
    1100, 400,
    2200, 2700, 3200, 3700,
    2500, 7,
    6300, 900, 1023,
    7300, 20,
    800, 900, 900,
    270, 300,
    1000, 200, 700,
    8,
    4, 2, 12, 4, 6, 50, 3,
    5, 8, 14, 8, 6, 11,
    43, 37, 8, 48};
template <int I> struct Sched { static constexpr int v = sched_default[I]; };
#define TN(i) (Sched<i>::v)
#define DBG 0
#define TDBG 0
#define X0 1
#define GE 8
#define PROMO CU_TENSOR_MAP_L2_PROMOTION_L2_256B

template <int TA, class H>
__device__ __forceinline__ void run_entry(uint32_t lo32, uint32_t prev, int accumulate, float (&accA)[64], float (&accB)[64], H inside) {
    const uint64_t da = desc64<TA>(lo32), db = TA ? desc64<0>(lo32 + (2 * TILE >> 4) - (31u << 16)) : da + (2 * TILE >> 4);
    wgmma_fence();
#pragma unroll
    for (int kk = 0; kk < 4; kk++) {
        wgmma_n128<TA>(accA, da + kk * (TA ? 128 : 2), db + kk * 2, kk > 0 ? 1 : accumulate);
        wgmma_n128<TA>(accB, da + 512 + kk * (TA ? 128 : 2), db + kk * 2, kk > 0 ? 1 : accumulate);
        if (kk == 1) {
            wgmma_commit();
            wgmma_wait<1>();
            if ((threadIdx.x & 31) == 0) mbar_arrive(prev);
            inside();
        }
    }
    wgmma_commit();
}
template <int TA, class H>
__device__ __forceinline__ void run_entries(uint32_t sb, int lo, int hi, int slot, float (&accA)[64], float (&accB)[64], H after) {
    const uint32_t da0 = TA ? make_desc_h(sb) : make_desc(sb), dlast = da0 + (NST - 1) * (SLOT >> 4);
    uint32_t prev = sb + OFF_FULL + 8 * 101, bar = sb + OFF_FULL + 8 * lo, lo32 = da0 + slot * (SLOT >> 4);
    int accumulate = 0;
#pragma unroll 1
    for (int i = lo; i < hi; i++) {
        mbar_wait(bar);
        KSTAMP(i);
        run_entry<TA>(lo32, prev, accumulate, accA, accB, []() {});
        prev = bar + (OFF_EMPTY - OFF_FULL);
        bar += 8;
        lo32 = lo32 == dlast ? da0 : lo32 + (SLOT >> 4);
        accumulate = 1;
        after(i);
    }
}

template <int TA>
__device__ __forceinline__ void small_tile(float (&acc)[4], uint32_t alo, uint32_t blo, bool first) {
    const uint64_t da = desc64<0>(alo), db = desc64<0>(blo);
#pragma unroll
    for (int kk = 0; kk < 4; kk++) wgmma_n8<TA>(acc, da + kk * (TA ? 128 : 2), db + kk * 2, kk > 0 || !first);
}

template <int N>
__device__ __forceinline__ uint32_t check_tile(uint32_t sb, uint32_t dst, uint32_t probe, const char* src, uint32_t par, uint32_t bar, uint32_t phase, uint32_t pause) {
    if (TDBG & 4) return phase;
#pragma unroll 1
    for (uint32_t it = 0; it < SPIN_LIMIT; it++) {
        uint32_t v[N], bad = 0;
#pragma unroll
        for (int u = 0; u < N; u++) v[u] = lds32(dst + probe + (u >> 1) * 2048 + (u & 1) * 256);
#pragma unroll
        for (int u = 0; u < N; u += 4)
            asm("{ .reg .b32 a, b; lop3.b32 a, %1, %2, %5, 0x7E; lop3.b32 b, %3, %4, %5, 0x7E; lop3.b32 %0, %0, a, b, 0xFE; }"
                : "+r"(bad) : "r"(v[u]), "r"(v[u + 1]), "r"(v[u + 2]), "r"(v[u + 3]), "r"(par));
        if (!__any_sync(0xffffffffu, bad & 1u)) return phase;
        STAMP(10);
        __nanosleep(pause);
        if (elect_one()) {
            mbar_expect_tx(bar, N * 1024);
            bulk_load(dst, src, N * 1024, bar);
        }
        mbar_wait(bar, phase);
        phase ^= 1;
    }
    __trap();
    return 0;
}

__global__ void __launch_bounds__(512, 1)
fused_kernel(const __grid_constant__ Params prm, const __grid_constant__ CUtensorMap mX, const __grid_constant__ CUtensorMap mB, const __grid_constant__ CUtensorMap mCre,
             const __grid_constant__ CUtensorMap mCim, const __grid_constant__ CUtensorMap mWg, const __grid_constant__ CUtensorMap mWu,
             const __grid_constant__ CUtensorMap mWd, const __grid_constant__ CUtensorMap mXr,
             const __grid_constant__ CUtensorMap mXe) {
    {
        const uint32_t t = threadIdx.x, b = blockIdx.x;
        const uint32_t row = t < 32 ? ((b & 60) * 2 + (b >> 6) * 4 + (b & 3)) * 16 + (t >> 1) : b * 4 + ((t >> 1) & 3);
        const char* base = (const char*)(t < 32 ? prm.x : t < 40 ? prm.b_re : prm.b_im);
        asm volatile("{ .reg .pred p; setp.lt.u32 p, %1, 48; @p prefetch.global.L2 [%0]; }" ::"l"(base + (row * 2048 + (t & 1) * 128)), "r"(t) : "memory");
    }
    extern __shared__ __align__(1024) uint8_t smem[];
    uint32_t sb;
    asm volatile("mov.u32 %0, %1;" : "=r"(sb) : "r"(smem_u32(smem)));
    const int tid = threadIdx.x, warp = __shfl_sync(0xffffffffu, tid >> 5, 0), lane = tid & 31;
    const int cta = blockIdx.x;
    const uint32_t cstart = clk32();
    const int chunk = (cta >> 2) & 15;
    const int dt = (cta >> 6) * 4 + (cta & 3);
    const int rid = chunk * 8 + dt;
    const int kslot = (rid & 3) * 32 + (rid >> 2);
    const bool owner = cta < 112;
    const uint32_t full = sb + OFF_FULL, empty = sb + OFF_EMPTY;
    const uint32_t bar_epoch = full + 8 * 73, dfull = full + 8 * 74, bar_retry = full + 8 * 81, bar_x = full + 8 * 82, ffull = full + 8 * 84,
                   hfull = full + 8 * 89, bar_base = full + 8 * 102;
    const uint32_t fempty = empty + 8 * 66, bar_order = empty + 8 * 71, bar_stored = empty + 8 * 73, bar_dfree = empty + 8 * 74,
                   bar_out = empty + 8 * 77, bar_g = empty + 8 * 85, bar_const = empty + 8 * 86;
    const int w = warp & 3, g = lane >> 2, c = lane & 3, at = tid & 127;

    const uint32_t probe = (lane >> 3) * 32 + (g & 1) * 144 + (c & 1) * 520 + (c >> 1) * 1028;

    LSTAMP(tid == 0, 96);
    GSTAMP(tid == 0, 94);
    auto init_barriers = [&](uint32_t base, uint32_t cnt, auto n) {
        if (elect_one()) {
#pragma unroll
            for (int i = 0; i < n(); i++) mbar_init(base + 8 * i, cnt);
            fence_mbar_init();
        }
        __syncwarp();
    };
    if (warp != 12) {
        if (warp == 15 && !(cta & 3) && lane < 8) st_relaxed((uint32_t*)&prm.s->start[cta >> 1] + lane, (lane & 1) ? gtime32() : cstart);
        if (warp < 12) sleep_until(cstart + (warp < 4 ? TN(T_W0) : TN(T_INIT)));
    }
    if (warp < 8) {
        if (warp < 4) init_barriers(warp == 0 ? full + 40 : warp == 3 ? full + 8 * 98 : empty + 40 * (warp - 1), (warp + 1) & 2 ? 4 : 1, []() { return 5; });
        else init_barriers(full + 80 + 176 * w, 1, []() { return 22; });
        asm volatile("setmaxnreg.inc.sync.aligned.u32 192;");
        if (warp < 4) {
            named_bar(5, 160);
            asm volatile("bar.arrive 0, 448;" ::: "memory");
            asm volatile("bar.arrive 6, 160;" ::: "memory");
            asm volatile("bar.arrive 7, 160;" ::: "memory");
        } else named_bar(0, 448);
        const int wg = warp >> 2;
        const int p = wg * 512 + dt * 32 + w * 8 + g;
        uint32_t cp = sb + OFF_CONST + 8 * (wg * 64 + w * 8 + g), cw = cp + 1024 * c, cm = sb + OFF_M + 4 * (wg * 64 + w * 8 + g);
        const int j1 = chunk - 1 - c;
        uint2* cq = &prm.s->carry[j1 * 1024 + p];
        char* hd = reinterpret_cast<char*>(prm.s->h) + (size_t)chunk * 524288 + wg * 262144 + (dt >> 1) * 16384 + ((dt & 1) * 4 + w) * 1024 + g * 64 + ((c ^ (g >> 1)) << 4);
        const bool never = uni(cstart == 0 && sb == 0);
        asm volatile("" : "+l"(cq), "+l"(hd), "+r"(cp), "+r"(cw), "+r"(cm));
        float2 a[2], a32[2], a64[2], a512[2], pw32[2], pw128[2];
        uint32_t mm[2], t2, par;
        auto constants = [&](int h) {
            if (h) { t2 = lds32(sb + OFF_EPOCH + 4); par = lds32(sb + OFF_EPOCH); }
            auto ldc = [](uint32_t a) { const uint2 v = lds64(a); return make_float2(__uint_as_float(v.x), __uint_as_float(v.y)); };
            a[h] = ldc(cp + 256 * h); a32[h] = ldc(cp + 256 * h + 1024); a64[h] = ldc(cp + 256 * h + 2048); a512[h] = ldc(cp + 256 * h + 7168);
            pw32[h] = ldc(cw + 256 * h);
            pw128[h] = ldc(cw + 256 * h + 3072);
            mm[h] = lds32(cm + 128 * h);
        };
        if (wg == 1) {
            const int pc = w * 256 + dt * 32 + lane;
            const float lr = __bfloat162float(prm.lam_re[pc]), li = __bfloat162float(prm.lam_im[pc]), ld = __bfloat162float(prm.log_dt[pc]);
            const uint32_t dk = __ldg(reinterpret_cast<const uint32_t*>(prm.dskip + dt * 128) + (at & 63));
            reinterpret_cast<uint32_t*>(smem + OFF_DK)[at & 63] = dk;
            const float dtv = rbf(expf(ld));
            const float er = expf(dtv * lr);
            float sn, cs;
            sincosf(dtv * li, &sn, &cs);
            const float ar = er * cs, ai = er * sn;
            const float nr = ar - 1.0f, ni = ai;
            const bool big = fabsf(lr) >= fabsf(li);
            const float t = (big ? li : lr) / (big ? lr : li), dn = big ? lr + li * t : lr * t + li;
            const float cr = (big ? nr + ni * t : nr * t + ni) / dn, ci = (big ? ni - nr * t : ni * t - nr) / dn;
            float2* ct = reinterpret_cast<float2*>(smem + OFF_CONST) + at;
            float2 pw = make_float2(ar, prm.swapped ? -ai : ai);
            ct[0] = pw;
            const float mx = prm.swapped ? -2.f * ci : 2.f * cr, my = prm.swapped ? 2.f * cr : -2.f * ci;
            reinterpret_cast<uint32_t*>(smem + OFF_M)[at] = pack_bf(mx, my);
#pragma unroll
            for (int i = 0; i < 5; i++) pw = cmul(pw, pw);
#pragma unroll
            for (int i = 0; i < 2; i++) {
                const float2 p2 = cmul(pw, pw);
                ct[128 + 384 * i] = pw; ct[256 + 384 * i] = p2; ct[384 + 384 * i] = cmul(p2, pw);
                pw = cmul(p2, p2);
            }
            ct[896] = pw;
            mbar_wait(bar_epoch);
            mbar_wait(empty + 8 * TN(RS_E));
            st_relaxed2(&prm.s->hid[cta * 128 + at], ~0u, ~0u);
            st_relaxed4(&prm.s->y[((at >> 4) * 8 + (cta >> 4)) * D_ + (cta & 15) * 64 + (at & 15) * 4], 0u, 0u, 0u, 0u);
            st_relaxed2(&prm.s->carry[chunk * 1024 + pc], 0u, 0u);
            __syncwarp();
            if (lane == 0) mbar_arrive(bar_const);
            STAMPIF(at == 0, 3);
            mbar_wait(bar_const);
            constants(0);
            constants(1);
            mbar_wait(bar_order);
        }

        float accA[64], accB[64];
        uint32_t t = 0;
        run_entries<0>(sb, wg * 16, wg * 16 + 15, wg, accA, accB, [&](int i) {
            if (i == GE - 2) {
                mbar_wait(bar_base);
                t = lds32(sb + OFF_EPOCH + 8) + TN(GT0);
            } else if (i == GE - 1) {
                const int late = clk32() - t - TN(GL);
                if ((uint32_t)(late + TN(GL)) >= (uint32_t)TN(GL)) sched_fence(late < 0 ? t : t + TN(GL) + 256 + (late | TN(GQ)));
            }
        });
        mbar_wait(full + 8 * (wg * 16 + 15));
        KSTAMP(wg * 16 + 15);
        if (wg == 0) {
            mbar_wait(bar_const);
            run_entry<0>(make_desc(sb), empty + 8 * 14, 1, accA, accB, [&]() { constants(0); constants(1); });
            if (lane == 0) mbar_arrive(bar_order);
        } else run_entry<0>(make_desc(sb + SLOT), empty + 8 * 30, 1, accA, accB, [&]() { if (lane == 0) mbar_arrive(bar_order + 8); });
        uint2 v[4];
#pragma unroll
        for (int m = 0; m < 4; m++) v[m] = make_uint2(t2, t2);
        wgmma_wait<0>();
        pin64(accA); pin64(accB);
        if (lane == 0) mbar_arrive(empty + 8 * (wg * 16 + 15));
        LSTAMP(at == 0, 96 + 30 + 10 * wg); GSTAMP(LT && at == 0, 193 + wg);

        auto cut = [&]() { if (never) sched_fence(cstart); };
        auto poll = [&](int h) {
#pragma unroll
            for (int m = 0; m < 4; m++)
                asm volatile("{ .reg .pred p; setp.ge.s32 p, %3, %4; @p ld.relaxed.gpu.global.v2.b32 {%0, %1}, [%2]; }"
                             : "+r"(v[m].x), "+r"(v[m].y) : "l"(cq + 256 * h - 4096 * m), "r"(j1), "r"(4 * m) : "memory");
        };
        auto valid = [&]() {
            uint32_t bad = 0;
#pragma unroll
            for (int m = 0; m < 4; m++) bad |= (v[m].x ^ t2) | (v[m].y ^ t2);
            return __all_sync(0xffffffffu, (bad & 3u) == 0);
        };
        float2 w0[2];
        uint32_t tp;
#pragma unroll
        for (int h = 0; h < 2; h++) {
            float (&acc)[64] = h ? accB : accA;
            float2 e = make_float2(acc[0], acc[2]);
#pragma unroll
            for (int s = 1; s < 32; s++) {
                const int i0 = 4 * (s >> 1) + (s & 1);
                e = cfma(a[h], e, make_float2(acc[i0], acc[i0 + 2]));
            }
            float2 y = make_float2(__shfl_up_sync(0xffffffffu, e.x, 1, 4), __shfl_up_sync(0xffffffffu, e.y, 1, 4));
            if (c >= 1) e = cfma(a32[h], y, e);
            y = make_float2(__shfl_up_sync(0xffffffffu, e.x, 2, 4), __shfl_up_sync(0xffffffffu, e.y, 2, 4));
            if (c >= 2) e = cfma(a64[h], y, e);
            if (c == 3) st_relaxed2(cq + 4096 + 256 * h, (__float_as_uint(e.x) & ~3u) | t2, (__float_as_uint(e.y) & ~3u) | t2);
            if (h == 0) tp = clk32();
            cut();
            w0[h] = make_float2(__shfl_up_sync(0xffffffffu, e.x, 1, 4), __shfl_up_sync(0xffffffffu, e.y, 1, 4));
            STAMPIF(at == 0, 31 + h + 10 * wg);
        }
        uint32_t sx[2][16], sy[2][16], mr[2][4];
        const uint32_t gap = wg ? TN(GAP1) : TN(GAP0);
#pragma unroll
        for (int h = 0; h < 2; h++) {
            const uint32_t sg = prm.swapped ? 0x80008000u : 0u;
            mr[h][0] = __byte_perm(mm[h], 0, 0x1010); mr[h][1] = __byte_perm(mm[h], 0, 0x3232);
            mr[h][2] = mr[h][1] ^ sg; mr[h][3] = mr[h][0] ^ sg ^ 0x80008000u;
        }
        auto put = [&](int e, int j) {
            uint32_t d[4];
#pragma unroll
            for (int u = 0; u < 4; u++) d[u] = fma_bf2(mr[e >> 1][2 * (e & 1)], sx[e >> 1][4 * j + u], mul_bf2(mr[e >> 1][2 * (e & 1) + 1], sy[e >> 1][4 * j + u]));
#pragma unroll
            for (int u = 0; u < 2; u++)
                asm("lop3.b32 %0, %0, %1, %2, 0xD8;" : "+r"(d[2 * (j & 1) + u]) : "r"(par), "r"((uint32_t)((w & 1) == u)));
            stg128(hd + e * 65536 + (j >> 1) * 8192 + (j & 1) * 512, d[0], d[1], d[2], d[3]);
            if (j == 3 && lane == 0) mbar_arrive(bar_out + 32 * wg + 8 * e);
        };
#pragma unroll
        for (int h = 0; h < 2; h++) {
            float (&acc)[64] = h ? accB : accA;
            uint32_t it = 0;
            if (h == 0) {
                sleep_until(tp + (wg ? TN(T_CP1) : TN(T_CP0)));
                poll(h);
            }
            while (!valid()) {
                if (++it > SPIN_LIMIT) __trap();
#pragma unroll
                for (int m = 0; m < 4; m++)
                    asm volatile("{ .reg .pred p; setp.ne.u32 p, %3, 0; @p ld.relaxed.gpu.global.v2.b32 {%0, %1}, [%2]; }"
                                 : "+r"(v[m].x), "+r"(v[m].y) : "l"(cq + 256 * h - 4096 * m), "r"(((v[m].x ^ t2) | (v[m].y ^ t2)) & 3u) : "memory");
            }
            float2 hin = make_float2(__uint_as_float(v[3].x), __uint_as_float(v[3].y));
#pragma unroll
            for (int m = 2; m >= 0; m--) hin = cfma(a512[h], hin, make_float2(__uint_as_float(v[m].x), __uint_as_float(v[m].y)));
            STAMPIF(at == 0 && it > 0 && h == 0, 39 + 10 * wg);
            if (c) hin = cmul(pw128[h], hin);
            hin.x += __shfl_xor_sync(0xffffffffu, hin.x, 1); hin.y += __shfl_xor_sync(0xffffffffu, hin.y, 1);
            hin.x += __shfl_xor_sync(0xffffffffu, hin.x, 2); hin.y += __shfl_xor_sync(0xffffffffu, hin.y, 2);
            float2 st = hin;
            if (c) st = cfma(pw32[h], hin, w0[h]);
            STAMPIF(at == 0, 33 + 3 * h + 10 * wg);
#pragma unroll
            for (int j = 0; j < 4; j++) {
#pragma unroll
                for (int u = 0; u < 4; u++) {
                    const int i0 = 16 * j + 4 * u;
                    const float2 y = cfma(a[h], st, make_float2(acc[i0], acc[i0 + 2]));
                    st = cfma(a[h], y, make_float2(acc[i0 + 1], acc[i0 + 3]));
                    sx[h][4 * j + u] = pack_bf(y.x, st.x); sy[h][4 * j + u] = pack_bf(y.y, st.y);
                }
                if (h) sleep_until(tp += gap);
                if (h == 0 && j == 1) poll(1);
                put(2 * h, j);
                cut();
            }
            STAMPIF(at == 0, 34 + 3 * h + 10 * wg);
            tp = clk32();
#pragma unroll
            for (int j = 0; j < 4; j++) {
                sleep_until(tp += gap);
                put(2 * h + 1, j);
            }
        }
        STAMPIF(at == 0, 38 + 10 * wg);

        if (wg == 1) {
            const char* src = reinterpret_cast<const char*>(prm.s->h) + (size_t)chunk * 524288;
            uint32_t rpar = 1;
#pragma unroll 1
            for (int n = w; n < 2 * NSPL; n += 4) {
                mbar_wait(empty + 8 * (NBIG - 7 + n));
                mbar_wait(hfull + 8 * (NST + n % 7), n / 7 & 1);
                const uint32_t dst = sb + tail_h(n);
                rpar = check_tile<8>(sb, dst, probe, src + tail_src(n), par, full + 8 * w, rpar, TN(T_RETRY));
                if (lane == 0) mbar_expect_tx(full + 8 * (NBIG + n), n < NSPL ? 2 * TILE : 0);
            }
        } else {
            asm volatile("setmaxnreg.inc.sync.aligned.u32 216;");
            const int tl = 64 * (w & 1) + 8 * (w >> 1) + g;
            float gf[4];
            float* op = prm.out + (size_t)(chunk * 128 + tl) * D_ + dt * 128 + 4 * c;
            const int xr = 2 * (g & 3) + (g >> 2);
            uint32_t xs = sb + (32 * (w & 1) + 8 * (w >> 1) + xr) * 128 + (((c >> 1) ^ xr) << 4) + (c & 1) * 8;
            uint32_t gs = sb + OFF_G + 2 * tl;
            asm volatile("" : "+r"(gs), "+l"(op), "+r"(xs));
            float outA[64], outB[64];
            STAMPIF(at == 0, 9);
            mbar_wait(bar_order + 8);
            STAMPIF(at == 0, 35);
            run_entries<1>(sb, 32, NBIG, 32 % NST, outA, outB, [](int) {});
            uint32_t gp[4], om[4];
            uint2 xt[4][8], dk[8];
            auto load_x = [&](int q, int j) {
#pragma unroll
                for (int r = 0; r < 2; r++) xt[2 * q + r][j] = lds64((xs ^ ((j & 3) << 5)) + (q ? tail_c(0) : OFF_FT) + (j >> 2) * TILE + r * 2048);
                if (q == 0) dk[j] = lds64(sb + OFF_DK + c * 8 + 32 * j);
            };
            auto term = [&](int q, int j) {
#pragma unroll
                for (int r = 2 * q; r < 2 * q + 2; r++) {
                    xt[r][j].x = mul_bf2(xt[r][j].x, fma_bf2(gp[r], dk[j].x, om[r]));
                    xt[r][j].y = mul_bf2(xt[r][j].y, fma_bf2(gp[r], dk[j].y, om[r]));
                }
            };
            auto store = [&](int q, int u0, int u1) {
                const float (&acc)[64] = q ? outB : outA;
#pragma unroll
                for (int u = u0; u < u1; u++) {
                    const int j = u >> 1, r = u & 1;
                    const int o = 8 * j + 2 * r;
                    const float gv = fabsf(gf[2 * q + r]);
                    const uint2 t = xt[2 * q + r][j];
                    stg128(op + (r * 32 + q * 16) * D_ + 16 * j, __float_as_uint(fmaf(gv, acc[o], bf_lo(t.x))), __float_as_uint(fmaf(gv, acc[o + 1], bf_hi(t.x))),
                           __float_as_uint(fmaf(gv, acc[o + 4], bf_lo(t.y))), __float_as_uint(fmaf(gv, acc[o + 5], bf_hi(t.y))));
                }
            };
            uint64_t dh = desc64<1>(make_desc_h(sb)), dc = desc64<0>(make_desc(sb));
#pragma unroll
            for (int n = 0; n < 2 * NSPL; n++) {
                const int j = n % NSPL;
                if (n == 0) mbar_wait(bar_g);
                if (n == X0) mbar_wait(bar_x);
                mbar_wait(full + 8 * (NBIG + n));
                KSTAMP(NBIG + n);
                asm volatile("mov.b64 %0, %0; mov.b64 %1, %1;" : "+l"(dh), "+l"(dc));
                const uint64_t da = dh + (tail_h(n) >> 4), db = dc + (tail_c(j) >> 4);
                const int xj = n - X0;
                wgmma_fence();
#pragma unroll
                for (int kk = 0; kk < 4; kk++) {
                    wgmma_n128<1>(n < NSPL ? outA : outB, da + kk * 128, db + kk * 2);
                    if (kk == 0 && n == 0) {
#pragma unroll
                        for (int r = 0; r < 4; r++) {
                            uint32_t u;
                            asm volatile("ld.shared.u16 %0, [%1];" : "=r"(u) : "r"(gs + (r & 1) * 64 + (r >> 1) * 32) : "memory");
                            gf[r] = bf_lo(u);
                        }
                    }
                    if (kk == 0 && xj >= 0 && xj < 8) load_x(0, xj);
                }
                wgmma_commit();
                if (n <= 2 * NSPL - 7) {
                    wgmma_wait<1>();
                    if (lane == 0) mbar_arrive(empty + 8 * (NBIG + n - 1));
                    if (!j) { LSTAMP(at == 0, 96 + 12 + n / NSPL); GSTAMP(LT && at == 0, 195 + n / NSPL); }
                } else if (n == 2 * NSPL - 1) {
                    mbar_wait(bar_x + 8);
                    load_x(1, 0);
                } else cut();
                if (n == 0) {
#pragma unroll
                    for (int r = 0; r < 4; r++) {
                        const bool routed = (int)__float_as_uint(gf[r]) < 0;
                        gp[r] = routed ? 0u : pack_bf(gf[r], gf[r]); om[r] = routed ? 0u : pack_bf(1.0f - gf[r], 1.0f - gf[r]);
                    }
                }
                if (xj >= 0 && xj < 8) term(0, xj);
                if (n == NSPL) pin64(outA);
                if (n >= NSPL) store(0, (j * 16 + 4) / NSPL, j == NSPL - 1 ? 16 : ((j + 1) * 16 + 4) / NSPL);
            }
            term(1, 0);
            cut();
            wgmma_wait<0>();
            pin64(outB);
            LSTAMP(at == 0, 96 + 51); GSTAMP(LT && at == 0, 197);
#pragma unroll
            for (int j = 1; j < 8; j++) load_x(1, j);
            store(1, 0, 2);
#pragma unroll
            for (int j = 1; j < 8; j++) {
                cut();
                term(1, j);
                store(1, 2 * j, 2 * j + 2);
            }
            __syncwarp();
            if (lane == 0) mbar_arrive(bar_stored);
            LSTAMP(at == 0, 96 + 52);
        }
    } else if (warp < 12) {
        asm volatile("setmaxnreg.dec.sync.aligned.u32 64;");
        init_barriers(empty + min(80 + 160 * w, 8 * 67), 4, []() { return 20; });
#pragma unroll
        for (int i = 0; i < 2; i++) sts128(sb + OFF_LIST + i * 2048 + at * 16, 0u, 0u, 0u, 0u);
        uint32_t* keys = reinterpret_cast<uint32_t*>(smem + OFF_KEYS);
        keys[4] = 0;
        named_bar(0, 448);
        if (at < 24) st_relaxed(at < 8 ? &prm.s->key[kslot * 8 + at] : &prm.s->gate[rid * 16 + at - 8], 0u);
        mbar_wait(bar_epoch);
        const uint32_t t2 = lds32(sb + OFF_EPOCH + 4);
        STAMPIF(at == 0, 20);
        float facc[4];
        const uint32_t dft = make_desc(sb + OFF_FT), dxs = make_desc(sb + OFF_XS);
#pragma unroll 1
        for (int u = 0; u < 4; u++) {
            mbar_wait(ffull + 8 * u);
            STAMPIF(at == 0, 4 + u);
            wgmma_fence();
            small_tile<0>(facc, dft + u * (TILE >> 4), dxs + u * 64, u == 0);
            wgmma_commit();
        }
        wgmma_wait<0>();
        pin4(facc);
        if (lane < 4) mbar_arrive(fempty + 8 * lane);
        auto gate_up = [&](auto rest) {
            uint32_t slot = 4, par = 0, prev = full + 8 * 101, e4 = 4 * TN(GC0);
#pragma unroll 1
            for (int j = 0; j < 14; j++) {
                if (j == 2) rest();
                STAMPW(at == 0, 75 + j);
                mbar_wait(ffull + 8 * slot, par);
                STAMPW(at == 0, 160 + j);
                mbar_wait(empty + 8 * (e4 >> 2));
                e4 += j < 8 ? TN(GCS) : TN(GCS4);
                wgmma_fence();
                small_tile<1>(facc, dft + slot * (TILE >> 4), dxs + j * 64, j == 0);
                wgmma_commit();
                wgmma_wait<1>();
                if (lane == 0) mbar_arrive(prev);
                prev = fempty + 8 * slot;
                if (++slot == NFT) { slot = 0; par ^= 1; }
            }
            wgmma_wait<0>();
            if (lane == 0) mbar_arrive(prev);
            pin4(facc);
        };
        auto help = [&]() {
            uint32_t slot = 4, par = 0, e4 = 4 * TN(GC0);
#pragma unroll 1
            for (int u = 0; u < 7; u++) {
                const uint32_t slot2 = slot == NFT - 1 ? 0 : slot + 1;
                mbar_wait(ffull + 8 * slot, par);
                par ^= slot2 == 0;
                mbar_wait(ffull + 8 * slot2, par);
                mbar_wait(empty + 8 * (e4 >> 2));
                e4 += TN(GCH);
                wgmma_fence();
                small_tile<1>(facc, dft + slot * (TILE >> 4), dxs, true);
                small_tile<1>(facc, dft + slot2 * (TILE >> 4), dxs + 64, false);
                wgmma_commit();
                wgmma_wait<0>();
                pin4(facc);
                if (lane < 2) mbar_arrive(fempty + 8 * (lane ? slot2 : slot));
                st_relaxed4(&prm.s->part[((cta - 112) * 7 + u) * 128 + at], (__float_as_uint(facc[0]) & ~3u) | t2, __float_as_uint(facc[1]),
                            __float_as_uint(facc[2]), __float_as_uint(facc[3]));
                slot = slot2 == NFT - 1 ? 0 : slot2 + 1;
                par ^= slot == 0;
            }
        };
        auto down = [&]() {
            const uint32_t dhid = make_desc(sb + OFF_HID);
#pragma unroll 1
            for (int j = 0; j < 7; j++) {
                mbar_wait(dfull + 8 * j);
                wgmma_fence();
                small_tile<1>(facc, dft + j * (TILE >> 4), dhid + j * 64, j == 0);
                wgmma_commit();
                if ((0x52 >> j) & 1) {
                    wgmma_wait<0>();
                    if (lane == 0) mbar_arrive(bar_dfree + 8 * (j / 3));
                }
            }
            wgmma_wait<0>();
            pin4(facc);
        };
        if ((c & 1) == (w >> 1)) {
            float* red = reinterpret_cast<float*>(smem + OFF_RED) + w * 32 + (c >> 1) * 16 + g;
            red[0] = (w & 1) ? facc[1] : facc[0];
            red[8] = (w & 1) ? facc[3] : facc[2];
        }
        named_bar(2, 128);
        STAMPIF(at == 0, 21);
        const uint32_t tpub = clk32();
        if (w < 2) {
            const float* red = reinterpret_cast<const float*>(smem + OFF_RED) + w * 16 + (lane & 15);
            const float v = rbf((red[0] + red[32]) + (red[64] + red[96]));
            if (w == 0) {
                uint32_t k = __float_as_uint(v);
                k = ((k ^ ((uint32_t)((int)k >> 31) | 0x80000000u)) & 0xFFFF0000u) | (t2 << 11) | (2047u - (uint32_t)(rid * 16 + (lane & 15)));
                int rank = 0;
#pragma unroll
                for (int i = 0; i < 8; i++) rank += __shfl_sync(0xffffffffu, k, (lane >> 4) * 8 + i) > k;
                rank += __shfl_xor_sync(0xffffffffu, rank, 16);
                if (rank < 8) st_relaxed(&prm.s->key[kslot * 8 + rank], k);
            } else if (lane < 16) st_relaxed(&prm.s->gate[rid * 16 + lane], __float_as_uint(rbf(sigmoidf_(v))) | t2);
            __syncwarp();
        }
        uint32_t it = 0;
        uint4 ka;
        mbar_wait(bar_base);
        sleep_until(lds32(sb + OFF_EPOCH + 8) + TN(GT1) + (cta >> 4) * TN(GS));
        sleep_until(tpub + TN(G0));
        bool bad = true;
        while (true) {
            if (bad) ka = ld_relaxed4(&prm.s->key[at * 8]);
            bad = ((ka.x ^ (t2 << 11)) & 0x1800u) != 0;
            if (!__any_sync(0xffffffffu, bad)) break;
            if (++it > SPIN_LIMIT) __trap();
            __nanosleep(TN(T_RETRY));
        }
        STAMPIF(at == 0, 22);
        STAMPIF(at == 0 && it > 0, 23);
        const uint32_t m1 = __reduce_max_sync(0xffffffffu, ka.x), m2 = __reduce_max_sync(0xffffffffu, ka.x == m1 ? ka.y : ka.x);
        if (lane == 0) keys[w] = m2;
        named_bar(2, 128);
        const uint4 th4 = *reinterpret_cast<const uint4*>(keys);
        const uint32_t th = min(min(th4.x, th4.y), min(th4.z, th4.w));
        {
            uint32_t k8[8] = {ka.x, ka.y, ka.z, ka.w, 0u, 0u, 0u, 0u};
            auto append = [&](int lo, int hi) {
                uint32_t n = 0, pos = 0;
#pragma unroll
                for (int i = lo; i < hi; i++) n += k8[i] >= th;
                asm volatile("{ .reg .pred p; setp.ne.u32 p, %2, 0; @p atom.shared.add.u32 %0, [%1], %2; }" : "+r"(pos) : "r"(sb + OFF_KEYS + 16), "r"(n) : "memory");
#pragma unroll
                for (int i = lo; i < hi; i++)
                    if (k8[i] >= th) reinterpret_cast<uint32_t*>(smem + OFF_LIST)[pos + i - lo] = k8[i];
            };
            append(0, 2);
            if (__any_sync(0xffffffffu, k8[2] >= th)) {
                if (k8[3] >= th) {
                    const uint4 kb4 = ld_relaxed4(&prm.s->key[at * 8 + 4]);
                    k8[4] = kb4.x; k8[5] = kb4.y; k8[6] = kb4.z; k8[7] = kb4.w;
                }
                append(2, 8);
            }
        }
        named_bar(2, 128);
        {
            const uint32_t* list = reinterpret_cast<const uint32_t*>(smem + OFF_LIST);
            const int n = (int)keys[4];
#pragma unroll 1
            for (int i0 = w * 32; i0 < n; i0 += 128) {
                const uint32_t k = list[i0 + lane];
                int rank = 0;
#pragma unroll 2
                for (int o = 0; o < n; o += 4) {
                    const uint4 l4 = *reinterpret_cast<const uint4*>(list + o);
                    rank += (l4.x > k) + (l4.y > k) + (l4.z > k) + (l4.w > k);
                }
                if (rank < 8) reinterpret_cast<uint32_t*>(smem + OFF_SEL)[rank] = k;
            }
        }
        named_bar(2, 128);
        STAMPIF(at == 0, 24);
        const uint32_t* sel = reinterpret_cast<const uint32_t*>(smem + OFF_SEL);
        auto gates = [&]() {
            uint32_t gv;
            it = 0;
            while (true) {
                gv = ld_relaxed(&prm.s->gate[chunk * 128 + at]);
                const uint32_t ar = ld_relaxed(&prm.s->armed[((cta >> 4) * 14 + min(lane, 13)) * 4]);
                if (__all_sync(0xffffffffu, (gv & 3u) == t2 && ar == t2)) break;
                if (++it > SPIN_LIMIT) __trap();
            }
            asm volatile("fence.acquire.gpu;" ::: "memory");
#pragma unroll
            for (int s = 0; s < 8; s++)
                if ((~sel[s] & 2047u) == (uint32_t)(chunk * 128 + at)) gv |= 0x80000000u;
            reinterpret_cast<uint16_t*>(smem + OFF_G)[at] = (uint16_t)(gv >> 16);
            __syncwarp();
            if (lane == 0) mbar_arrive(bar_g);
        };
        {
            const int tk = (at >> 3) & 7;
            const char* xt = (const char*)prm.x + (~sel[tk] & 2047u) * 2048 + (owner ? 256 : 0) + (at >> 6) * 128 + (at & 7) * 16;
#pragma unroll
            for (int i = 0; i < 7; i++) {
                if (i == 0 || owner) cp_async16(sb + OFF_XS + (2 * i + (at >> 6)) * 1024 + tk * 128 + (((at & 7) ^ tk) << 4), xt + i * 256);
                if (i == 0 || i == 6) asm volatile("cp.async.commit_group;" ::: "memory");
            }
            asm volatile("cp.async.wait_group 1;" ::: "memory");
            fence_async_smem();
            named_bar(2, 128);
            STAMPIF(at == 0, 25);
        }
        if (!owner) help();
        else {
            gate_up([&]() {
                asm volatile("cp.async.wait_all;" ::: "memory");
                fence_async_smem();
                named_bar(2, 128);
            });
            it = 0;
            while (true) {
                const uint4 v = ld_relaxed4(&prm.s->part[cta * 128 + at]);
                if (__all_sync(0xffffffffu, (v.x & 3u) == t2)) {
                    facc[0] += __uint_as_float(v.x); facc[1] += __uint_as_float(v.y); facc[2] += __uint_as_float(v.z); facc[3] += __uint_as_float(v.w);
                    break;
                }
                if (++it > SPIN_LIMIT) __trap();
                __nanosleep(TN(T_RETRY));
            }
            if (!(cta & 1)) {
#pragma unroll
                for (int u = 0; u < 4; u++) {
                    const float v = rbf(facc[u]);
                    facc[u] = __fdividef(v, 1.0f + __expf(-v));
                }
            }
            st_relaxed2(&prm.s->hid[cta * 128 + at], pack_bf(facc[0], facc[1]), pack_bf(facc[2], facc[3]));
        }
        STAMPIF(at == 0, 26);
        gates();
        uint32_t mine = __ballot_sync(0xffffffffu, lane < 8 && (int)((~sel[lane & 7] & 2047u) >> 7) == chunk), tr;
        uint2 xr, xd;
        float gr, rs;
        auto skip = [&](int n) {
#pragma unroll 1
            for (int i = 0; i < n; i++) mine &= mine - 1;
            if (mine) {
                const uint32_t key = sel[__ffs(mine) - 1], kb = key >> 16;
                tr = ~key & 2047u;
                xr = __ldg(reinterpret_cast<const uint2*>(prm.x + (size_t)tr * D_ + dt * 128) + lane);
                rs = rbf(sigmoidf_(bf_lo((kb & 0x8000u) ? (kb & 0x7FFFu) : (~kb & 0xFFFFu))));
                gr = fabsf(__bfloat162float(reinterpret_cast<const __nv_bfloat16*>(smem + OFF_G)[tr & 127]));
                xd = lds64(sb + OFF_DK + 8 * lane);
            }
        };
        mbar_wait(bar_g);
        skip(w);
        {
            mbar_wait(empty + 8 * max(TN(HG), 31));
            const uint2* hp = &prm.s->hid[(cta >> 4) * 14 * 128 + at];
            uint32_t hv[16];
            it = 0;
            while (true) {
                uint32_t top = 0;
#pragma unroll
                for (int j = 0; j < 7; j++) {
                    const uint2 hg = ld_relaxed2(hp + 256 * j), hu = ld_relaxed2(hp + 256 * j + 128);
                    top = max(top, max(hg.x, hu.x));
                    hv[2 * j] = mul_bf2(hg.x, hu.x); hv[2 * j + 1] = mul_bf2(hg.y, hu.y);
                }
                if (__all_sync(0xffffffffu, top != ~0u)) break;
                do {
                    if (++it > SPIN_LIMIT) __trap();
                } while (!__all_sync(0xffffffffu, ld_relaxed(hp + min(lane, 13) * 128 - lane) != ~0u));
            }
            STAMPIF(at == 0 && it > 0, 61);
            hv[14] = hv[15] = 0;
#pragma unroll
            for (int j = 0; j < 4; j++)
                asm volatile("stmatrix.sync.aligned.m8n8.x4.trans.shared.b16 [%0], {%1, %2, %3, %4};" ::"r"(
                                 sb + OFF_HID + (2 * j + (lane >> 4)) * 1024 + (lane & 7) * 128 + (((2 * w + ((lane >> 3) & 1)) ^ (lane & 7)) << 4)),
                             "r"(hv[4 * j]), "r"(hv[4 * j + 1]), "r"(hv[4 * j + 2]), "r"(hv[4 * j + 3]) : "memory");
        }
        fence_async_smem();
        named_bar(2, 128);
        STAMPIF(at == 0, 27);
        down();
#pragma unroll
        for (int u = 0; u < 4; u++)
            st_relaxed(&prm.s->y[((2 * c + (u & 1)) * 8 + (cta >> 4)) * D_ + (cta & 15) * 64 + w * 16 + g + 8 * (u >> 1)], (__float_as_uint(facc[u]) & ~3u) | t2);
        STAMPIF(at == 0, 28);
        sleep_until(clk32() + TN(T_Y));
        while (mine) {
            const uint32_t* yp = &prm.s->y[(__ffs(mine) - 1) * 8 * D_ + dt * 128 + 4 * lane];
            float y[4];
            it = 0;
            while (true) {
                uint32_t bad = 0;
                y[0] = y[1] = y[2] = y[3] = 0.f;
#pragma unroll
                for (int ks = 0; ks < 8; ks++) {
                    const uint4 v = ld_relaxed4(yp + ks * D_);
                    bad |= v.x ^ t2;
                    y[0] += __uint_as_float(v.x); y[1] += __uint_as_float(v.y); y[2] += __uint_as_float(v.z); y[3] += __uint_as_float(v.w);
                }
                if (__all_sync(0xffffffffu, (bad & 3u) == 0)) break;
                if (++it > SPIN_LIMIT) __trap();
            }
            STAMPIF(lane == 0 && it, 62);
#pragma unroll
            for (int u = 0; u < 4; u++) {
                const uint32_t x2 = (u & 2) ? xr.y : xr.x, d2 = mul_bf2(x2, (u & 2) ? xd.y : xd.x);
                y[u] = fmaf(gr, (u & 1) ? bf_hi(d2) : bf_lo(d2), rbf(rbf(1.0f - gr) * rbf(((u & 1) ? bf_hi(x2) : bf_lo(x2)) + rbf(rbf(y[u]) * rs))));
            }
            STAMPIF(lane == 0, 50);
            mbar_wait(bar_stored);
            asm volatile("red.global.add.v4.f32 [%0], {%1, %2, %3, %4};" ::"l"(prm.out + (size_t)tr * D_ + dt * 128 + 4 * lane), "f"(y[0]), "f"(y[1]), "f"(y[2]), "f"(y[3]) : "memory");
            skip(4);
        }
        LSTAMP(lane == 0, 96 + 29);
    } else {
        asm volatile("setmaxnreg.dec.sync.aligned.u32 40;");
        if (warp != 12) sleep_until(cstart + (warp == 13 ? TN(T_SMALL) : warp == 14 ? TN(PF0) - 250 : TN(T_W3)));
        auto behind = [&](int e) { mbar_wait(empty + 8 * e); };
        if (warp == 15) {
            prefetch_map(&mXr);
            named_bar(0, 448);
            asm volatile("bar.arrive 1, 64;" ::: "memory");
#pragma unroll 1
            for (int u = 0; u < 4; u++) {
                if (lane == 0) mbar_expect_tx(ffull + 8 * u, TILE);
                sleep_until(cstart + (u == 0 ? TN(RT0) : u == 1 ? TN(RT1) : u == 2 ? TN(RT2) : TN(RT3)));
                if (elect_one()) tma3(sb + OFF_FT + u * TILE, &mXr, u * 256, rid * 16, ffull + 8 * u);
                STAMP(53 + u);
            }
            if (sb & 1023) __trap();
            prefetch_map(&mWg);
            prefetch_map(&mWu);
            prefetch_map(&mWd);
            uint32_t slot = 4, par = 1;
#pragma unroll 1
            for (int j = 0; j < (DBG != 1 ? 14 : 0); j++) {
                const int o = owner ? cta : (cta - 112) * 7 + (j >> 1);
                mbar_wait(fempty + 8 * slot, par);
                if (lane == 0) mbar_expect_tx(ffull + 8 * slot, TILE);
                if (j < NFT) behind(TN(GU_E0) + j * TN(W_NUM) / 4);
                STAMPW(1, 176 + j);
                if (elect_one()) tma2(sb + OFF_FT + slot * TILE, (o & 1) ? &mWu : &mWg, (o >> 1) * 64, (owner ? j + 2 : j & 1) * 64, ffull + 8 * slot);
                if (++slot == NFT) { slot = 0; par ^= 1; }
            }
            if (lane < 9) mbar_expect_tx(lane < 7 ? dfull + 8 * lane : bar_x + 8 * (lane - 7), lane < 7 ? TILE : 2 * TILE);
#pragma unroll 1
            for (int j = 0; j < (DBG != 1 ? 7 : 0); j++) {
                if (j < 3) mbar_wait(fempty + 8 * j, 1);
                behind(min(TN(DL0) + j * TN(DLS) / 4, NBIG - 2));
                if (elect_one()) tma2(sb + OFF_FT + j * TILE, &mWd, (cta & 15) * 64, (cta >> 4) * 448 + j * 64, dfull + 8 * j);
            }
            prefetch_map(&mXe);
#pragma unroll 1
            for (int u = 0; u < 4; u++) {
                if (u == 2) {
                    mbar_wait(bar_dfree + 16);
                    if (elect_one()) tma5(sb + tail_c(8), &mCim, c_col(63), dt * 8, full + 8 * (NBIG + 8));
                }
                mbar_wait(bar_dfree);
                behind(u < 2 ? TN(DN_E0) + u : NBIG + NSPL);
                if (elect_one())
                    asm volatile("cp.async.bulk.tensor.5d.shared::cluster.global.mbarrier::complete_tx::bytes [%0], [%1, {%3, %6, %6, %4, %5}], [%2];"
                                 ::"r"(sb + (u < 2 ? OFF_FT : tail_c(0)) + (u & 1) * TILE), "l"(&mXe), "r"(bar_x + 4 * (u & 2)), "r"(dt * 128 + (u & 1) * 64),
                                 "r"(u & 2), "r"(chunk * 4), "r"(0) : "memory");
            }
        } else if (warp == 13) {
#pragma unroll
            for (int u = 0; u < 8; u++) {
                const int row = (u >> 2) * 4 + (lane >> 3);
                cp_async16(sb + OFF_XS + (u & 3) * 1024 + row * 128 + (((lane & 7) ^ row) << 4), (const char*)(u < 4 ? prm.w_r : prm.gate_w) + (u & 3) * 512 + lane * 16);
            }
            STAMP(57);
            const uint32_t tag = ld_relaxed(&prm.s->epoch[cta]) + 1;
            named_bar(1, 64);
            *reinterpret_cast<uint2*>(smem + OFF_EPOCH) = make_uint2(tag, tag % 3u + 1u);
            STAMPIF(tag, 58);
            asm volatile("cp.async.wait_all;" ::: "memory");
            STAMP(59);
            fence_async_smem();
            __syncwarp();
            if (lane == 0) {
                mbar_arrive(bar_epoch);
                prm.s->epoch[cta] = tag;
            }
            sleep_until(cstart + TN(T_BASE));
            {
                const uint2 st = ld_relaxed2(&prm.s->start[2 * lane]);
                const uint32_t d = st.x - cstart + 512u, age = gtime32() - st.y;
                const uint32_t m = __reduce_max_sync(0xffffffffu, d < 1024u && age < 4096u ? (d << 12) | age : 0u);
                const uint32_t late = (m & 4095u) - __reduce_min_sync(0xffffffffu, age);
                *reinterpret_cast<volatile uint32_t*>(smem + OFF_EPOCH + 8) = cstart + (m ? (m >> 12) - 512u + min(late, 256u) * TN(G_NS) / 4 : 0u);
                __syncwarp();
                if (lane == 0) mbar_arrive(bar_base);
                STAMP(60);
            }
            mbar_wait(bar_const);
            asm volatile("fence.acq_rel.gpu;" ::: "memory");
            if (lane < 4) st_relaxed2(&prm.s->armed[cta * 4 + lane], tag % 3u + 1u, 0u);
            prefetch_map(&mCre);
            prefetch_map(&mCim);
            const char* src = reinterpret_cast<const char*>(prm.s->h) + (size_t)chunk * 524288;
            uint32_t slot = 32 % NST, hpar = 0, rpar = 0;
#pragma unroll 1
            for (int i = 32; i < NBIG; i++) {
                mbar_wait(hfull + 8 * slot, hpar);
                STAMPIF(i == 32 || i == 33, 14 + (i & 1));
                rpar = check_tile<16>(sb, sb + slot * SLOT, probe, src, tag, bar_retry, rpar, TN(T_RETRY));
                if (lane == 0) mbar_expect_tx(full + 8 * i, 2 * TILE);
                STAMPIF(i == 32 || i == 33, 16 + (i & 1));
                src += 2 * TILE;
                slot = slot == NST - 1 ? 0 : slot + 1;
                hpar ^= slot == 32 % NST;
            }
        } else if (warp == 14) {
            const char* pc = (const char*)((lane & 16) ? prm.c_im : prm.c_re) + (cta * 8 + (g & 3)) * 2048 + c * 128;
            auto pf_c = [&](int k) { prefetch_l2(pc + (k >> 1) * 512 + (k & 1) * 8192); };
            {
                const char* px = (const char*)prm.x + (rid * 16 + (lane >> 1)) * 2048 + (lane & 1) * 128;
                const char* pb = (const char*)((lane & 8) ? prm.b_im : prm.b_re) + (cta * 4 + ((lane >> 1) & 3)) * 2048 + (lane & 1) * 128;
#pragma unroll 1
                for (int k = 1; k < 8; k++) {
                    sleep_until(cstart + TN(PF0) + (k - 1) * TN(PF1));
                    prefetch_l2(px + k * 256);
                    if (lane < 16) prefetch_l2(pb + k * 256);
                }
            }
            named_bar(7, 160);
            mbar_wait(bar_base);
#pragma unroll 1
            for (int k = 0; k < 4; k++) {
                behind(TN(PB_E0) + TN(PB_STEP) * k);
                prefetch_l2((const char*)((lane & 16) ? prm.b_im : prm.b_re) + (512 + cta * 4 + (g & 3)) * 2048 + c * 128 + k * 512);
            }
#pragma unroll 1
            for (int k = 0; k < TN(PC_N); k++) {
                behind(min(TN(PC_E0) + TN(PC_STEP) * k / 2, 25));
                pf_c(k);
            }
            int pk = TN(PC_N), pe = TN(PC_E1);
            auto own_part = [&](int e) {
                if (!(TDBG & 16) && !mbar_test(bar_out + 8 * e, 0)) {
                    mbar_wait(bar_out + 8 * e);
                    sleep_until(clk32() + TN(T_OWN));
                    STAMP(11);
                }
            };
            const char* src = reinterpret_cast<const char*>(prm.s->h) + (size_t)chunk * 524288;
            uint32_t slot = 32 % NST;
#pragma unroll 1
            for (int i = 32; i < NBIG; i++) {
                if (!(i & 3)) own_part((i - 32) >> 2);
                mbar_wait(empty + 8 * (i - NST));
                PSTAMP(i);
                if (elect_one()) {
                    mbar_expect_tx(hfull + 8 * slot, 2 * TILE);
                    bulk_load(sb + slot * SLOT, src, 2 * TILE, hfull + 8 * slot);
                    tma5(sb + slot * SLOT + 2 * TILE, (i & 4) ? &mCim : &mCre, c_col(i), dt * 8, full + 8 * i);
                }
                if (i == pe && pk < 8) {
                    pf_c(pk);
                    pk++; pe += TN(PC_S1);
                }
                src += 2 * TILE;
                slot = slot == NST - 1 ? 0 : slot + 1;
            }
            src -= (NBIG - 32) * 2 * TILE;
#pragma unroll
            for (int k = 0; k < 2 * NSPL - 2; k++) {
                if (k == 0 || k == 2) own_part(6 + k / 2);
                mbar_wait(empty + 8 * (NBIG - NST + k));
                if (k >= 1 && k <= 4) {
                    if (elect_one()) {
#pragma unroll
                        for (int j = 2 * k - 2; j < 2 * k; j++)
                            tma5(sb + tail_c(j), ((NBIG + j) & 4) ? &mCim : &mCre, c_col(NBIG + j), dt * 8, full + 8 * (NBIG + j));
                    }
                }
                if (k == 4) continue;
                if (k == 2) mbar_wait(bar_dfree + 8);
                if (elect_one()) {
#pragma unroll
                    for (int n = k < 5 ? 2 * k : k + 2; n < (k < 3 ? 2 * k + 2 : k == 3 ? 7 : k + 3); n++) {
                        mbar_expect_tx(hfull + 8 * (NST + n % 7), TILE);
                        bulk_load(sb + tail_h(n), src + tail_src(n), TILE, hfull + 8 * (NST + n % 7));
                    }
                }
            }
        } else {
            if (elect_one()) {
#pragma unroll
                for (int i = 0; i < NST; i++) mbar_init(full + 8 * i, 1);
                fence_mbar_init();
            }
            __syncwarp();
            asm volatile("bar.arrive 5, 160;" ::: "memory");
            asm volatile("bar.arrive 0, 448;" ::: "memory");
#pragma unroll 1
            for (int i = 0; i < NST; i++) {
                if (elect_one()) {
                    mbar_expect_tx(full + 8 * i, SLOT);
                    tma5b(sb + i * SLOT, &mB, i * 64, dt * 4, full + 8 * i);
                    tma4(sb + i * SLOT + 2 * TILE, &mX, i * 64, chunk * 64, full + 8 * i);
                }
                STAMPIF(i == 0, 1);
            }
            STAMP(2);
            named_bar(6, 160);
            uint32_t dst = sb;
#pragma unroll 1
            for (int i = NST; i < 32; i++) {
                if (i == 2 * NST) mbar_wait(bar_base);
                if (lane == 0) mbar_expect_tx(full + 8 * i, SLOT);
                mbar_wait(empty + 8 * (i - NST));
                PSTAMP(i);
                if (elect_one()) {
                    tma5b(dst, &mB, (i & 15) * 64, (i >> 4) * 64 + dt * 4, full + 8 * i);
                    tma4(dst + 2 * TILE, &mX, (i & 15) * 64, chunk * 64, full + 8 * i);
                }
                dst = dst == sb + (NST - 1) * SLOT ? sb : dst + SLOT;
            }
        }
    }
}

typedef CUresult (*EncodeFn)(CUtensorMap*, CUtensorMapDataType, cuuint32_t, void*, const cuuint64_t*, const cuuint64_t*, const cuuint32_t*,
                             const cuuint32_t*, CUtensorMapInterleave, CUtensorMapSwizzle, CUtensorMapL2promotion, CUtensorMapFloatOOBfill);

bool encode(EncodeFn fn, CUtensorMap* m, const void* ptr, int rank, const cuuint64_t* dims, const cuuint64_t* strides, const cuuint32_t* box,
            CUtensorMapL2promotion promo = CU_TENSOR_MAP_L2_PROMOTION_NONE) {
    const cuuint32_t es[5] = {1, 1, 1, 1, 1};
    return fn(m, CU_TENSOR_MAP_DATA_TYPE_BFLOAT16, rank, const_cast<void*>(ptr), dims, strides, box, es, CU_TENSOR_MAP_INTERLEAVE_NONE,
              CU_TENSOR_MAP_SWIZZLE_128B, promo, CU_TENSOR_MAP_FLOAT_OOB_FILL_NONE) == CUDA_SUCCESS;
}

}

extern "C" void kernel_launch(void* const* d_in, const int* in_sizes, int n_in, void* d_out, int out_size) {
    (void)in_sizes; (void)n_in; (void)out_size;
    Params prm;
    prm.x = (const __nv_bfloat16*)d_in[0];
    prm.lam_re = (const __nv_bfloat16*)d_in[1];
    prm.lam_im = (const __nv_bfloat16*)d_in[2];
    prm.b_re = (const __nv_bfloat16*)d_in[3];
    prm.b_im = (const __nv_bfloat16*)d_in[4];
    prm.c_re = (const __nv_bfloat16*)d_in[5];
    prm.c_im = (const __nv_bfloat16*)d_in[6];
    prm.log_dt = (const __nv_bfloat16*)d_in[7];
    prm.dskip = (const __nv_bfloat16*)d_in[8];
    prm.w_r = (const __nv_bfloat16*)d_in[10];
    prm.gate_w = (const __nv_bfloat16*)d_in[14];
    prm.out = (float*)d_out;
    cudaGetSymbolAddress((void**)&prm.s, g_scratch);
    prm.swapped = prm.b_im < prm.b_re;

    void* fnp = nullptr;
    cudaDriverEntryPointQueryResult qr;
    cudaGetDriverEntryPoint("cuTensorMapEncodeTiled", &fnp, cudaEnableDefault, &qr);
    EncodeFn fn = (EncodeFn)fnp;
    cudaFuncSetAttribute(fused_kernel, cudaFuncAttributeMaxDynamicSharedMemorySize, SMEM_BYTES);

    CUtensorMap mX, mB, mCre, mCim, mWg, mWu, mWd, mXr, mXe;
    const cuuint64_t row = 2048;
    {
        const cuuint64_t dims[4] = {1024, 2, 4, 976}, st[3] = {row, 32 * row, 2 * row};
        const cuuint32_t box[4] = {64, 2, 4, 16};
        encode(fn, &mX, prm.x, 4, dims, st, box, PROMO);
    }
    {
        const char *lo = (const char*)(prm.swapped ? prm.b_im : prm.b_re), *hi = (const char*)(prm.swapped ? prm.b_re : prm.b_im);
        const cuuint64_t dims[5] = {1024, 8, 2, 96, 2}, st[4] = {row, (cuuint64_t)(hi - lo), 8 * row, 256 * row};
        const cuuint32_t box[5] = {64, 8, 2, 4, 2};
        encode(fn, &mB, lo, 5, dims, st, box, PROMO);
    }
    {
        const cuuint64_t dims[5] = {1024, 2, 4, 2, 64}, st[4] = {row, 4 * row, 2 * row, 16 * row};
        const cuuint32_t box[5] = {64, 2, 4, 2, 8};
        encode(fn, &mCre, prm.c_re, 5, dims, st, box);
        encode(fn, &mCim, prm.c_im, 5, dims, st, box);
    }
    {
        const cuuint64_t dims[2] = {F_, D_}, st[1] = {F_ * 2}, dimsd[2] = {D_, F_}, std_[1] = {row};
        const cuuint32_t box[2] = {64, 64};
        encode(fn, &mWg, d_in[11], 2, dims, st, box);
        encode(fn, &mWu, d_in[12], 2, dims, st, box);
        encode(fn, &mWd, d_in[13], 2, dimsd, std_, box);
    }
    {
        const cuuint64_t dims[3] = {D_ - 192, S_, 4}, st[2] = {row, 128};
        const cuuint32_t box[3] = {64, 16, 4};
        encode(fn, &mXr, prm.x, 3, dims, st, box);
    }
    {
        const cuuint64_t dims[5] = {1024, 2, 4, 4, S_ / 32}, st[4] = {4 * row, row, 8 * row, 32 * row};
        const cuuint32_t box[5] = {64, 2, 4, 2, 4};
        encode(fn, &mXe, prm.x, 5, dims, st, box);
    }
    fused_kernel<<<NCTA, 512, SMEM_BYTES, cudaStreamPerThread>>>(prm, mX, mB, mCre, mCim, mWg, mWu, mWd, mXr, mXe);
}
```

```cpp
#include <cuda_runtime.h>
#include <cuda_bf16.h>
#include <cuda.h>
#include <stdint.h>

namespace {

constexpr int S_ = 2048, D_ = 1024, F_ = 3584;
constexpr int NCTA = 128;
constexpr int NSPL = 9, NBIG = 64 - NSPL, NENT = NBIG + 2 * NSPL;
constexpr int NST = 5;
constexpr int NFT = 5;
constexpr uint32_t SLOT = 32768, TILE = 8192;
constexpr uint32_t OFF_FT = NST * SLOT;
constexpr uint32_t OFF_XS = OFF_FT + NFT * TILE;
constexpr uint32_t OFF_LIST = OFF_XS + 8192;
constexpr uint32_t OFF_RED = OFF_XS + 4096;
constexpr uint32_t OFF_CONST = OFF_XS + 16384;
constexpr uint32_t OFF_M = OFF_CONST + 8192;
constexpr uint32_t OFF_HID = OFF_CONST;
constexpr uint32_t OFF_G = OFF_M + 512;
constexpr uint32_t OFF_DK = OFF_G + 256;
constexpr uint32_t OFF_FULL = OFF_DK + 256;
constexpr uint32_t OFF_EMPTY = OFF_FULL + 103 * 8;
constexpr uint32_t OFF_KEYS = OFF_EMPTY + 87 * 8;
constexpr uint32_t OFF_SEL = OFF_KEYS + 32;
constexpr uint32_t OFF_EPOCH = OFF_SEL + 32;
constexpr uint32_t OFF_PROF = OFF_EPOCH + 16;
constexpr uint32_t SMEM_BYTES = OFF_PROF + 432;
static_assert(SMEM_BYTES <= 232448, "smem");

static_assert(NBIG % NST == 0, "tail layout");
__host__ __device__ constexpr uint32_t tail_c(int j) { return j < 8 ? SLOT + j * 2 * TILE : OFF_FT + 5 * TILE; }
__host__ __device__ constexpr uint32_t tail_h(int n) { return n % 7 < 4 ? n % 7 * TILE : OFF_FT + (n % 7 - 2) * TILE; }
__host__ __device__ constexpr uint32_t tail_src(int n) { return (n % NSPL + NBIG - 32) * 2 * TILE + n / NSPL * TILE; }
__host__ __device__ constexpr int c_col(int i) { return ((i & 3) + ((i >> 1) & 12)) * 64; }

constexpr uint32_t SPIN_LIMIT = 1u << 18;

struct Scratch {
    uint2 carry[16 * 1024];
    uint2 hid[NCTA * 128];
    uint32_t y[8 * 8 * D_];
    uint32_t key[NCTA * 8];
    uint32_t gate[S_];
    uint4 part[112 * 128];
    uint2 armed[NCTA * 4];
    unsigned int epoch[256];
    uint4 start[32 * 2];
    uint4 h[16 * 32 * 1024];
};
__device__ __align__(1024) Scratch g_scratch;
#define STAMPW_(cond, w) do {} while (0)
#define GSTAMP(cond, w) do {} while (0)
#define LSTAMP(cond, w) STAMPW_(cond, w)
#define LT 0
#define STAMPW(cond, w) STAMPW_(cond, w)
#define STAMPIF(cond, i) STAMPW(cond, 96 + (i))
#define STAMP(i) STAMPW(1, 96 + (i))
#define KSTAMP(i) STAMPW((threadIdx.x & 127) == 0, i)
#define PSTAMP(i) STAMPW((i) < 56 && (i) >= 32, 160 + (i))

struct Params {
    const __nv_bfloat16 *x, *b_re, *b_im, *lam_re, *lam_im, *c_re, *c_im, *log_dt, *dskip, *w_r, *gate_w;
    float* out;
    Scratch* s;
    int swapped;
};

__device__ __forceinline__ uint32_t smem_u32(const void* p) { return (uint32_t)__cvta_generic_to_shared(p); }
__device__ __forceinline__ void mbar_init(uint32_t bar, uint32_t cnt) { asm volatile("mbarrier.init.shared::cta.b64 [%0], %1;" ::"r"(bar), "r"(cnt) : "memory"); }
__device__ __forceinline__ void mbar_expect_tx(uint32_t bar, uint32_t bytes) { asm volatile("mbarrier.arrive.expect_tx.shared::cta.b64 _, [%0], %1;" ::"r"(bar), "r"(bytes) : "memory"); }
__device__ __forceinline__ void mbar_arrive(uint32_t bar) { asm volatile("mbarrier.arrive.shared::cta.b64 _, [%0];" ::"r"(bar) : "memory"); }
__device__ __forceinline__ bool mbar_test(uint32_t bar, uint32_t parity) {
    uint32_t ok;
    asm volatile("{ .reg .pred p; mbarrier.test_wait.parity.shared::cta.b64 p, [%1], %2; selp.u32 %0, 1, 0, p; }" : "=r"(ok) : "r"(bar), "r"(parity) : "memory");
    return __all_sync(0xffffffffu, ok);
}
__device__ __forceinline__ void mbar_wait(uint32_t bar, uint32_t parity = 0) {
    asm volatile("{ .reg .pred p; .reg .u32 n; mov.u32 n, 0;\nW%=: mbarrier.try_wait.parity.shared::cta.b64 p, [%0], %1; @p bra D%=;\n"
                 "add.u32 n, n, 0x4000; setp.ne.u32 p, n, 0; @p bra W%=; trap;\nD%=: }" ::"r"(bar), "r"(parity) : "memory");
}
__device__ __forceinline__ bool elect_one() {
    uint32_t pred;
    asm volatile("{ .reg .pred P; elect.sync _|P, 0xffffffff; selp.b32 %0, 1, 0, P; }" : "=r"(pred));
    return pred;
}
__device__ __forceinline__ void named_bar(int id, int n) { asm volatile("bar.sync %0, %1;" ::"r"(id), "r"(n) : "memory"); }
__device__ __forceinline__ void fence_mbar_init() { asm volatile("fence.mbarrier_init.release.cluster;" ::: "memory"); }
__device__ __forceinline__ void fence_async_smem() { asm volatile("fence.proxy.async.shared::cta;" ::: "memory"); }

__device__ __forceinline__ void bulk_load(uint32_t dst, const void* src, uint32_t bytes, uint32_t bar) {
    asm volatile("cp.async.bulk.shared::cluster.global.mbarrier::complete_tx::bytes [%0], [%1], %2, [%3];" ::"r"(dst), "l"(src), "r"(bytes), "r"(bar) : "memory");
}
__device__ __forceinline__ void cp_async16(uint32_t dst, const void* src) { asm volatile("cp.async.cg.shared.global [%0], [%1], 16;" ::"r"(dst), "l"(src) : "memory"); }
__device__ __forceinline__ void sts128(uint32_t a, uint32_t x, uint32_t y, uint32_t z, uint32_t w) {
    asm volatile("st.shared.v4.u32 [%0], {%1,%2,%3,%4};" ::"r"(a), "r"(x), "r"(y), "r"(z), "r"(w) : "memory");
}
__device__ __forceinline__ uint2 lds64(uint32_t a) {
    uint2 v;
    asm volatile("ld.shared.v2.u32 {%0,%1}, [%2];" : "=r"(v.x), "=r"(v.y) : "r"(a) : "memory");
    return v;
}
__device__ __forceinline__ uint32_t lds32(uint32_t a) {
    uint32_t v;
    asm volatile("ld.volatile.shared.u32 %0, [%1];" : "=r"(v) : "r"(a) : "memory");
    return v;
}
__device__ __forceinline__ void stg128(void* p, uint32_t x, uint32_t y, uint32_t z, uint32_t w) {
    asm volatile("st.global.v4.u32 [%0], {%1,%2,%3,%4};" ::"l"(p), "r"(x), "r"(y), "r"(z), "r"(w) : "memory");
}
__device__ __forceinline__ void st_relaxed(void* p, uint32_t x) { asm volatile("st.relaxed.gpu.global.b32 [%0], %1;" ::"l"(p), "r"(x) : "memory"); }
__device__ __forceinline__ void st_relaxed2(void* p, uint32_t x, uint32_t y) { asm volatile("st.relaxed.gpu.global.v2.b32 [%0], {%1, %2};" ::"l"(p), "r"(x), "r"(y) : "memory"); }
__device__ __forceinline__ void st_relaxed4(void* p, uint32_t x, uint32_t y, uint32_t z, uint32_t w) {
    asm volatile("st.relaxed.gpu.global.v4.b32 [%0], {%1, %2, %3, %4};" ::"l"(p), "r"(x), "r"(y), "r"(z), "r"(w) : "memory");
}
__device__ __forceinline__ uint32_t ld_relaxed(const void* p) {
    uint32_t v;
    asm volatile("ld.relaxed.gpu.global.b32 %0, [%1];" : "=r"(v) : "l"(p) : "memory");
    return v;
}
__device__ __forceinline__ uint2 ld_relaxed2(const void* p) {
    uint2 v;
    asm volatile("ld.relaxed.gpu.global.v2.b32 {%0, %1}, [%2];" : "=r"(v.x), "=r"(v.y) : "l"(p) : "memory");
    return v;
}
__device__ __forceinline__ uint4 ld_relaxed4(const void* p) {
    uint4 v;
    asm volatile("ld.relaxed.gpu.global.v4.b32 {%0, %1, %2, %3}, [%4];" : "=r"(v.x), "=r"(v.y), "=r"(v.z), "=r"(v.w) : "l"(p) : "memory");
    return v;
}
__device__ __forceinline__ uint32_t clk32() { uint32_t c; asm volatile("mov.u32 %0, %%clock;" : "=r"(c)); return c; }
__device__ __forceinline__ uint32_t gtime32() { uint32_t c; asm volatile("mov.u32 %0, %%globaltimer_lo;" : "=r"(c)); return c; }
__device__ __forceinline__ void sched_fence(uint32_t t) { while ((int)(clk32() - t) < 0) {} }
__device__ __forceinline__ void sleep_until(uint32_t t) { while ((int)(clk32() - t) < 0) __nanosleep(40); }

__device__ __forceinline__ void tma2(uint32_t dst, const CUtensorMap* m, int c0, int c1, uint32_t bar) {
    asm volatile("{ .reg .b64 pol; createpolicy.fractional.L2::evict_first.b64 pol;\n"
                 "cp.async.bulk.tensor.2d.shared::cluster.global.mbarrier::complete_tx::bytes.L2::cache_hint [%0], [%1, {%3, %4}], [%2], pol; }"
                 ::"r"(dst), "l"(m), "r"(bar), "r"(c0), "r"(c1) : "memory");
}
__device__ __forceinline__ void tma3(uint32_t dst, const CUtensorMap* m, int c0, int c1, uint32_t bar) {
    asm volatile("cp.async.bulk.tensor.3d.shared::cluster.global.mbarrier::complete_tx::bytes [%0], [%1, {%3, %4, %5}], [%2];"
                 ::"r"(dst), "l"(m), "r"(bar), "r"(c0), "r"(c1), "r"(0) : "memory");
}
__device__ __forceinline__ void tma4(uint32_t dst, const CUtensorMap* m, int c0, int c3, uint32_t bar) {
    asm volatile("cp.async.bulk.tensor.4d.shared::cluster.global.mbarrier::complete_tx::bytes [%0], [%1, {%3, %5, %5, %4}], [%2];"
                 ::"r"(dst), "l"(m), "r"(bar), "r"(c0), "r"(c3), "r"(0) : "memory");
}
__device__ __forceinline__ void tma5(uint32_t dst, const CUtensorMap* m, int c0, int c4, uint32_t bar) {
    asm volatile("cp.async.bulk.tensor.5d.shared::cluster.global.mbarrier::complete_tx::bytes [%0], [%1, {%3, %5, %5, %5, %4}], [%2];"
                 ::"r"(dst), "l"(m), "r"(bar), "r"(c0), "r"(c4), "r"(0) : "memory");
}
__device__ __forceinline__ void tma5b(uint32_t dst, const CUtensorMap* m, int c0, int c3, uint32_t bar) {
    asm volatile("cp.async.bulk.tensor.5d.shared::cluster.global.mbarrier::complete_tx::bytes [%0], [%1, {%3, %5, %5, %4, %5}], [%2];"
                 ::"r"(dst), "l"(m), "r"(bar), "r"(c0), "r"(c3), "r"(0) : "memory");
}
__device__ __forceinline__ void prefetch_l2(const void* p) { asm volatile("prefetch.global.L2 [%0];" ::"l"(p)); }
__device__ __forceinline__ void prefetch_map(const CUtensorMap* m) { asm volatile("prefetch.tensormap [%0];" ::"l"(m)); }
__device__ __forceinline__ uint32_t uni(uint32_t v) { return __shfl_sync(0xffffffffu, v, 0); }

__device__ __forceinline__ uint32_t make_desc(uint32_t addr) { return ((addr & 0x3FFFF) >> 4) | (1u << 16); }
__device__ __forceinline__ uint32_t make_desc_h(uint32_t addr) { return ((addr & 0x3FFFF) >> 4) | (32u << 16); }
template <int H> __device__ __forceinline__ uint64_t desc64(uint32_t lo) {
    uint64_t d;
    asm volatile("mov.b64 %0, {%1, %2};" : "=l"(d) : "r"(lo), "n"(64u | ((H ? 2u : 1u) << 30)));
    return d;
}
__device__ __forceinline__ void wgmma_fence() { asm volatile("wgmma.fence.sync.aligned;" ::: "memory"); }
__device__ __forceinline__ void wgmma_commit() { asm volatile("wgmma.commit_group.sync.aligned;" ::: "memory"); }
template <int N> __device__ __forceinline__ void wgmma_wait() { asm volatile("wgmma.wait_group.sync.aligned %0;" ::"n"(N) : "memory"); }

#define R8(d, i) "+f"(d[i]), "+f"(d[i + 1]), "+f"(d[i + 2]), "+f"(d[i + 3]), "+f"(d[i + 4]), "+f"(d[i + 5]), "+f"(d[i + 6]), "+f"(d[i + 7])
#define R64(d) R8(d, 0), R8(d, 8), R8(d, 16), R8(d, 24), R8(d, 32), R8(d, 40), R8(d, 48), R8(d, 56)
template <int TA>
__device__ __forceinline__ void wgmma_n128(float (&d)[64], uint64_t da, uint64_t db, int scale_d = 1) {
    asm volatile("{ .reg .pred p; setp.ne.b32 p, %66, 0;\n"
                 "wgmma.mma_async.sync.aligned.m64n128k16.f32.bf16.bf16 "
                 "{%0,%1,%2,%3,%4,%5,%6,%7,%8,%9,%10,%11,%12,%13,%14,%15,%16,%17,%18,%19,%20,%21,%22,%23,%24,%25,%26,%27,%28,%29,%30,%31,"
                 "%32,%33,%34,%35,%36,%37,%38,%39,%40,%41,%42,%43,%44,%45,%46,%47,%48,%49,%50,%51,%52,%53,%54,%55,%56,%57,%58,%59,%60,%61,%62,%63}, "
                 "%64, %65, p, 1, 1, %67, 0; }"
                 : R64(d)
                 : "l"(da), "l"(db), "r"(scale_d), "n"(TA));
}
__device__ __forceinline__ void pin4(float (&d)[4]) { asm volatile("" : "+f"(d[0]), "+f"(d[1]), "+f"(d[2]), "+f"(d[3])::"memory"); }
__device__ __forceinline__ void pin64(float (&d)[64]) { asm volatile("" : R64(d)::"memory"); }

template <int TA>
__device__ __forceinline__ void wgmma_n8(float (&d)[4], uint64_t da, uint64_t db, int scale_d = 1) {
    asm volatile("{ .reg .pred p; setp.ne.b32 p, %7, 0;\n"
                 "wgmma.mma_async.sync.aligned.m64n8k16.f32.bf16.bf16 {%0,%1,%2,%3}, %4, %5, p, 1, 1, %6, 0; }"
                 : "+f"(d[0]), "+f"(d[1]), "+f"(d[2]), "+f"(d[3])
                 : "l"(da), "l"(db), "n"(TA), "r"(scale_d));
}

__device__ __forceinline__ float bf_lo(uint32_t u) { return __uint_as_float(u << 16); }
__device__ __forceinline__ float bf_hi(uint32_t u) { return __uint_as_float(u & 0xFFFF0000u); }
__device__ __forceinline__ float rbf(float v) { return __bfloat162float(__float2bfloat16_rn(v)); }
__device__ __forceinline__ uint32_t pack_bf(float lo, float hi) {
    uint32_t r;
    asm("cvt.rn.bf16x2.f32 %0, %1, %2;" : "=r"(r) : "f"(hi), "f"(lo));
    return r;
}
__device__ __forceinline__ uint32_t mul_bf2(uint32_t a, uint32_t b) {
    uint32_t r;
    asm("mul.rn.bf16x2 %0, %1, %2;" : "=r"(r) : "r"(a), "r"(b));
    return r;
}
__device__ __forceinline__ uint32_t fma_bf2(uint32_t a, uint32_t b, uint32_t c) {
    uint32_t r;
    asm("fma.rn.bf16x2 %0, %1, %2, %3;" : "=r"(r) : "r"(a), "r"(b), "r"(c));
    return r;
}
__device__ __forceinline__ float2 cmul(float2 a, float2 b) { return make_float2(a.x * b.x - a.y * b.y, a.x * b.y + a.y * b.x); }
__device__ __forceinline__ float2 cfma(float2 a, float2 b, float2 c) {
    return make_float2(fmaf(a.x, b.x, fmaf(-a.y, b.y, c.x)), fmaf(a.x, b.y, fmaf(a.y, b.x, c.y)));
}
__device__ __forceinline__ float sigmoidf_(float v) { return __fdividef(1.0f, 1.0f + expf(-v)); }

#define SCHED_NAMES T_W0, T_INIT, T_SMALL, T_W3, PF0, PF1, RT0, RT1, RT2, RT3, T_BASE, G_NS, GT0, GL, GQ, GT1, GS, G0, T_CP0, T_CP1, GAP0, GAP1, T_OWN, \
    T_RETRY, T_Y, RS_E, PB_E0, PB_STEP, PC_E0, PC_STEP, PC_N, PC_E1, PC_S1, GU_E0, W_NUM, GC0, GCS, GCS4, GCH, HG, DL0, DLS, DN_E0
enum { SCHED_NAMES, NTUNE };
constexpr int sched_default[NTUNE] = {
    600, 1000, 1000, 1000,
    1100, 450,
    2200, 2700, 3200, 3700,
    2500, 3,
    6100, 1100, 1023,
    7300, 20,
    800, 900, 900,
    270, 300,
    1000, 200, 700,
    8,
    4, 2, 12, 4, 6, 50, 3,
    5, 8, 14, 8, 5, 11,
    43, 37, 8, 49};
template <int I> struct Sched { static constexpr int v = sched_default[I]; };
#define TN(i) (Sched<i>::v)
#define DBG 0
#define TDBG 0
#define X0 1
#define GE 8
#define PROMO CU_TENSOR_MAP_L2_PROMOTION_L2_256B

template <int TA, class H>
__device__ __forceinline__ void run_entry(uint32_t lo32, uint32_t prev, int accumulate, float (&accA)[64], float (&accB)[64], H inside) {
    const uint64_t da = desc64<TA>(lo32), db = TA ? desc64<0>(lo32 + (2 * TILE >> 4) - (31u << 16)) : da + (2 * TILE >> 4);
    wgmma_fence();
#pragma unroll
    for (int kk = 0; kk < 4; kk++) {
        wgmma_n128<TA>(accA, da + kk * (TA ? 128 : 2), db + kk * 2, kk > 0 ? 1 : accumulate);
        wgmma_n128<TA>(accB, da + 512 + kk * (TA ? 128 : 2), db + kk * 2, kk > 0 ? 1 : accumulate);
        if (kk == 1) {
            wgmma_commit();
            wgmma_wait<1>();
            if ((threadIdx.x & 31) == 0) mbar_arrive(prev);
            inside();
        }
    }
    wgmma_commit();
}
template <int TA, class H>
__device__ __forceinline__ void run_entries(uint32_t sb, int lo, int hi, int slot, float (&accA)[64], float (&accB)[64], H after) {
    const uint32_t da0 = TA ? make_desc_h(sb) : make_desc(sb), dlast = da0 + (NST - 1) * (SLOT >> 4);
    uint32_t prev = sb + OFF_FULL + 8 * 101, bar = sb + OFF_FULL + 8 * lo, lo32 = da0 + slot * (SLOT >> 4);
    int accumulate = 0;
#pragma unroll 1
    for (int i = lo; i < hi; i++) {
        mbar_wait(bar);
        KSTAMP(i);
        run_entry<TA>(lo32, prev, accumulate, accA, accB, []() {});
        prev = bar + (OFF_EMPTY - OFF_FULL);
        bar += 8;
        lo32 = lo32 == dlast ? da0 : lo32 + (SLOT >> 4);
        accumulate = 1;
        after(i);
    }
}

template <int TA>
__device__ __forceinline__ void small_tile(float (&acc)[4], uint32_t alo, uint32_t blo, bool first) {
    const uint64_t da = desc64<0>(alo), db = desc64<0>(blo);
#pragma unroll
    for (int kk = 0; kk < 4; kk++) wgmma_n8<TA>(acc, da + kk * (TA ? 128 : 2), db + kk * 2, kk > 0 || !first);
}

template <int N>
__device__ __forceinline__ uint32_t check_tile(uint32_t sb, uint32_t dst, uint32_t probe, const char* src, uint32_t par, uint32_t bar, uint32_t phase, uint32_t pause) {
    if (TDBG & 4) return phase;
#pragma unroll 1
    for (uint32_t it = 0; it < SPIN_LIMIT; it++) {
        uint32_t v[N], bad = 0;
#pragma unroll
        for (int u = 0; u < N; u++) v[u] = lds32(dst + probe + (u >> 1) * 2048 + (u & 1) * 256);
#pragma unroll
        for (int u = 0; u < N; u += 4)
            asm("{ .reg .b32 a, b; lop3.b32 a, %1, %2, %5, 0x7E; lop3.b32 b, %3, %4, %5, 0x7E; lop3.b32 %0, %0, a, b, 0xFE; }"
                : "+r"(bad) : "r"(v[u]), "r"(v[u + 1]), "r"(v[u + 2]), "r"(v[u + 3]), "r"(par));
        if (!__any_sync(0xffffffffu, bad & 1u)) return phase;
        STAMP(10);
        __nanosleep(pause);
        if (elect_one()) {
            mbar_expect_tx(bar, N * 1024);
            bulk_load(dst, src, N * 1024, bar);
        }
        mbar_wait(bar, phase);
        phase ^= 1;
    }
    __trap();
    return 0;
}

__global__ void __launch_bounds__(512, 1)
fused_kernel(const __grid_constant__ Params prm, const __grid_constant__ CUtensorMap mX, const __grid_constant__ CUtensorMap mB, const __grid_constant__ CUtensorMap mCre,
             const __grid_constant__ CUtensorMap mCim, const __grid_constant__ CUtensorMap mWg, const __grid_constant__ CUtensorMap mWu,
             const __grid_constant__ CUtensorMap mWd, const __grid_constant__ CUtensorMap mXr,
             const __grid_constant__ CUtensorMap mXe) {
    {
        const uint32_t t = threadIdx.x, b = blockIdx.x;
        const uint32_t row = t < 32 ? ((b & 60) * 2 + (b >> 6) * 4 + (b & 3)) * 16 + (t >> 1) : b * 4 + ((t >> 1) & 3);
        const char* base = (const char*)(t < 32 ? prm.x : t < 40 ? prm.b_re : prm.b_im);
        asm volatile("{ .reg .pred p; setp.lt.u32 p, %1, 48; @p prefetch.global.L2 [%0]; }" ::"l"(base + (row * 2048 + (t & 1) * 128)), "r"(t) : "memory");
    }
    extern __shared__ __align__(1024) uint8_t smem[];
    uint32_t sb;
    asm volatile("mov.u32 %0, %1;" : "=r"(sb) : "r"(smem_u32(smem)));
    const int tid = threadIdx.x, warp = __shfl_sync(0xffffffffu, tid >> 5, 0), lane = tid & 31;
    const int cta = blockIdx.x;
    const uint32_t cstart = clk32();
    const int chunk = (cta >> 2) & 15;
    const int dt = (cta >> 6) * 4 + (cta & 3);
    const int rid = chunk * 8 + dt;
    const int kslot = (rid & 3) * 32 + (rid >> 2);
    const bool owner = cta < 112;
    const uint32_t full = sb + OFF_FULL, empty = sb + OFF_EMPTY;
    const uint32_t bar_epoch = full + 8 * 73, dfull = full + 8 * 74, bar_retry = full + 8 * 81, bar_x = full + 8 * 82, ffull = full + 8 * 84,
                   hfull = full + 8 * 89, bar_base = full + 8 * 102;
    const uint32_t fempty = empty + 8 * 66, bar_order = empty + 8 * 71, bar_stored = empty + 8 * 73, bar_dfree = empty + 8 * 74,
                   bar_out = empty + 8 * 77, bar_g = empty + 8 * 85, bar_const = empty + 8 * 86;
    const int w = warp & 3, g = lane >> 2, c = lane & 3, at = tid & 127;

    const uint32_t probe = (lane >> 3) * 32 + (g & 1) * 144 + (c & 1) * 520 + (c >> 1) * 1028;

    LSTAMP(tid == 0, 96);
    GSTAMP(tid == 0, 94);
    auto init_barriers = [&](uint32_t base, uint32_t cnt, auto n) {
        if (elect_one()) {
#pragma unroll
            for (int i = 0; i < n(); i++) mbar_init(base + 8 * i, cnt);
            fence_mbar_init();
        }
        __syncwarp();
    };
    if (warp != 12) {
        if (warp == 15 && !(cta & 3) && lane < 8) st_relaxed((uint32_t*)&prm.s->start[cta >> 1] + lane, (lane & 1) ? gtime32() : cstart);
        if (warp < 12) sleep_until(cstart + (warp < 4 ? TN(T_W0) : TN(T_INIT)));
    }
    if (warp < 8) {
        if (warp < 4) init_barriers(warp == 0 ? full + 40 : warp == 3 ? full + 8 * 98 : empty + 40 * (warp - 1), (warp + 1) & 2 ? 4 : 1, []() { return 5; });
        else init_barriers(full + 80 + 176 * w, 1, []() { return 22; });
        asm volatile("setmaxnreg.inc.sync.aligned.u32 192;");
        if (warp < 4) {
            named_bar(5, 160);
            asm volatile("bar.arrive 0, 448;" ::: "memory");
            asm volatile("bar.arrive 6, 160;" ::: "memory");
            asm volatile("bar.arrive 7, 160;" ::: "memory");
        } else named_bar(0, 448);
        const int wg = warp >> 2;
        const int p = wg * 512 + dt * 32 + w * 8 + g;
        uint32_t cp = sb + OFF_CONST + 8 * (wg * 64 + w * 8 + g), cw = cp + 1024 * c, cm = sb + OFF_M + 4 * (wg * 64 + w * 8 + g);
        const int j1 = chunk - 1 - c;
        uint2* cq = &prm.s->carry[j1 * 1024 + p];
        char* hd = reinterpret_cast<char*>(prm.s->h) + (size_t)chunk * 524288 + wg * 262144 + (dt >> 1) * 16384 + ((dt & 1) * 4 + w) * 1024 + g * 64 + ((c ^ (g >> 1)) << 4);
        const bool never = uni(cstart == 0 && sb == 0);
        asm volatile("" : "+l"(cq), "+l"(hd), "+r"(cp), "+r"(cw), "+r"(cm));
        float2 a[2], a32[2], a64[2], a512[2], pw32[2], pw128[2];
        uint32_t mm[2], t2, par;
        auto constants = [&](int h) {
            if (h) { t2 = lds32(sb + OFF_EPOCH + 4); par = lds32(sb + OFF_EPOCH); }
            auto ldc = [](uint32_t a) { const uint2 v = lds64(a); return make_float2(__uint_as_float(v.x), __uint_as_float(v.y)); };
            a[h] = ldc(cp + 256 * h); a32[h] = ldc(cp + 256 * h + 1024); a64[h] = ldc(cp + 256 * h + 2048); a512[h] = ldc(cp + 256 * h + 7168);
            pw32[h] = ldc(cw + 256 * h);
            pw128[h] = ldc(cw + 256 * h + 3072);
            mm[h] = lds32(cm + 128 * h);
        };
        if (wg == 1) {
            const int pc = w * 256 + dt * 32 + lane;
            const float lr = __bfloat162float(prm.lam_re[pc]), li = __bfloat162float(prm.lam_im[pc]), ld = __bfloat162float(prm.log_dt[pc]);
            const uint32_t dk = __ldg(reinterpret_cast<const uint32_t*>(prm.dskip + dt * 128) + (at & 63));
            reinterpret_cast<uint32_t*>(smem + OFF_DK)[at & 63] = dk;
            const float dtv = rbf(expf(ld));
            const float er = expf(dtv * lr);
            float sn, cs;
            sincosf(dtv * li, &sn, &cs);
            const float ar = er * cs, ai = er * sn;
            const float nr = ar - 1.0f, ni = ai;
            const bool big = fabsf(lr) >= fabsf(li);
            const float t = (big ? li : lr) / (big ? lr : li), dn = big ? lr + li * t : lr * t + li;
            const float cr = (big ? nr + ni * t : nr * t + ni) / dn, ci = (big ? ni - nr * t : ni * t - nr) / dn;
            float2* ct = reinterpret_cast<float2*>(smem + OFF_CONST) + at;
            float2 pw = make_float2(ar, prm.swapped ? -ai : ai);
            ct[0] = pw;
            const float mx = prm.swapped ? -2.f * ci : 2.f * cr, my = prm.swapped ? 2.f * cr : -2.f * ci;
            reinterpret_cast<uint32_t*>(smem + OFF_M)[at] = pack_bf(mx, my);
#pragma unroll
            for (int i = 0; i < 5; i++) pw = cmul(pw, pw);
#pragma unroll
            for (int i = 0; i < 2; i++) {
                const float2 p2 = cmul(pw, pw);
                ct[128 + 384 * i] = pw; ct[256 + 384 * i] = p2; ct[384 + 384 * i] = cmul(p2, pw);
                pw = cmul(p2, p2);
            }
            ct[896] = pw;
            mbar_wait(bar_epoch);
            mbar_wait(empty + 8 * TN(RS_E));
            st_relaxed2(&prm.s->hid[cta * 128 + at], ~0u, ~0u);
            st_relaxed4(&prm.s->y[((at >> 4) * 8 + (cta >> 4)) * D_ + (cta & 15) * 64 + (at & 15) * 4], 0u, 0u, 0u, 0u);
            st_relaxed2(&prm.s->carry[chunk * 1024 + pc], 0u, 0u);
            __syncwarp();
            if (lane == 0) mbar_arrive(bar_const);
            STAMPIF(at == 0, 3);
            mbar_wait(bar_const);
            constants(0);
            constants(1);
            mbar_wait(bar_order);
        }

        float accA[64], accB[64];
        uint32_t t = 0;
        run_entries<0>(sb, wg * 16, wg * 16 + 15, wg, accA, accB, [&](int i) {
            if (i == GE - 2) {
                mbar_wait(bar_base);
                t = lds32(sb + OFF_EPOCH + 8) + TN(GT0);
            } else if (i == GE - 1) {
                const int late = clk32() - t - TN(GL);
                if ((uint32_t)(late + TN(GL)) >= (uint32_t)TN(GL)) sched_fence(late < 0 ? t : t + TN(GL) + 256 + (late | TN(GQ)));
            }
        });
        mbar_wait(full + 8 * (wg * 16 + 15));
        KSTAMP(wg * 16 + 15);
        if (wg == 0) {
            mbar_wait(bar_const);
            run_entry<0>(make_desc(sb), empty + 8 * 14, 1, accA, accB, [&]() { constants(0); constants(1); });
            if (lane == 0) mbar_arrive(bar_order);
        } else run_entry<0>(make_desc(sb + SLOT), empty + 8 * 30, 1, accA, accB, [&]() { if (lane == 0) mbar_arrive(bar_order + 8); });
        uint2 v[4];
#pragma unroll
        for (int m = 0; m < 4; m++) v[m] = make_uint2(t2, t2);
        wgmma_wait<0>();
        pin64(accA); pin64(accB);
        if (lane == 0) mbar_arrive(empty + 8 * (wg * 16 + 15));
        LSTAMP(at == 0, 96 + 30 + 10 * wg); GSTAMP(LT && at == 0, 193 + wg);

        auto cut = [&]() { if (never) sched_fence(cstart); };
        auto poll = [&](int h) {
#pragma unroll
            for (int m = 0; m < 4; m++)
                asm volatile("{ .reg .pred p; setp.ge.s32 p, %3, %4; @p ld.relaxed.gpu.global.v2.b32 {%0, %1}, [%2]; }"
                             : "+r"(v[m].x), "+r"(v[m].y) : "l"(cq + 256 * h - 4096 * m), "r"(j1), "r"(4 * m) : "memory");
        };
        auto valid = [&]() {
            uint32_t bad = 0;
#pragma unroll
            for (int m = 0; m < 4; m++) bad |= (v[m].x ^ t2) | (v[m].y ^ t2);
            return __all_sync(0xffffffffu, (bad & 3u) == 0);
        };
        float2 w0[2];
        uint32_t tp;
#pragma unroll
        for (int h = 0; h < 2; h++) {
            float (&acc)[64] = h ? accB : accA;
            float2 e = make_float2(acc[0], acc[2]);
#pragma unroll
            for (int s = 1; s < 32; s++) {
                const int i0 = 4 * (s >> 1) + (s & 1);
                e = cfma(a[h], e, make_float2(acc[i0], acc[i0 + 2]));
            }
            float2 y = make_float2(__shfl_up_sync(0xffffffffu, e.x, 1, 4), __shfl_up_sync(0xffffffffu, e.y, 1, 4));
            if (c >= 1) e = cfma(a32[h], y, e);
            y = make_float2(__shfl_up_sync(0xffffffffu, e.x, 2, 4), __shfl_up_sync(0xffffffffu, e.y, 2, 4));
            if (c >= 2) e = cfma(a64[h], y, e);
            if (c == 3) st_relaxed2(cq + 4096 + 256 * h, (__float_as_uint(e.x) & ~3u) | t2, (__float_as_uint(e.y) & ~3u) | t2);
            if (h == 0) tp = clk32();
            cut();
            w0[h] = make_float2(__shfl_up_sync(0xffffffffu, e.x, 1, 4), __shfl_up_sync(0xffffffffu, e.y, 1, 4));
            STAMPIF(at == 0, 31 + h + 10 * wg);
        }
        uint32_t sx[2][16], sy[2][16], mr[2][4];
        const uint32_t gap = wg ? TN(GAP1) : TN(GAP0);
#pragma unroll
        for (int h = 0; h < 2; h++) {
            const uint32_t sg = prm.swapped ? 0x80008000u : 0u;
            mr[h][0] = __byte_perm(mm[h], 0, 0x1010); mr[h][1] = __byte_perm(mm[h], 0, 0x3232);
            mr[h][2] = mr[h][1] ^ sg; mr[h][3] = mr[h][0] ^ sg ^ 0x80008000u;
        }
        auto put = [&](int e, int j) {
            uint32_t d[4];
#pragma unroll
            for (int u = 0; u < 4; u++) d[u] = fma_bf2(mr[e >> 1][2 * (e & 1)], sx[e >> 1][4 * j + u], mul_bf2(mr[e >> 1][2 * (e & 1) + 1], sy[e >> 1][4 * j + u]));
#pragma unroll
            for (int u = 0; u < 2; u++)
                asm("lop3.b32 %0, %0, %1, %2, 0xD8;" : "+r"(d[2 * (j & 1) + u]) : "r"(par), "r"((uint32_t)((w & 1) == u)));
            stg128(hd + e * 65536 + (j >> 1) * 8192 + (j & 1) * 512, d[0], d[1], d[2], d[3]);
            if (j == 3 && lane == 0) mbar_arrive(bar_out + 32 * wg + 8 * e);
        };
#pragma unroll
        for (int h = 0; h < 2; h++) {
            float (&acc)[64] = h ? accB : accA;
            uint32_t it = 0;
            if (h == 0) {
                sleep_until(tp + (wg ? TN(T_CP1) : TN(T_CP0)));
                poll(h);
            }
            while (!valid()) {
                if (++it > SPIN_LIMIT) __trap();
#pragma unroll
                for (int m = 0; m < 4; m++)
                    asm volatile("{ .reg .pred p; setp.ne.u32 p, %3, 0; @p ld.relaxed.gpu.global.v2.b32 {%0, %1}, [%2]; }"
                                 : "+r"(v[m].x), "+r"(v[m].y) : "l"(cq + 256 * h - 4096 * m), "r"(((v[m].x ^ t2) | (v[m].y ^ t2)) & 3u) : "memory");
            }
            float2 hin = make_float2(__uint_as_float(v[3].x), __uint_as_float(v[3].y));
#pragma unroll
            for (int m = 2; m >= 0; m--) hin = cfma(a512[h], hin, make_float2(__uint_as_float(v[m].x), __uint_as_float(v[m].y)));
            STAMPIF(at == 0 && it > 0 && h == 0, 39 + 10 * wg);
            if (c) hin = cmul(pw128[h], hin);
            hin.x += __shfl_xor_sync(0xffffffffu, hin.x, 1); hin.y += __shfl_xor_sync(0xffffffffu, hin.y, 1);
            hin.x += __shfl_xor_sync(0xffffffffu, hin.x, 2); hin.y += __shfl_xor_sync(0xffffffffu, hin.y, 2);
            float2 st = hin;
            if (c) st = cfma(pw32[h], hin, w0[h]);
            STAMPIF(at == 0, 33 + 3 * h + 10 * wg);
#pragma unroll
            for (int j = 0; j < 4; j++) {
#pragma unroll
                for (int u = 0; u < 4; u++) {
                    const int i0 = 16 * j + 4 * u;
                    const float2 y = cfma(a[h], st, make_float2(acc[i0], acc[i0 + 2]));
                    st = cfma(a[h], y, make_float2(acc[i0 + 1], acc[i0 + 3]));
                    sx[h][4 * j + u] = pack_bf(y.x, st.x); sy[h][4 * j + u] = pack_bf(y.y, st.y);
                }
                if (h) sleep_until(tp += gap);
                if (h == 0 && j == 1) poll(1);
                put(2 * h, j);
                cut();
            }
            STAMPIF(at == 0, 34 + 3 * h + 10 * wg);
            tp = clk32();
#pragma unroll
            for (int j = 0; j < 4; j++) {
                sleep_until(tp += gap);
                put(2 * h + 1, j);
            }
        }
        STAMPIF(at == 0, 38 + 10 * wg);

        if (wg == 1) {
            const char* src = reinterpret_cast<const char*>(prm.s->h) + (size_t)chunk * 524288;
            uint32_t rpar = 1;
#pragma unroll 1
            for (int n = w; n < 2 * NSPL; n += 4) {
                mbar_wait(empty + 8 * (NBIG - 7 + n));
                mbar_wait(hfull + 8 * (NST + n % 7), n / 7 & 1);
                const uint32_t dst = sb + tail_h(n);
                rpar = check_tile<8>(sb, dst, probe, src + tail_src(n), par, full + 8 * w, rpar, TN(T_RETRY));
                if (lane == 0) mbar_expect_tx(full + 8 * (NBIG + n), n < NSPL ? 2 * TILE : 0);
            }
        } else {
            asm volatile("setmaxnreg.inc.sync.aligned.u32 216;");
            const int tl = 64 * (w & 1) + 8 * (w >> 1) + g;
            float gf[4];
            float* op = prm.out + (size_t)(chunk * 128 + tl) * D_ + dt * 128 + 4 * c;
            const int xr = 2 * (g & 3) + (g >> 2);
            uint32_t xs = sb + (32 * (w & 1) + 8 * (w >> 1) + xr) * 128 + (((c >> 1) ^ xr) << 4) + (c & 1) * 8;
            uint32_t gs = sb + OFF_G + 2 * tl;
            asm volatile("" : "+r"(gs), "+l"(op), "+r"(xs));
            float outA[64], outB[64];
            STAMPIF(at == 0, 9);
            mbar_wait(bar_order + 8);
            STAMPIF(at == 0, 35);
            run_entries<1>(sb, 32, NBIG, 32 % NST, outA, outB, [](int) {});
            uint32_t gp[4], om[4];
            uint2 xt[4][8], dk[8];
            auto load_x = [&](int q, int j) {
#pragma unroll
                for (int r = 0; r < 2; r++) xt[2 * q + r][j] = lds64((xs ^ ((j & 3) << 5)) + (q ? tail_c(0) : OFF_FT) + (j >> 2) * TILE + r * 2048);
                if (q == 0) dk[j] = lds64(sb + OFF_DK + c * 8 + 32 * j);
            };
            auto term = [&](int q, int j) {
#pragma unroll
                for (int r = 2 * q; r < 2 * q + 2; r++) {
                    xt[r][j].x = mul_bf2(xt[r][j].x, fma_bf2(gp[r], dk[j].x, om[r]));
                    xt[r][j].y = mul_bf2(xt[r][j].y, fma_bf2(gp[r], dk[j].y, om[r]));
                }
            };
            auto store = [&](int q, int u0, int u1) {
                const float (&acc)[64] = q ? outB : outA;
#pragma unroll
                for (int u = u0; u < u1; u++) {
                    const int j = u >> 1, r = u & 1;
                    const int o = 8 * j + 2 * r;
                    const float gv = fabsf(gf[2 * q + r]);
                    const uint2 t = xt[2 * q + r][j];
                    stg128(op + (r * 32 + q * 16) * D_ + 16 * j, __float_as_uint(fmaf(gv, acc[o], bf_lo(t.x))), __float_as_uint(fmaf(gv, acc[o + 1], bf_hi(t.x))),
                           __float_as_uint(fmaf(gv, acc[o + 4], bf_lo(t.y))), __float_as_uint(fmaf(gv, acc[o + 5], bf_hi(t.y))));
                }
            };
            uint64_t dh = desc64<1>(make_desc_h(sb)), dc = desc64<0>(make_desc(sb));
#pragma unroll
            for (int n = 0; n < 2 * NSPL; n++) {
                const int j = n % NSPL;
                if (n == 0) mbar_wait(bar_g);
                if (n == X0) mbar_wait(bar_x);
                mbar_wait(full + 8 * (NBIG + n));
                KSTAMP(NBIG + n);
                asm volatile("mov.b64 %0, %0; mov.b64 %1, %1;" : "+l"(dh), "+l"(dc));
                const uint64_t da = dh + (tail_h(n) >> 4), db = dc + (tail_c(j) >> 4);
                const int xj = n - X0;
                wgmma_fence();
#pragma unroll
                for (int kk = 0; kk < 4; kk++) {
                    wgmma_n128<1>(n < NSPL ? outA : outB, da + kk * 128, db + kk * 2);
                    if (kk == 0 && n == 0) {
#pragma unroll
                        for (int r = 0; r < 4; r++) {
                            uint32_t u;
                            asm volatile("ld.shared.u16 %0, [%1];" : "=r"(u) : "r"(gs + (r & 1) * 64 + (r >> 1) * 32) : "memory");
                            gf[r] = bf_lo(u);
                        }
                    }
                    if (kk == 0 && xj >= 0 && xj < 8) load_x(0, xj);
                }
                wgmma_commit();
                if (n <= 2 * NSPL - 7) {
                    wgmma_wait<1>();
                    if (lane == 0) mbar_arrive(empty + 8 * (NBIG + n - 1));
                    if (!j) { LSTAMP(at == 0, 96 + 12 + n / NSPL); GSTAMP(LT && at == 0, 195 + n / NSPL); }
                } else if (n == 2 * NSPL - 1) {
                    mbar_wait(bar_x + 8);
                    load_x(1, 0);
                } else cut();
                if (n == 0) {
#pragma unroll
                    for (int r = 0; r < 4; r++) {
                        const bool routed = (int)__float_as_uint(gf[r]) < 0;
                        gp[r] = routed ? 0u : pack_bf(gf[r], gf[r]); om[r] = routed ? 0u : pack_bf(1.0f - gf[r], 1.0f - gf[r]);
                    }
                }
                if (xj >= 0 && xj < 8) term(0, xj);
                if (n == NSPL) pin64(outA);
                if (n >= NSPL) store(0, (j * 16 + 4) / NSPL, j == NSPL - 1 ? 16 : ((j + 1) * 16 + 4) / NSPL);
            }
            term(1, 0);
            cut();
            wgmma_wait<0>();
            pin64(outB);
            LSTAMP(at == 0, 96 + 51); GSTAMP(LT && at == 0, 197);
#pragma unroll
            for (int j = 1; j < 8; j++) load_x(1, j);
            store(1, 0, 2);
#pragma unroll
            for (int j = 1; j < 8; j++) {
                cut();
                term(1, j);
                store(1, 2 * j, 2 * j + 2);
            }
            __syncwarp();
            if (lane == 0) mbar_arrive(bar_stored);
            LSTAMP(at == 0, 96 + 52);
        }
    } else if (warp < 12) {
        asm volatile("setmaxnreg.dec.sync.aligned.u32 64;");
        init_barriers(empty + min(80 + 160 * w, 8 * 67), 4, []() { return 20; });
#pragma unroll
        for (int i = 0; i < 2; i++) sts128(sb + OFF_LIST + i * 2048 + at * 16, 0u, 0u, 0u, 0u);
        uint32_t* keys = reinterpret_cast<uint32_t*>(smem + OFF_KEYS);
        keys[4] = 0;
        named_bar(0, 448);
        if (at < 24) st_relaxed(at < 8 ? &prm.s->key[kslot * 8 + at] : &prm.s->gate[rid * 16 + at - 8], 0u);
        mbar_wait(bar_epoch);
        const uint32_t t2 = lds32(sb + OFF_EPOCH + 4);
        STAMPIF(at == 0, 20);
        float facc[4];
        const uint32_t dft = make_desc(sb + OFF_FT), dxs = make_desc(sb + OFF_XS);
#pragma unroll 1
        for (int u = 0; u < 4; u++) {
            mbar_wait(ffull + 8 * u);
            STAMPIF(at == 0, 4 + u);
            wgmma_fence();
            small_tile<0>(facc, dft + u * (TILE >> 4), dxs + u * 64, u == 0);
            wgmma_commit();
        }
        wgmma_wait<0>();
        pin4(facc);
        if (lane < 4) mbar_arrive(fempty + 8 * lane);
        auto gate_up = [&](auto rest) {
            uint32_t slot = 4, par = 0, prev = full + 8 * 101, e4 = 4 * TN(GC0);
#pragma unroll 1
            for (int j = 0; j < 14; j++) {
                if (j == 2) rest();
                STAMPW(at == 0, 75 + j);
                mbar_wait(ffull + 8 * slot, par);
                STAMPW(at == 0, 160 + j);
                mbar_wait(empty + 8 * (e4 >> 2));
                e4 += j < 8 ? TN(GCS) : TN(GCS4);
                wgmma_fence();
                small_tile<1>(facc, dft + slot * (TILE >> 4), dxs + j * 64, j == 0);
                wgmma_commit();
                wgmma_wait<1>();
                if (lane == 0) mbar_arrive(prev);
                prev = fempty + 8 * slot;
                if (++slot == NFT) { slot = 0; par ^= 1; }
            }
            wgmma_wait<0>();
            if (lane == 0) mbar_arrive(prev);
            pin4(facc);
        };
        auto help = [&]() {
            uint32_t slot = 4, par = 0, e4 = 4 * TN(GC0);
#pragma unroll 1
            for (int u = 0; u < 7; u++) {
                const uint32_t slot2 = slot == NFT - 1 ? 0 : slot + 1;
                mbar_wait(ffull + 8 * slot, par);
                par ^= slot2 == 0;
                mbar_wait(ffull + 8 * slot2, par);
                mbar_wait(empty + 8 * (e4 >> 2));
                e4 += TN(GCH);
                wgmma_fence();
                small_tile<1>(facc, dft + slot * (TILE >> 4), dxs, true);
                small_tile<1>(facc, dft + slot2 * (TILE >> 4), dxs + 64, false);
                wgmma_commit();
                wgmma_wait<0>();
                pin4(facc);
                if (lane < 2) mbar_arrive(fempty + 8 * (lane ? slot2 : slot));
                st_relaxed4(&prm.s->part[((cta - 112) * 7 + u) * 128 + at], (__float_as_uint(facc[0]) & ~3u) | t2, __float_as_uint(facc[1]),
                            __float_as_uint(facc[2]), __float_as_uint(facc[3]));
                slot = slot2 == NFT - 1 ? 0 : slot2 + 1;
                par ^= slot == 0;
            }
        };
        auto down = [&]() {
            const uint32_t dhid = make_desc(sb + OFF_HID);
#pragma unroll 1
            for (int j = 0; j < 7; j++) {
                mbar_wait(dfull + 8 * j);
                wgmma_fence();
                small_tile<1>(facc, dft + j * (TILE >> 4), dhid + j * 64, j == 0);
                wgmma_commit();
                if ((0x52 >> j) & 1) {
                    wgmma_wait<0>();
                    if (lane == 0) mbar_arrive(bar_dfree + 8 * (j / 3));
                }
            }
            wgmma_wait<0>();
            pin4(facc);
        };
        if ((c & 1) == (w >> 1)) {
            float* red = reinterpret_cast<float*>(smem + OFF_RED) + w * 32 + (c >> 1) * 16 + g;
            red[0] = (w & 1) ? facc[1] : facc[0];
            red[8] = (w & 1) ? facc[3] : facc[2];
        }
        named_bar(2, 128);
        STAMPIF(at == 0, 21);
        const uint32_t tpub = clk32();
        if (w < 2) {
            const float* red = reinterpret_cast<const float*>(smem + OFF_RED) + w * 16 + (lane & 15);
            const float v = rbf((red[0] + red[32]) + (red[64] + red[96]));
            if (w == 0) {
                uint32_t k = __float_as_uint(v);
                k = ((k ^ ((uint32_t)((int)k >> 31) | 0x80000000u)) & 0xFFFF0000u) | (t2 << 11) | (2047u - (uint32_t)(rid * 16 + (lane & 15)));
                int rank = 0;
#pragma unroll
                for (int i = 0; i < 8; i++) rank += __shfl_sync(0xffffffffu, k, (lane >> 4) * 8 + i) > k;
                rank += __shfl_xor_sync(0xffffffffu, rank, 16);
                if (rank < 8) st_relaxed(&prm.s->key[kslot * 8 + rank], k);
            } else if (lane < 16) st_relaxed(&prm.s->gate[rid * 16 + lane], __float_as_uint(rbf(sigmoidf_(v))) | t2);
            __syncwarp();
        }
        uint32_t it = 0;
        uint4 ka;
        mbar_wait(bar_base);
        sleep_until(lds32(sb + OFF_EPOCH + 8) + TN(GT1) + (cta >> 4) * TN(GS));
        sleep_until(tpub + TN(G0));
        bool bad = true;
        while (true) {
            if (bad) ka = ld_relaxed4(&prm.s->key[at * 8]);
            bad = ((ka.x ^ (t2 << 11)) & 0x1800u) != 0;
            if (!__any_sync(0xffffffffu, bad)) break;
            if (++it > SPIN_LIMIT) __trap();
            __nanosleep(TN(T_RETRY));
        }
        STAMPIF(at == 0, 22);
        STAMPIF(at == 0 && it > 0, 23);
        const uint32_t m1 = __reduce_max_sync(0xffffffffu, ka.x), m2 = __reduce_max_sync(0xffffffffu, ka.x == m1 ? ka.y : ka.x);
        if (lane == 0) keys[w] = m2;
        named_bar(2, 128);
        const uint4 th4 = *reinterpret_cast<const uint4*>(keys);
        const uint32_t th = min(min(th4.x, th4.y), min(th4.z, th4.w));
        {
            uint32_t k8[8] = {ka.x, ka.y, ka.z, ka.w, 0u, 0u, 0u, 0u};
            auto append = [&](int lo, int hi) {
                uint32_t n = 0, pos = 0;
#pragma unroll
                for (int i = lo; i < hi; i++) n += k8[i] >= th;
                asm volatile("{ .reg .pred p; setp.ne.u32 p, %2, 0; @p atom.shared.add.u32 %0, [%1], %2; }" : "+r"(pos) : "r"(sb + OFF_KEYS + 16), "r"(n) : "memory");
#pragma unroll
                for (int i = lo; i < hi; i++)
                    if (k8[i] >= th) reinterpret_cast<uint32_t*>(smem + OFF_LIST)[pos + i - lo] = k8[i];
            };
            append(0, 2);
            if (__any_sync(0xffffffffu, k8[2] >= th)) {
                if (k8[3] >= th) {
                    const uint4 kb4 = ld_relaxed4(&prm.s->key[at * 8 + 4]);
                    k8[4] = kb4.x; k8[5] = kb4.y; k8[6] = kb4.z; k8[7] = kb4.w;
                }
                append(2, 8);
            }
        }
        named_bar(2, 128);
        {
            const uint32_t* list = reinterpret_cast<const uint32_t*>(smem + OFF_LIST);
            const int n = (int)keys[4];
#pragma unroll 1
            for (int i0 = w * 32; i0 < n; i0 += 128) {
                const uint32_t k = list[i0 + lane];
                int rank = 0;
#pragma unroll 2
                for (int o = 0; o < n; o += 4) {
                    const uint4 l4 = *reinterpret_cast<const uint4*>(list + o);
                    rank += (l4.x > k) + (l4.y > k) + (l4.z > k) + (l4.w > k);
                }
                if (rank < 8) reinterpret_cast<uint32_t*>(smem + OFF_SEL)[rank] = k;
            }
        }
        named_bar(2, 128);
        STAMPIF(at == 0, 24);
        const uint32_t* sel = reinterpret_cast<const uint32_t*>(smem + OFF_SEL);
        auto gates = [&]() {
            uint32_t gv;
            it = 0;
            while (true) {
                gv = ld_relaxed(&prm.s->gate[chunk * 128 + at]);
                const uint32_t ar = ld_relaxed(&prm.s->armed[((cta >> 4) * 14 + min(lane, 13)) * 4]);
                if (__all_sync(0xffffffffu, (gv & 3u) == t2 && ar == t2)) break;
                if (++it > SPIN_LIMIT) __trap();
            }
            asm volatile("fence.acquire.gpu;" ::: "memory");
#pragma unroll
            for (int s = 0; s < 8; s++)
                if ((~sel[s] & 2047u) == (uint32_t)(chunk * 128 + at)) gv |= 0x80000000u;
            reinterpret_cast<uint16_t*>(smem + OFF_G)[at] = (uint16_t)(gv >> 16);
            __syncwarp();
            if (lane == 0) mbar_arrive(bar_g);
        };
        {
            const int tk = (at >> 3) & 7;
            const char* xt = (const char*)prm.x + (~sel[tk] & 2047u) * 2048 + (owner ? 256 : 0) + (at >> 6) * 128 + (at & 7) * 16;
#pragma unroll
            for (int i = 0; i < 7; i++) {
                if (i == 0 || owner) cp_async16(sb + OFF_XS + (2 * i + (at >> 6)) * 1024 + tk * 128 + (((at & 7) ^ tk) << 4), xt + i * 256);
                if (i == 0 || i == 6) asm volatile("cp.async.commit_group;" ::: "memory");
            }
            asm volatile("cp.async.wait_group 1;" ::: "memory");
            fence_async_smem();
            named_bar(2, 128);
            STAMPIF(at == 0, 25);
        }
        if (!owner) help();
        else {
            gate_up([&]() {
                asm volatile("cp.async.wait_all;" ::: "memory");
                fence_async_smem();
                named_bar(2, 128);
            });
            it = 0;
            while (true) {
                const uint4 v = ld_relaxed4(&prm.s->part[cta * 128 + at]);
                if (__all_sync(0xffffffffu, (v.x & 3u) == t2)) {
                    facc[0] += __uint_as_float(v.x); facc[1] += __uint_as_float(v.y); facc[2] += __uint_as_float(v.z); facc[3] += __uint_as_float(v.w);
                    break;
                }
                if (++it > SPIN_LIMIT) __trap();
                __nanosleep(TN(T_RETRY));
            }
            if (!(cta & 1)) {
#pragma unroll
                for (int u = 0; u < 4; u++) {
                    const float v = rbf(facc[u]);
                    facc[u] = __fdividef(v, 1.0f + __expf(-v));
                }
            }
            st_relaxed2(&prm.s->hid[cta * 128 + at], pack_bf(facc[0], facc[1]), pack_bf(facc[2], facc[3]));
        }
        STAMPIF(at == 0, 26);
        gates();
        uint32_t mine = __ballot_sync(0xffffffffu, lane < 8 && (int)((~sel[lane & 7] & 2047u) >> 7) == chunk), tr;
        uint2 xr, xd;
        float gr, rs;
        auto skip = [&](int n) {
#pragma unroll 1
            for (int i = 0; i < n; i++) mine &= mine - 1;
            if (mine) {
                const uint32_t key = sel[__ffs(mine) - 1], kb = key >> 16;
                tr = ~key & 2047u;
                xr = __ldg(reinterpret_cast<const uint2*>(prm.x + (size_t)tr * D_ + dt * 128) + lane);
                rs = rbf(sigmoidf_(bf_lo((kb & 0x8000u) ? (kb & 0x7FFFu) : (~kb & 0xFFFFu))));
                gr = fabsf(__bfloat162float(reinterpret_cast<const __nv_bfloat16*>(smem + OFF_G)[tr & 127]));
                xd = lds64(sb + OFF_DK + 8 * lane);
            }
        };
        mbar_wait(bar_g);
        skip(w);
        {
            mbar_wait(empty + 8 * max(TN(HG), 31));
            const uint2* hp = &prm.s->hid[(cta >> 4) * 14 * 128 + at];
            uint32_t hv[16];
            it = 0;
            while (true) {
                uint32_t top = 0;
#pragma unroll
                for (int j = 0; j < 7; j++) {
                    const uint2 hg = ld_relaxed2(hp + 256 * j), hu = ld_relaxed2(hp + 256 * j + 128);
                    top = max(top, max(hg.x, hu.x));
                    hv[2 * j] = mul_bf2(hg.x, hu.x); hv[2 * j + 1] = mul_bf2(hg.y, hu.y);
                }
                if (__all_sync(0xffffffffu, top != ~0u)) break;
                do {
                    if (++it > SPIN_LIMIT) __trap();
                } while (!__all_sync(0xffffffffu, ld_relaxed(hp + min(lane, 13) * 128 - lane) != ~0u));
            }
            STAMPIF(at == 0 && it > 0, 61);
            hv[14] = hv[15] = 0;
#pragma unroll
            for (int j = 0; j < 4; j++)
                asm volatile("stmatrix.sync.aligned.m8n8.x4.trans.shared.b16 [%0], {%1, %2, %3, %4};" ::"r"(
                                 sb + OFF_HID + (2 * j + (lane >> 4)) * 1024 + (lane & 7) * 128 + (((2 * w + ((lane >> 3) & 1)) ^ (lane & 7)) << 4)),
                             "r"(hv[4 * j]), "r"(hv[4 * j + 1]), "r"(hv[4 * j + 2]), "r"(hv[4 * j + 3]) : "memory");
        }
        fence_async_smem();
        named_bar(2, 128);
        STAMPIF(at == 0, 27);
        down();
#pragma unroll
        for (int u = 0; u < 4; u++)
            st_relaxed(&prm.s->y[((2 * c + (u & 1)) * 8 + (cta >> 4)) * D_ + (cta & 15) * 64 + w * 16 + g + 8 * (u >> 1)], (__float_as_uint(facc[u]) & ~3u) | t2);
        STAMPIF(at == 0, 28);
        sleep_until(clk32() + TN(T_Y));
        while (mine) {
            const uint32_t* yp = &prm.s->y[(__ffs(mine) - 1) * 8 * D_ + dt * 128 + 4 * lane];
            float y[4];
            it = 0;
            while (true) {
                uint32_t bad = 0;
                y[0] = y[1] = y[2] = y[3] = 0.f;
#pragma unroll
                for (int ks = 0; ks < 8; ks++) {
                    const uint4 v = ld_relaxed4(yp + ks * D_);
                    bad |= v.x ^ t2;
                    y[0] += __uint_as_float(v.x); y[1] += __uint_as_float(v.y); y[2] += __uint_as_float(v.z); y[3] += __uint_as_float(v.w);
                }
                if (__all_sync(0xffffffffu, (bad & 3u) == 0)) break;
                if (++it > SPIN_LIMIT) __trap();
            }
            STAMPIF(lane == 0 && it, 62);
#pragma unroll
            for (int u = 0; u < 4; u++) {
                const uint32_t x2 = (u & 2) ? xr.y : xr.x, d2 = mul_bf2(x2, (u & 2) ? xd.y : xd.x);
                y[u] = fmaf(gr, (u & 1) ? bf_hi(d2) : bf_lo(d2), rbf(rbf(1.0f - gr) * rbf(((u & 1) ? bf_hi(x2) : bf_lo(x2)) + rbf(rbf(y[u]) * rs))));
            }
            STAMPIF(lane == 0, 50);
            mbar_wait(bar_stored);
            asm volatile("red.global.add.v4.f32 [%0], {%1, %2, %3, %4};" ::"l"(prm.out + (size_t)tr * D_ + dt * 128 + 4 * lane), "f"(y[0]), "f"(y[1]), "f"(y[2]), "f"(y[3]) : "memory");
            skip(4);
        }
        LSTAMP(lane == 0, 96 + 29);
    } else {
        asm volatile("setmaxnreg.dec.sync.aligned.u32 40;");
        if (warp != 12) sleep_until(cstart + (warp == 13 ? TN(T_SMALL) : warp == 14 ? TN(PF0) - 250 : TN(T_W3)));
        auto behind = [&](int e) { mbar_wait(empty + 8 * e); };
        if (warp == 15) {
            prefetch_map(&mXr);
            named_bar(0, 448);
            asm volatile("bar.arrive 1, 64;" ::: "memory");
#pragma unroll 1
            for (int u = 0; u < 4; u++) {
                if (lane == 0) mbar_expect_tx(ffull + 8 * u, TILE);
                sleep_until(cstart + (u == 0 ? TN(RT0) : u == 1 ? TN(RT1) : u == 2 ? TN(RT2) : TN(RT3)));
                if (elect_one()) tma3(sb + OFF_FT + u * TILE, &mXr, u * 256, rid * 16, ffull + 8 * u);
                STAMP(53 + u);
            }
            if (sb & 1023) __trap();
            prefetch_map(&mWg);
            prefetch_map(&mWu);
            prefetch_map(&mWd);
            uint32_t slot = 4, par = 1;
#pragma unroll 1
            for (int j = 0; j < (DBG != 1 ? 14 : 0); j++) {
                const int o = owner ? cta : (cta - 112) * 7 + (j >> 1);
                mbar_wait(fempty + 8 * slot, par);
                if (lane == 0) mbar_expect_tx(ffull + 8 * slot, TILE);
                if (j < NFT) behind(TN(GU_E0) + j * TN(W_NUM) / 4);
                STAMPW(1, 176 + j);
                if (elect_one()) tma2(sb + OFF_FT + slot * TILE, (o & 1) ? &mWu : &mWg, (o >> 1) * 64, (owner ? j + 2 : j & 1) * 64, ffull + 8 * slot);
                if (++slot == NFT) { slot = 0; par ^= 1; }
            }
            if (lane < 9) mbar_expect_tx(lane < 7 ? dfull + 8 * lane : bar_x + 8 * (lane - 7), lane < 7 ? TILE : 2 * TILE);
#pragma unroll 1
            for (int j = 0; j < (DBG != 1 ? 7 : 0); j++) {
                if (j < 3) mbar_wait(fempty + 8 * j, 1);
                behind(min(TN(DL0) + j * TN(DLS) / 4, NBIG - 2));
                if (elect_one()) tma2(sb + OFF_FT + j * TILE, &mWd, (cta & 15) * 64, (cta >> 4) * 448 + j * 64, dfull + 8 * j);
            }
            prefetch_map(&mXe);
#pragma unroll 1
            for (int u = 0; u < 4; u++) {
                if (u == 2) {
                    mbar_wait(bar_dfree + 16);
                    if (elect_one()) tma5(sb + tail_c(8), &mCim, c_col(63), dt * 8, full + 8 * (NBIG + 8));
                }
                mbar_wait(bar_dfree);
                behind(u < 2 ? TN(DN_E0) + u : NBIG + NSPL);
                if (elect_one())
                    asm volatile("cp.async.bulk.tensor.5d.shared::cluster.global.mbarrier::complete_tx::bytes [%0], [%1, {%3, %6, %6, %4, %5}], [%2];"
                                 ::"r"(sb + (u < 2 ? OFF_FT : tail_c(0)) + (u & 1) * TILE), "l"(&mXe), "r"(bar_x + 4 * (u & 2)), "r"(dt * 128 + (u & 1) * 64),
                                 "r"(u & 2), "r"(chunk * 4), "r"(0) : "memory");
            }
        } else if (warp == 13) {
#pragma unroll
            for (int u = 0; u < 8; u++) {
                const int row = (u >> 2) * 4 + (lane >> 3);
                cp_async16(sb + OFF_XS + (u & 3) * 1024 + row * 128 + (((lane & 7) ^ row) << 4), (const char*)(u < 4 ? prm.w_r : prm.gate_w) + (u & 3) * 512 + lane * 16);
            }
            STAMP(57);
            const uint32_t tag = ld_relaxed(&prm.s->epoch[cta]) + 1;
            named_bar(1, 64);
            *reinterpret_cast<uint2*>(smem + OFF_EPOCH) = make_uint2(tag, tag % 3u + 1u);
            STAMPIF(tag, 58);
            asm volatile("cp.async.wait_all;" ::: "memory");
            STAMP(59);
            fence_async_smem();
            __syncwarp();
            if (lane == 0) {
                mbar_arrive(bar_epoch);
                prm.s->epoch[cta] = tag;
            }
            sleep_until(cstart + TN(T_BASE));
            {
                const uint2 st = ld_relaxed2(&prm.s->start[2 * lane]);
                const uint32_t d = st.x - cstart + 512u, age = gtime32() - st.y;
                const uint32_t m = __reduce_max_sync(0xffffffffu, d < 1024u && age < 4096u ? (d << 12) | age : 0u);
                const uint32_t late = (m & 4095u) - __reduce_min_sync(0xffffffffu, age);
                *reinterpret_cast<volatile uint32_t*>(smem + OFF_EPOCH + 8) = cstart + (m ? (m >> 12) - 512u + min(late, 256u) * TN(G_NS) / 4 : 0u);
                __syncwarp();
                if (lane == 0) mbar_arrive(bar_base);
                STAMP(60);
            }
            mbar_wait(bar_const);
            asm volatile("fence.acq_rel.gpu;" ::: "memory");
            if (lane < 4) st_relaxed2(&prm.s->armed[cta * 4 + lane], tag % 3u + 1u, 0u);
            prefetch_map(&mCre);
            prefetch_map(&mCim);
            const char* src = reinterpret_cast<const char*>(prm.s->h) + (size_t)chunk * 524288;
            uint32_t slot = 32 % NST, hpar = 0, rpar = 0;
#pragma unroll 1
            for (int i = 32; i < NBIG; i++) {
                mbar_wait(hfull + 8 * slot, hpar);
                STAMPIF(i == 32 || i == 33, 14 + (i & 1));
                rpar = check_tile<16>(sb, sb + slot * SLOT, probe, src, tag, bar_retry, rpar, TN(T_RETRY));
                if (lane == 0) mbar_expect_tx(full + 8 * i, 2 * TILE);
                STAMPIF(i == 32 || i == 33, 16 + (i & 1));
                src += 2 * TILE;
                slot = slot == NST - 1 ? 0 : slot + 1;
                hpar ^= slot == 32 % NST;
            }
        } else if (warp == 14) {
            const char* pc = (const char*)((lane & 16) ? prm.c_im : prm.c_re) + (cta * 8 + (g & 3)) * 2048 + c * 128;
            auto pf_c = [&](int k) { prefetch_l2(pc + (k >> 1) * 512 + (k & 1) * 8192); };
            {
                const char* px = (const char*)prm.x + (rid * 16 + (lane >> 1)) * 2048 + (lane & 1) * 128;
                const char* pb = (const char*)((lane & 8) ? prm.b_im : prm.b_re) + (cta * 4 + ((lane >> 1) & 3)) * 2048 + (lane & 1) * 128;
#pragma unroll 1
                for (int k = 1; k < 8; k++) {
                    sleep_until(cstart + TN(PF0) + (k - 1) * TN(PF1));
                    prefetch_l2(px + k * 256);
                    if (lane < 16) prefetch_l2(pb + k * 256);
                }
            }
            named_bar(7, 160);
            mbar_wait(bar_base);
#pragma unroll 1
            for (int k = 0; k < 4; k++) {
                behind(TN(PB_E0) + TN(PB_STEP) * k);
                prefetch_l2((const char*)((lane & 16) ? prm.b_im : prm.b_re) + (512 + cta * 4 + (g & 3)) * 2048 + c * 128 + k * 512);
            }
#pragma unroll 1
            for (int k = 0; k < TN(PC_N); k++) {
                behind(min(TN(PC_E0) + TN(PC_STEP) * k / 2, 25));
                pf_c(k);
            }
            int pk = TN(PC_N), pe = TN(PC_E1);
            auto own_part = [&](int e) {
                if (!(TDBG & 16) && !mbar_test(bar_out + 8 * e, 0)) {
                    mbar_wait(bar_out + 8 * e);
                    sleep_until(clk32() + TN(T_OWN));
                    STAMP(11);
                }
            };
            const char* src = reinterpret_cast<const char*>(prm.s->h) + (size_t)chunk * 524288;
            uint32_t slot = 32 % NST;
#pragma unroll 1
            for (int i = 32; i < NBIG; i++) {
                if (!(i & 3)) own_part((i - 32) >> 2);
                mbar_wait(empty + 8 * (i - NST));
                PSTAMP(i);
                if (elect_one()) {
                    mbar_expect_tx(hfull + 8 * slot, 2 * TILE);
                    bulk_load(sb + slot * SLOT, src, 2 * TILE, hfull + 8 * slot);
                    tma5(sb + slot * SLOT + 2 * TILE, (i & 4) ? &mCim : &mCre, c_col(i), dt * 8, full + 8 * i);
                }
                if (i == pe && pk < 8) {
                    pf_c(pk);
                    pk++; pe += TN(PC_S1);
                }
                src += 2 * TILE;
                slot = slot == NST - 1 ? 0 : slot + 1;
            }
            src -= (NBIG - 32) * 2 * TILE;
#pragma unroll
            for (int k = 0; k < 2 * NSPL - 2; k++) {
                if (k == 0 || k == 2) own_part(6 + k / 2);
                mbar_wait(empty + 8 * (NBIG - NST + k));
                if (k >= 1 && k <= 4) {
                    if (elect_one()) {
#pragma unroll
                        for (int j = 2 * k - 2; j < 2 * k; j++)
                            tma5(sb + tail_c(j), ((NBIG + j) & 4) ? &mCim : &mCre, c_col(NBIG + j), dt * 8, full + 8 * (NBIG + j));
                    }
                }
                if (k == 4) continue;
                if (k == 2) mbar_wait(bar_dfree + 8);
                if (elect_one()) {
#pragma unroll
                    for (int n = k < 5 ? 2 * k : k + 2; n < (k < 3 ? 2 * k + 2 : k == 3 ? 7 : k + 3); n++) {
                        mbar_expect_tx(hfull + 8 * (NST + n % 7), TILE);
                        bulk_load(sb + tail_h(n), src + tail_src(n), TILE, hfull + 8 * (NST + n % 7));
                    }
                }
            }
        } else {
            if (elect_one()) {
#pragma unroll
                for (int i = 0; i < NST; i++) mbar_init(full + 8 * i, 1);
                fence_mbar_init();
            }
            __syncwarp();
            asm volatile("bar.arrive 5, 160;" ::: "memory");
            asm volatile("bar.arrive 0, 448;" ::: "memory");
#pragma unroll 1
            for (int i = 0; i < NST; i++) {
                if (elect_one()) {
                    mbar_expect_tx(full + 8 * i, SLOT);
                    tma5b(sb + i * SLOT, &mB, i * 64, dt * 4, full + 8 * i);
                    tma4(sb + i * SLOT + 2 * TILE, &mX, i * 64, chunk * 64, full + 8 * i);
                }
                STAMPIF(i == 0, 1);
            }
            STAMP(2);
            named_bar(6, 160);
            uint32_t dst = sb;
#pragma unroll 1
            for (int i = NST; i < 32; i++) {
                if (i == 2 * NST) mbar_wait(bar_base);
                if (lane == 0) mbar_expect_tx(full + 8 * i, SLOT);
                mbar_wait(empty + 8 * (i - NST));
                PSTAMP(i);
                if (elect_one()) {
                    tma5b(dst, &mB, (i & 15) * 64, (i >> 4) * 64 + dt * 4, full + 8 * i);
                    tma4(dst + 2 * TILE, &mX, (i & 15) * 64, chunk * 64, full + 8 * i);
                }
                dst = dst == sb + (NST - 1) * SLOT ? sb : dst + SLOT;
            }
        }
    }
}

typedef CUresult (*EncodeFn)(CUtensorMap*, CUtensorMapDataType, cuuint32_t, void*, const cuuint64_t*, const cuuint64_t*, const cuuint32_t*,
                             const cuuint32_t*, CUtensorMapInterleave, CUtensorMapSwizzle, CUtensorMapL2promotion, CUtensorMapFloatOOBfill);

bool encode(EncodeFn fn, CUtensorMap* m, const void* ptr, int rank, const cuuint64_t* dims, const cuuint64_t* strides, const cuuint32_t* box,
            CUtensorMapL2promotion promo = CU_TENSOR_MAP_L2_PROMOTION_NONE) {
    const cuuint32_t es[5] = {1, 1, 1, 1, 1};
    return fn(m, CU_TENSOR_MAP_DATA_TYPE_BFLOAT16, rank, const_cast<void*>(ptr), dims, strides, box, es, CU_TENSOR_MAP_INTERLEAVE_NONE,
              CU_TENSOR_MAP_SWIZZLE_128B, promo, CU_TENSOR_MAP_FLOAT_OOB_FILL_NONE) == CUDA_SUCCESS;
}

}

extern "C" void kernel_launch(void* const* d_in, const int* in_sizes, int n_in, void* d_out, int out_size) {
    (void)in_sizes; (void)n_in; (void)out_size;
    Params prm;
    prm.x = (const __nv_bfloat16*)d_in[0];
    prm.lam_re = (const __nv_bfloat16*)d_in[1];
    prm.lam_im = (const __nv_bfloat16*)d_in[2];
    prm.b_re = (const __nv_bfloat16*)d_in[3];
    prm.b_im = (const __nv_bfloat16*)d_in[4];
    prm.c_re = (const __nv_bfloat16*)d_in[5];
    prm.c_im = (const __nv_bfloat16*)d_in[6];
    prm.log_dt = (const __nv_bfloat16*)d_in[7];
    prm.dskip = (const __nv_bfloat16*)d_in[8];
    prm.w_r = (const __nv_bfloat16*)d_in[10];
    prm.gate_w = (const __nv_bfloat16*)d_in[14];
    prm.out = (float*)d_out;
    cudaGetSymbolAddress((void**)&prm.s, g_scratch);
    prm.swapped = prm.b_im < prm.b_re;

    void* fnp = nullptr;
    cudaDriverEntryPointQueryResult qr;
    cudaGetDriverEntryPoint("cuTensorMapEncodeTiled", &fnp, cudaEnableDefault, &qr);
    EncodeFn fn = (EncodeFn)fnp;
    cudaFuncSetAttribute(fused_kernel, cudaFuncAttributeMaxDynamicSharedMemorySize, SMEM_BYTES);

    CUtensorMap mX, mB, mCre, mCim, mWg, mWu, mWd, mXr, mXe;
    const cuuint64_t row = 2048;
    {
        const cuuint64_t dims[4] = {1024, 2, 4, 976}, st[3] = {row, 32 * row, 2 * row};
        const cuuint32_t box[4] = {64, 2, 4, 16};
        encode(fn, &mX, prm.x, 4, dims, st, box, PROMO);
    }
    {
        const char *lo = (const char*)(prm.swapped ? prm.b_im : prm.b_re), *hi = (const char*)(prm.swapped ? prm.b_re : prm.b_im);
        const cuuint64_t dims[5] = {1024, 8, 2, 96, 2}, st[4] = {row, (cuuint64_t)(hi - lo), 8 * row, 256 * row};
        const cuuint32_t box[5] = {64, 8, 2, 4, 2};
        encode(fn, &mB, lo, 5, dims, st, box, PROMO);
    }
    {
        const cuuint64_t dims[5] = {1024, 2, 4, 2, 64}, st[4] = {row, 4 * row, 2 * row, 16 * row};
        const cuuint32_t box[5] = {64, 2, 4, 2, 8};
        encode(fn, &mCre, prm.c_re, 5, dims, st, box);
        encode(fn, &mCim, prm.c_im, 5, dims, st, box);
    }
    {
        const cuuint64_t dims[2] = {F_, D_}, st[1] = {F_ * 2}, dimsd[2] = {D_, F_}, std_[1] = {row};
        const cuuint32_t box[2] = {64, 64};
        encode(fn, &mWg, d_in[11], 2, dims, st, box);
        encode(fn, &mWu, d_in[12], 2, dims, st, box);
        encode(fn, &mWd, d_in[13], 2, dimsd, std_, box);
    }
    {
        const cuuint64_t dims[3] = {D_ - 192, S_, 4}, st[2] = {row, 128};
        const cuuint32_t box[3] = {64, 16, 4};
        encode(fn, &mXr, prm.x, 3, dims, st, box);
    }
    {
        const cuuint64_t dims[5] = {1024, 2, 4, 4, S_ / 32}, st[4] = {4 * row, row, 8 * row, 32 * row};
        const cuuint32_t box[5] = {64, 2, 4, 2, 4};
        encode(fn, &mXe, prm.x, 5, dims, st, box);
    }
    fused_kernel<<<NCTA, 512, SMEM_BYTES, cudaStreamPerThread>>>(prm, mX, mB, mCre, mCim, mWg, mWu, mWd, mXr, mXe);
}
```

```cpp
#include <cuda_runtime.h>
#include <cuda_bf16.h>
#include <cuda.h>
#include <stdint.h>

namespace {

constexpr int S_ = 2048, D_ = 1024, F_ = 3584;
constexpr int NCTA = 128;
constexpr int NSPL = 9, NBIG = 64 - NSPL, NENT = NBIG + 2 * NSPL;
constexpr int NST = 5;
constexpr int NFT = 5;
constexpr uint32_t SLOT = 32768, TILE = 8192;
constexpr uint32_t OFF_FT = NST * SLOT;
constexpr uint32_t OFF_XS = OFF_FT + NFT * TILE;
constexpr uint32_t OFF_LIST = OFF_XS + 8192;
constexpr uint32_t OFF_RED = OFF_XS + 4096;
constexpr uint32_t OFF_CONST = OFF_XS + 16384;
constexpr uint32_t OFF_M = OFF_CONST + 8192;
constexpr uint32_t OFF_HID = OFF_CONST;
constexpr uint32_t OFF_G = OFF_M + 512;
constexpr uint32_t OFF_DK = OFF_G + 256;
constexpr uint32_t OFF_FULL = OFF_DK + 256;
constexpr uint32_t OFF_EMPTY = OFF_FULL + 103 * 8;
constexpr uint32_t OFF_KEYS = OFF_EMPTY + 87 * 8;
constexpr uint32_t OFF_SEL = OFF_KEYS + 32;
constexpr uint32_t OFF_EPOCH = OFF_SEL + 32;
constexpr uint32_t OFF_PROF = OFF_EPOCH + 16;
constexpr uint32_t SMEM_BYTES = OFF_PROF + 432;
static_assert(SMEM_BYTES <= 232448, "smem");

static_assert(NBIG % NST == 0, "tail layout");
__host__ __device__ constexpr uint32_t tail_c(int j) { return j < 8 ? SLOT + j * 2 * TILE : OFF_FT + 5 * TILE; }
__host__ __device__ constexpr uint32_t tail_h(int n) { return n % 7 < 4 ? n % 7 * TILE : OFF_FT + (n % 7 - 2) * TILE; }
__host__ __device__ constexpr uint32_t tail_src(int n) { return (n % NSPL + NBIG - 32) * 2 * TILE + n / NSPL * TILE; }
__host__ __device__ constexpr int c_col(int i) { return ((i & 3) + ((i >> 1) & 12)) * 64; }

constexpr uint32_t SPIN_LIMIT = 1u << 20;

struct Scratch {
    uint2 carry[16 * 1024];
    uint2 hid[NCTA * 128];
    uint32_t y[8 * 8 * D_];
    uint32_t key[NCTA * 8];
    uint32_t gate[S_];
    uint4 part[112 * 128];
    unsigned int epoch[256];
    uint4 h[16 * 32 * 1024];
};
__device__ __align__(1024) Scratch g_scratch;
#define STAMPW_(cond, w) do {} while (0)
#define GSTAMP(cond, w) do {} while (0)
#define LSTAMP(cond, w) STAMPW_(cond, w)
#define LT 0
#define STAMPW(cond, w) STAMPW_(cond, w)
#define STAMPIF(cond, i) STAMPW(cond, 96 + (i))
#define STAMP(i) STAMPW(1, 96 + (i))
#define KSTAMP(i) STAMPW((threadIdx.x & 127) == 0, i)
#define PSTAMP(i) STAMPW((i) < 56 && (i) >= 32, 160 + (i))

struct Params {
    const __nv_bfloat16 *x, *b_re, *b_im, *lam_re, *lam_im, *c_re, *c_im, *log_dt, *dskip, *w_r, *gate_w;
    float* out;
    Scratch* s;
    int swapped;
};

__device__ __forceinline__ uint32_t smem_u32(const void* p) { return (uint32_t)__cvta_generic_to_shared(p); }
__device__ __forceinline__ void mbar_init(uint32_t bar, uint32_t cnt) { asm volatile("mbarrier.init.shared::cta.b64 [%0], %1;" ::"r"(bar), "r"(cnt) : "memory"); }
__device__ __forceinline__ void mbar_expect_tx(uint32_t bar, uint32_t bytes) { asm volatile("mbarrier.arrive.expect_tx.shared::cta.b64 _, [%0], %1;" ::"r"(bar), "r"(bytes) : "memory"); }
__device__ __forceinline__ void mbar_arrive(uint32_t bar) { asm volatile("mbarrier.arrive.shared::cta.b64 _, [%0];" ::"r"(bar) : "memory"); }
__device__ __forceinline__ bool mbar_test(uint32_t bar, uint32_t parity) {
    uint32_t ok;
    asm volatile("{ .reg .pred p; mbarrier.test_wait.parity.shared::cta.b64 p, [%1], %2; selp.u32 %0, 1, 0, p; }" : "=r"(ok) : "r"(bar), "r"(parity) : "memory");
    return __all_sync(0xffffffffu, ok);
}
__device__ __forceinline__ void mbar_wait(uint32_t bar, uint32_t parity = 0) {
    asm volatile("{ .reg .pred p; .reg .u32 n; mov.u32 n, 0;\nW%=: mbarrier.try_wait.parity.shared::cta.b64 p, [%0], %1; @p bra D%=;\n"
                 "add.u32 n, n, 0x1000; setp.ne.u32 p, n, 0; @p bra W%=; trap;\nD%=: }" ::"r"(bar), "r"(parity) : "memory");
}
__device__ __forceinline__ bool elect_one() {
    uint32_t pred;
    asm volatile("{ .reg .pred P; elect.sync _|P, 0xffffffff; selp.b32 %0, 1, 0, P; }" : "=r"(pred));
    return pred;
}
__device__ __forceinline__ void named_bar(int id, int n) { asm volatile("bar.sync %0, %1;" ::"r"(id), "r"(n) : "memory"); }
__device__ __forceinline__ void fence_mbar_init() { asm volatile("fence.mbarrier_init.release.cluster;" ::: "memory"); }
__device__ __forceinline__ void fence_async_smem() { asm volatile("fence.proxy.async.shared::cta;" ::: "memory"); }

__device__ __forceinline__ void bulk_load(uint32_t dst, const void* src, uint32_t bytes, uint32_t bar) {
    asm volatile("cp.async.bulk.shared::cluster.global.mbarrier::complete_tx::bytes [%0], [%1], %2, [%3];" ::"r"(dst), "l"(src), "r"(bytes), "r"(bar) : "memory");
}
__device__ __forceinline__ void cp_async16(uint32_t dst, const void* src) { asm volatile("cp.async.cg.shared.global [%0], [%1], 16;" ::"r"(dst), "l"(src) : "memory"); }
__device__ __forceinline__ void sts128(uint32_t a, uint32_t x, uint32_t y, uint32_t z, uint32_t w) {
    asm volatile("st.shared.v4.u32 [%0], {%1,%2,%3,%4};" ::"r"(a), "r"(x), "r"(y), "r"(z), "r"(w) : "memory");
}
__device__ __forceinline__ uint2 lds64(uint32_t a) {
    uint2 v;
    asm volatile("ld.shared.v2.u32 {%0,%1}, [%2];" : "=r"(v.x), "=r"(v.y) : "r"(a) : "memory");
    return v;
}
__device__ __forceinline__ uint32_t lds32(uint32_t a) {
    uint32_t v;
    asm volatile("ld.volatile.shared.u32 %0, [%1];" : "=r"(v) : "r"(a) : "memory");
    return v;
}
__device__ __forceinline__ void stg128(void* p, uint32_t x, uint32_t y, uint32_t z, uint32_t w) {
    asm volatile("st.global.v4.u32 [%0], {%1,%2,%3,%4};" ::"l"(p), "r"(x), "r"(y), "r"(z), "r"(w) : "memory");
}
__device__ __forceinline__ void st_relaxed(void* p, uint32_t x) { asm volatile("st.relaxed.gpu.global.b32 [%0], %1;" ::"l"(p), "r"(x) : "memory"); }
__device__ __forceinline__ void st_relaxed2(void* p, uint32_t x, uint32_t y) { asm volatile("st.relaxed.gpu.global.v2.b32 [%0], {%1, %2};" ::"l"(p), "r"(x), "r"(y) : "memory"); }
__device__ __forceinline__ void st_relaxed4(void* p, uint32_t x, uint32_t y, uint32_t z, uint32_t w) {
    asm volatile("st.relaxed.gpu.global.v4.b32 [%0], {%1, %2, %3, %4};" ::"l"(p), "r"(x), "r"(y), "r"(z), "r"(w) : "memory");
}
__device__ __forceinline__ uint32_t ld_relaxed(const void* p) {
    uint32_t v;
    asm volatile("ld.relaxed.gpu.global.b32 %0, [%1];" : "=r"(v) : "l"(p) : "memory");
    return v;
}
__device__ __forceinline__ uint2 ld_relaxed2(const void* p) {
    uint2 v;
    asm volatile("ld.relaxed.gpu.global.v2.b32 {%0, %1}, [%2];" : "=r"(v.x), "=r"(v.y) : "l"(p) : "memory");
    return v;
}
__device__ __forceinline__ uint4 ld_relaxed4(const void* p) {
    uint4 v;
    asm volatile("ld.relaxed.gpu.global.v4.b32 {%0, %1, %2, %3}, [%4];" : "=r"(v.x), "=r"(v.y), "=r"(v.z), "=r"(v.w) : "l"(p) : "memory");
    return v;
}
__device__ __forceinline__ uint32_t clk32() { uint32_t c; asm volatile("mov.u32 %0, %%clock;" : "=r"(c)); return c; }
__device__ __forceinline__ void sched_fence(uint32_t t) { while ((int)(clk32() - t) < 0) {} }
__device__ __forceinline__ void sleep_until(uint32_t t) { while ((int)(clk32() - t) < 0) __nanosleep(40); }

__device__ __forceinline__ void tma2(uint32_t dst, const CUtensorMap* m, int c0, int c1, uint32_t bar) {
    asm volatile("{ .reg .b64 pol; createpolicy.fractional.L2::evict_first.b64 pol;\n"
                 "cp.async.bulk.tensor.2d.shared::cluster.global.mbarrier::complete_tx::bytes.L2::cache_hint [%0], [%1, {%3, %4}], [%2], pol; }"
                 ::"r"(dst), "l"(m), "r"(bar), "r"(c0), "r"(c1) : "memory");
}
__device__ __forceinline__ void tma3(uint32_t dst, const CUtensorMap* m, int c0, int c1, uint32_t bar) {
    asm volatile("cp.async.bulk.tensor.3d.shared::cluster.global.mbarrier::complete_tx::bytes [%0], [%1, {%3, %4, %5}], [%2];"
                 ::"r"(dst), "l"(m), "r"(bar), "r"(c0), "r"(c1), "r"(0) : "memory");
}
__device__ __forceinline__ void tma4(uint32_t dst, const CUtensorMap* m, int c0, int c3, uint32_t bar) {
    asm volatile("cp.async.bulk.tensor.4d.shared::cluster.global.mbarrier::complete_tx::bytes [%0], [%1, {%3, %5, %5, %4}], [%2];"
                 ::"r"(dst), "l"(m), "r"(bar), "r"(c0), "r"(c3), "r"(0) : "memory");
}
__device__ __forceinline__ void tma5(uint32_t dst, const CUtensorMap* m, int c0, int c4, uint32_t bar) {
    asm volatile("cp.async.bulk.tensor.5d.shared::cluster.global.mbarrier::complete_tx::bytes [%0], [%1, {%3, %5, %5, %5, %4}], [%2];"
                 ::"r"(dst), "l"(m), "r"(bar), "r"(c0), "r"(c4), "r"(0) : "memory");
}
__device__ __forceinline__ void tma5b(uint32_t dst, const CUtensorMap* m, int c0, int c3, uint32_t bar) {
    asm volatile("cp.async.bulk.tensor.5d.shared::cluster.global.mbarrier::complete_tx::bytes [%0], [%1, {%3, %5, %5, %4, %5}], [%2];"
                 ::"r"(dst), "l"(m), "r"(bar), "r"(c0), "r"(c3), "r"(0) : "memory");
}
__device__ __forceinline__ void prefetch_l2(const void* p) { asm volatile("prefetch.global.L2 [%0];" ::"l"(p)); }
__device__ __forceinline__ void prefetch_map(const CUtensorMap* m) { asm volatile("prefetch.tensormap [%0];" ::"l"(m)); }
__device__ __forceinline__ uint32_t uni(uint32_t v) { return __shfl_sync(0xffffffffu, v, 0); }

__device__ __forceinline__ uint32_t make_desc(uint32_t addr) { return ((addr & 0x3FFFF) >> 4) | (1u << 16); }
__device__ __forceinline__ uint32_t make_desc_h(uint32_t addr) { return ((addr & 0x3FFFF) >> 4) | (32u << 16); }
template <int H> __device__ __forceinline__ uint64_t desc64(uint32_t lo) {
    uint64_t d;
    asm volatile("mov.b64 %0, {%1, %2};" : "=l"(d) : "r"(lo), "n"(64u | ((H ? 2u : 1u) << 30)));
    return d;
}
__device__ __forceinline__ void wgmma_fence() { asm volatile("wgmma.fence.sync.aligned;" ::: "memory"); }
__device__ __forceinline__ void wgmma_commit() { asm volatile("wgmma.commit_group.sync.aligned;" ::: "memory"); }
template <int N> __device__ __forceinline__ void wgmma_wait() { asm volatile("wgmma.wait_group.sync.aligned %0;" ::"n"(N) : "memory"); }

#define R8(d, i) "+f"(d[i]), "+f"(d[i + 1]), "+f"(d[i + 2]), "+f"(d[i + 3]), "+f"(d[i + 4]), "+f"(d[i + 5]), "+f"(d[i + 6]), "+f"(d[i + 7])
#define R64(d) R8(d, 0), R8(d, 8), R8(d, 16), R8(d, 24), R8(d, 32), R8(d, 40), R8(d, 48), R8(d, 56)
template <int TA>
__device__ __forceinline__ void wgmma_n128(float (&d)[64], uint64_t da, uint64_t db, int scale_d = 1) {
    asm volatile("{ .reg .pred p; setp.ne.b32 p, %66, 0;\n"
                 "wgmma.mma_async.sync.aligned.m64n128k16.f32.bf16.bf16 "
                 "{%0,%1,%2,%3,%4,%5,%6,%7,%8,%9,%10,%11,%12,%13,%14,%15,%16,%17,%18,%19,%20,%21,%22,%23,%24,%25,%26,%27,%28,%29,%30,%31,"
                 "%32,%33,%34,%35,%36,%37,%38,%39,%40,%41,%42,%43,%44,%45,%46,%47,%48,%49,%50,%51,%52,%53,%54,%55,%56,%57,%58,%59,%60,%61,%62,%63}, "
                 "%64, %65, p, 1, 1, %67, 0; }"
                 : R64(d)
                 : "l"(da), "l"(db), "r"(scale_d), "n"(TA));
}
__device__ __forceinline__ void pin4(float (&d)[4]) { asm volatile("" : "+f"(d[0]), "+f"(d[1]), "+f"(d[2]), "+f"(d[3])::"memory"); }
__device__ __forceinline__ void pin64(float (&d)[64]) { asm volatile("" : R64(d)::"memory"); }

template <int TA>
__device__ __forceinline__ void wgmma_n8(float (&d)[4], uint64_t da, uint64_t db, int scale_d = 1) {
    asm volatile("{ .reg .pred p; setp.ne.b32 p, %7, 0;\n"
                 "wgmma.mma_async.sync.aligned.m64n8k16.f32.bf16.bf16 {%0,%1,%2,%3}, %4, %5, p, 1, 1, %6, 0; }"
                 : "+f"(d[0]), "+f"(d[1]), "+f"(d[2]), "+f"(d[3])
                 : "l"(da), "l"(db), "n"(TA), "r"(scale_d));
}

__device__ __forceinline__ float bf_lo(uint32_t u) { return __uint_as_float(u << 16); }
__device__ __forceinline__ float bf_hi(uint32_t u) { return __uint_as_float(u & 0xFFFF0000u); }
__device__ __forceinline__ float rbf(float v) { return __bfloat162float(__float2bfloat16_rn(v)); }
__device__ __forceinline__ uint32_t pack_bf(float lo, float hi) {
    uint32_t r;
    asm("cvt.rn.bf16x2.f32 %0, %1, %2;" : "=r"(r) : "f"(hi), "f"(lo));
    return r;
}
__device__ __forceinline__ uint32_t mul_bf2(uint32_t a, uint32_t b) {
    uint32_t r;
    asm("mul.rn.bf16x2 %0, %1, %2;" : "=r"(r) : "r"(a), "r"(b));
    return r;
}
__device__ __forceinline__ uint32_t fma_bf2(uint32_t a, uint32_t b, uint32_t c) {
    uint32_t r;
    asm("fma.rn.bf16x2 %0, %1, %2, %3;" : "=r"(r) : "r"(a), "r"(b), "r"(c));
    return r;
}
__device__ __forceinline__ float2 cmul(float2 a, float2 b) { return make_float2(a.x * b.x - a.y * b.y, a.x * b.y + a.y * b.x); }
__device__ __forceinline__ float2 cfma(float2 a, float2 b, float2 c) {
    return make_float2(fmaf(a.x, b.x, fmaf(-a.y, b.y, c.x)), fmaf(a.x, b.y, fmaf(a.y, b.x, c.y)));
}
__device__ __forceinline__ float sigmoidf_(float v) { return __fdividef(1.0f, 1.0f + expf(-v)); }

#define SCHED_NAMES T_W0, T_INIT, T_SMALL, T_W3, PF0, PF1, RT0, RT1, RT2, RT3, GT1, G0, T_CP0, T_CP1, GAP0, GAP1, T_OWN, \
    T_RETRY, T_Y, PB_E0, PB_STEP, PC_E0, PC_STEP, PC_N, PC_E1, PC_S1, GU_E0, W_NUM, GC0, GCS, GCS4, GCH, HG, DL0, DLS, DN_E0
enum { SCHED_NAMES, NTUNE };
constexpr int sched_default[NTUNE] = {
    600, 1000, 1000, 1000,
    1100, 450,
    2200, 2700, 3200, 3700,
    7300,
    800, 1000, 1000,
    270, 300,
    1000, 200, 1000,
    4, 2, 12, 4, 6, 50, 3,
    5, 8, 14, 8, 5, 11,
    43, 37, 8, 49};
template <int I> struct Sched { static constexpr int v = sched_default[I]; };
#define TN(i) (Sched<i>::v)
#define DBG 0
#define TDBG 0
#define X0 1
#define PROMO CU_TENSOR_MAP_L2_PROMOTION_L2_256B

template <int TA, class H>
__device__ __forceinline__ void run_entry(uint32_t lo32, uint32_t prev, int accumulate, float (&accA)[64], float (&accB)[64], H inside) {
    const uint64_t da = desc64<TA>(lo32), db = TA ? desc64<0>(lo32 + (2 * TILE >> 4) - (31u << 16)) : da + (2 * TILE >> 4);
    wgmma_fence();
#pragma unroll
    for (int kk = 0; kk < 4; kk++) {
        wgmma_n128<TA>(accA, da + kk * (TA ? 128 : 2), db + kk * 2, kk > 0 ? 1 : accumulate);
        wgmma_n128<TA>(accB, da + 512 + kk * (TA ? 128 : 2), db + kk * 2, kk > 0 ? 1 : accumulate);
        if (kk == 1) {
            wgmma_commit();
            wgmma_wait<1>();
            if ((threadIdx.x & 31) == 0) mbar_arrive(prev);
            inside();
        }
    }
    wgmma_commit();
}
template <int TA, class H>
__device__ __forceinline__ void run_entries(uint32_t sb, int lo, int hi, int slot, float (&accA)[64], float (&accB)[64], H after) {
    const uint32_t da0 = TA ? make_desc_h(sb) : make_desc(sb), dlast = da0 + (NST - 1) * (SLOT >> 4);
    uint32_t prev = sb + OFF_FULL + 8 * 101, bar = sb + OFF_FULL + 8 * lo, lo32 = da0 + slot * (SLOT >> 4);
    int accumulate = 0;
#pragma unroll 1
    for (int i = lo; i < hi; i++) {
        mbar_wait(bar);
        KSTAMP(i);
        run_entry<TA>(lo32, prev, accumulate, accA, accB, []() {});
        prev = bar + (OFF_EMPTY - OFF_FULL);
        bar += 8;
        lo32 = lo32 == dlast ? da0 : lo32 + (SLOT >> 4);
        accumulate = 1;
        after(i);
    }
}

template <int TA>
__device__ __forceinline__ void small_tile(float (&acc)[4], uint32_t alo, uint32_t blo, bool first) {
    const uint64_t da = desc64<0>(alo), db = desc64<0>(blo);
#pragma unroll
    for (int kk = 0; kk < 4; kk++) wgmma_n8<TA>(acc, da + kk * (TA ? 128 : 2), db + kk * 2, kk > 0 || !first);
}

template <int N>
__device__ __forceinline__ uint32_t check_tile(uint32_t sb, uint32_t dst, uint32_t probe, const char* src, uint32_t par, uint32_t bar, uint32_t phase, uint32_t pause) {
    if (TDBG & 4) return phase;
#pragma unroll 1
    for (uint32_t it = 0; it < SPIN_LIMIT; it++) {
        uint32_t v[N], bad = 0;
#pragma unroll
        for (int u = 0; u < N; u++) v[u] = lds32(dst + probe + (u >> 1) * 2048 + (u & 1) * 256);
#pragma unroll
        for (int u = 0; u < N; u += 4)
            asm("{ .reg .b32 a, b; lop3.b32 a, %1, %2, %5, 0x7E; lop3.b32 b, %3, %4, %5, 0x7E; lop3.b32 %0, %0, a, b, 0xFE; }"
                : "+r"(bad) : "r"(v[u]), "r"(v[u + 1]), "r"(v[u + 2]), "r"(v[u + 3]), "r"(par));
        if (!__any_sync(0xffffffffu, bad & 1u)) return phase;
        STAMP(10);
        __nanosleep(pause);
        if (elect_one()) {
            mbar_expect_tx(bar, N * 1024);
            bulk_load(dst, src, N * 1024, bar);
        }
        mbar_wait(bar, phase);
        phase ^= 1;
    }
    __trap();
    return 0;
}

__global__ void __launch_bounds__(512, 1)
fused_kernel(const __grid_constant__ Params prm, const __grid_constant__ CUtensorMap mX, const __grid_constant__ CUtensorMap mB, const __grid_constant__ CUtensorMap mCre,
             const __grid_constant__ CUtensorMap mCim, const __grid_constant__ CUtensorMap mWg, const __grid_constant__ CUtensorMap mWu,
             const __grid_constant__ CUtensorMap mWd, const __grid_constant__ CUtensorMap mXr,
             const __grid_constant__ CUtensorMap mXe) {
    {
        const uint32_t t = threadIdx.x, b = blockIdx.x;
        const uint32_t row = t < 32 ? ((b & 60) * 2 + (b >> 6) * 4 + (b & 3)) * 16 + (t >> 1) : b * 4 + ((t >> 1) & 3);
        const char* base = (const char*)(t < 32 ? prm.x : t < 40 ? prm.b_re : prm.b_im);
        asm volatile("{ .reg .pred p; setp.lt.u32 p, %1, 48; @p prefetch.global.L2 [%0]; }" ::"l"(base + (row * 2048 + (t & 1) * 128)), "r"(t) : "memory");
    }
    extern __shared__ __align__(1024) uint8_t smem[];
    uint32_t sb;
    asm volatile("mov.u32 %0, %1;" : "=r"(sb) : "r"(smem_u32(smem)));
    const int tid = threadIdx.x, warp = __shfl_sync(0xffffffffu, tid >> 5, 0), lane = tid & 31;
    const int cta = blockIdx.x;
    const uint32_t cstart = clk32();
    const int chunk = (cta >> 2) & 15;
    const int dt = (cta >> 6) * 4 + (cta & 3);
    const int rid = chunk * 8 + dt;
    const int kslot = (rid & 3) * 32 + (rid >> 2);
    const bool owner = cta < 112;
    const uint32_t full = sb + OFF_FULL, empty = sb + OFF_EMPTY;
    const uint32_t dfull = full + 8 * 74, bar_retry = full + 8 * 81, bar_x = full + 8 * 82, ffull = full + 8 * 84,
                   hfull = full + 8 * 89, bar_epoch = full + 8 * 102;
    const uint32_t fempty = empty + 8 * 66, bar_order = empty + 8 * 71, bar_stored = empty + 8 * 73, bar_dfree = empty + 8 * 74,
                   bar_out = empty + 8 * 77, bar_g = empty + 8 * 85, bar_const = empty + 8 * 86;
    const int w = warp & 3, g = lane >> 2, c = lane & 3, at = tid & 127;

    const uint32_t probe = (lane >> 3) * 32 + (g & 1) * 144 + (c & 1) * 520 + (c >> 1) * 1028;

    LSTAMP(tid == 0, 96);
    GSTAMP(tid == 0, 94);
    auto init_barriers = [&](uint32_t base, uint32_t cnt, auto n) {
        if (elect_one()) {
#pragma unroll
            for (int i = 0; i < n(); i++) mbar_init(base + 8 * i, cnt);
            fence_mbar_init();
        }
        __syncwarp();
    };
    if (warp < 12) sleep_until(cstart + (warp < 4 ? TN(T_W0) : TN(T_INIT)));
    if (warp < 8) {
        if (warp < 4) init_barriers(warp == 0 ? full + 40 : warp == 3 ? full + 8 * 98 : empty + 40 * (warp - 1), (warp + 1) & 2 ? 4 : 1, []() { return 5; });
        else init_barriers(full + 80 + 176 * w, 1, []() { return 22; });
        asm volatile("setmaxnreg.inc.sync.aligned.u32 192;");
        if (warp < 4) {
            named_bar(5, 160);
            asm volatile("bar.arrive 0, 448;" ::: "memory");
            asm volatile("bar.arrive 6, 160;" ::: "memory");
            asm volatile("bar.arrive 7, 160;" ::: "memory");
        } else named_bar(0, 448);
        const int wg = warp >> 2;
        const int p = wg * 512 + dt * 32 + w * 8 + g;
        uint32_t cp = sb + OFF_CONST + 8 * (wg * 64 + w * 8 + g), cw = cp + 1024 * c, cm = sb + OFF_M + 4 * (wg * 64 + w * 8 + g);
        const int j1 = chunk - 1 - c;
        uint2* cq = &prm.s->carry[j1 * 1024 + p];
        char* hd = reinterpret_cast<char*>(prm.s->h) + (size_t)chunk * 524288 + wg * 262144 + (dt >> 1) * 16384 + ((dt & 1) * 4 + w) * 1024 + g * 64 + ((c ^ (g >> 1)) << 4);
        const bool never = uni(cstart == 0 && sb == 0);
        asm volatile("" : "+l"(cq), "+l"(hd), "+r"(cp), "+r"(cw), "+r"(cm));
        float2 a[2], a32[2], a64[2], a512[2], pw32[2], pw128[2];
        uint32_t mm[2], t2, par;
        auto constants = [&](int h) {
            if (h) { t2 = lds32(sb + OFF_EPOCH + 4); par = lds32(sb + OFF_EPOCH); }
            auto ldc = [](uint32_t a) { const uint2 v = lds64(a); return make_float2(__uint_as_float(v.x), __uint_as_float(v.y)); };
            a[h] = ldc(cp + 256 * h); a32[h] = ldc(cp + 256 * h + 1024); a64[h] = ldc(cp + 256 * h + 2048); a512[h] = ldc(cp + 256 * h + 7168);
            pw32[h] = ldc(cw + 256 * h);
            pw128[h] = ldc(cw + 256 * h + 3072);
            mm[h] = lds32(cm + 128 * h);
        };
        if (wg == 1) {
            const int pc = w * 256 + dt * 32 + lane;
            const float lr = __bfloat162float(prm.lam_re[pc]), li = __bfloat162float(prm.lam_im[pc]), ld = __bfloat162float(prm.log_dt[pc]);
            const uint32_t dk = __ldg(reinterpret_cast<const uint32_t*>(prm.dskip + dt * 128) + (at & 63));
            reinterpret_cast<uint32_t*>(smem + OFF_DK)[at & 63] = dk;
            const float dtv = rbf(expf(ld));
            const float er = expf(dtv * lr);
            float sn, cs;
            sincosf(dtv * li, &sn, &cs);
            const float ar = er * cs, ai = er * sn;
            const float nr = ar - 1.0f, ni = ai;
            const bool big = fabsf(lr) >= fabsf(li);
            const float t = (big ? li : lr) / (big ? lr : li), dn = big ? lr + li * t : lr * t + li;
            const float cr = (big ? nr + ni * t : nr * t + ni) / dn, ci = (big ? ni - nr * t : ni * t - nr) / dn;
            float2* ct = reinterpret_cast<float2*>(smem + OFF_CONST) + at;
            float2 pw = make_float2(ar, prm.swapped ? -ai : ai);
            ct[0] = pw;
            const float mx = prm.swapped ? -2.f * ci : 2.f * cr, my = prm.swapped ? 2.f * cr : -2.f * ci;
            reinterpret_cast<uint32_t*>(smem + OFF_M)[at] = pack_bf(mx, my);
#pragma unroll
            for (int i = 0; i < 5; i++) pw = cmul(pw, pw);
#pragma unroll
            for (int i = 0; i < 2; i++) {
                const float2 p2 = cmul(pw, pw);
                ct[128 + 384 * i] = pw; ct[256 + 384 * i] = p2; ct[384 + 384 * i] = cmul(p2, pw);
                pw = cmul(p2, p2);
            }
            ct[896] = pw;
            mbar_wait(bar_epoch);
            __syncwarp();
            if (lane == 0) mbar_arrive(bar_const);
            STAMPIF(at == 0, 3);
            mbar_wait(bar_const);
            constants(0);
            constants(1);
            mbar_wait(bar_order);
        }

        float accA[64], accB[64];
        run_entries<0>(sb, wg * 16, wg * 16 + 15, wg, accA, accB, [&](int i) {
            if (i == 2 * NST - 2) mbar_wait(bar_epoch);
        });
        mbar_wait(full + 8 * (wg * 16 + 15));
        KSTAMP(wg * 16 + 15);
        if (wg == 0) {
            mbar_wait(bar_const);
            run_entry<0>(make_desc(sb), empty + 8 * 14, 1, accA, accB, [&]() { constants(0); constants(1); });
            if (lane == 0) mbar_arrive(bar_order);
        } else run_entry<0>(make_desc(sb + SLOT), empty + 8 * 30, 1, accA, accB, [&]() { if (lane == 0) mbar_arrive(bar_order + 8); });
        uint2 v[4];
#pragma unroll
        for (int m = 0; m < 4; m++) v[m] = make_uint2(t2, t2);
        wgmma_wait<0>();
        pin64(accA); pin64(accB);
        if (lane == 0) mbar_arrive(empty + 8 * (wg * 16 + 15));
        LSTAMP(at == 0, 96 + 30 + 10 * wg); GSTAMP(LT && at == 0, 193 + wg);

        auto cut = [&]() { if (never) sched_fence(cstart); };
        auto poll = [&](int h) {
#pragma unroll
            for (int m = 0; m < 4; m++)
                asm volatile("{ .reg .pred p; setp.ge.s32 p, %3, %4; @p ld.relaxed.gpu.global.v2.b32 {%0, %1}, [%2]; }"
                             : "+r"(v[m].x), "+r"(v[m].y) : "l"(cq + 256 * h - 4096 * m), "r"(j1), "r"(4 * m) : "memory");
        };
        auto valid = [&]() {
            uint32_t bad = 0;
#pragma unroll
            for (int m = 0; m < 4; m++) bad |= (v[m].x ^ t2) | (v[m].y ^ t2);
            return __all_sync(0xffffffffu, (bad & 3u) == 0);
        };
        float2 w0[2];
        uint32_t tp;
#pragma unroll
        for (int h = 0; h < 2; h++) {
            float (&acc)[64] = h ? accB : accA;
            float2 e = make_float2(acc[0], acc[2]);
#pragma unroll
            for (int s = 1; s < 32; s++) {
                const int i0 = 4 * (s >> 1) + (s & 1);
                e = cfma(a[h], e, make_float2(acc[i0], acc[i0 + 2]));
            }
            float2 y = make_float2(__shfl_up_sync(0xffffffffu, e.x, 1, 4), __shfl_up_sync(0xffffffffu, e.y, 1, 4));
            if (c >= 1) e = cfma(a32[h], y, e);
            y = make_float2(__shfl_up_sync(0xffffffffu, e.x, 2, 4), __shfl_up_sync(0xffffffffu, e.y, 2, 4));
            if (c >= 2) e = cfma(a64[h], y, e);
            if (c == 3) st_relaxed2(cq + 4096 + 256 * h, (__float_as_uint(e.x) & ~3u) | t2, (__float_as_uint(e.y) & ~3u) | t2);
            if (h == 0) tp = clk32();
            cut();
            w0[h] = make_float2(__shfl_up_sync(0xffffffffu, e.x, 1, 4), __shfl_up_sync(0xffffffffu, e.y, 1, 4));
            STAMPIF(at == 0, 31 + h + 10 * wg);
        }
        uint32_t sx[2][16], sy[2][16], mr[2][4];
        const uint32_t gap = wg ? TN(GAP1) : TN(GAP0);
#pragma unroll
        for (int h = 0; h < 2; h++) {
            const uint32_t sg = prm.swapped ? 0x80008000u : 0u;
            mr[h][0] = __byte_perm(mm[h], 0, 0x1010); mr[h][1] = __byte_perm(mm[h], 0, 0x3232);
            mr[h][2] = mr[h][1] ^ sg; mr[h][3] = mr[h][0] ^ sg ^ 0x80008000u;
        }
        auto put = [&](int e, int j) {
            uint32_t d[4];
#pragma unroll
            for (int u = 0; u < 4; u++) d[u] = fma_bf2(mr[e >> 1][2 * (e & 1)], sx[e >> 1][4 * j + u], mul_bf2(mr[e >> 1][2 * (e & 1) + 1], sy[e >> 1][4 * j + u]));
#pragma unroll
            for (int u = 0; u < 2; u++)
                asm("lop3.b32 %0, %0, %1, %2, 0xD8;" : "+r"(d[2 * (j & 1) + u]) : "r"(par), "r"((uint32_t)((w & 1) == u)));
            stg128(hd + e * 65536 + (j >> 1) * 8192 + (j & 1) * 512, d[0], d[1], d[2], d[3]);
            if (j == 3 && lane == 0) mbar_arrive(bar_out + 32 * wg + 8 * e);
        };
#pragma unroll
        for (int h = 0; h < 2; h++) {
            float (&acc)[64] = h ? accB : accA;
            uint32_t it = 0;
            if (h == 0) {
                sleep_until(tp + (wg ? TN(T_CP1) : TN(T_CP0)));
                poll(h);
            }
            while (!valid()) {
                if (++it > SPIN_LIMIT) __trap();
#pragma unroll
                for (int m = 0; m < 4; m++)
                    asm volatile("{ .reg .pred p; setp.ne.u32 p, %3, 0; @p ld.relaxed.gpu.global.v2.b32 {%0, %1}, [%2]; }"
                                 : "+r"(v[m].x), "+r"(v[m].y) : "l"(cq + 256 * h - 4096 * m), "r"(((v[m].x ^ t2) | (v[m].y ^ t2)) & 3u) : "memory");
            }
            float2 hin = make_float2(__uint_as_float(v[3].x), __uint_as_float(v[3].y));
#pragma unroll
            for (int m = 2; m >= 0; m--) hin = cfma(a512[h], hin, make_float2(__uint_as_float(v[m].x), __uint_as_float(v[m].y)));
            STAMPIF(at == 0 && it > 0 && h == 0, 39 + 10 * wg);
            if (c) hin = cmul(pw128[h], hin);
            hin.x += __shfl_xor_sync(0xffffffffu, hin.x, 1); hin.y += __shfl_xor_sync(0xffffffffu, hin.y, 1);
            hin.x += __shfl_xor_sync(0xffffffffu, hin.x, 2); hin.y += __shfl_xor_sync(0xffffffffu, hin.y, 2);
            float2 st = hin;
            if (c) st = cfma(pw32[h], hin, w0[h]);
            STAMPIF(at == 0, 33 + 3 * h + 10 * wg);
#pragma unroll
            for (int j = 0; j < 4; j++) {
#pragma unroll
                for (int u = 0; u < 4; u++) {
                    const int i0 = 16 * j + 4 * u;
                    const float2 y = cfma(a[h], st, make_float2(acc[i0], acc[i0 + 2]));
                    st = cfma(a[h], y, make_float2(acc[i0 + 1], acc[i0 + 3]));
                    sx[h][4 * j + u] = pack_bf(y.x, st.x); sy[h][4 * j + u] = pack_bf(y.y, st.y);
                }
                if (h) sleep_until(tp += gap);
                if (h == 0 && j == 1) poll(1);
                put(2 * h, j);
                cut();
            }
            STAMPIF(at == 0, 34 + 3 * h + 10 * wg);
            tp = clk32();
#pragma unroll
            for (int j = 0; j < 4; j++) {
                sleep_until(tp += gap);
                put(2 * h + 1, j);
            }
        }
        STAMPIF(at == 0, 38 + 10 * wg);

        if (wg == 1) {
            const char* src = reinterpret_cast<const char*>(prm.s->h) + (size_t)chunk * 524288;
            uint32_t rpar = 1;
#pragma unroll 1
            for (int n = w; n < 2 * NSPL; n += 4) {
                mbar_wait(empty + 8 * (NBIG - 7 + n));
                mbar_wait(hfull + 8 * (NST + n % 7), n / 7 & 1);
                const uint32_t dst = sb + tail_h(n);
                rpar = check_tile<8>(sb, dst, probe, src + tail_src(n), par, full + 8 * w, rpar, TN(T_RETRY));
                if (lane == 0) mbar_expect_tx(full + 8 * (NBIG + n), n < NSPL ? 2 * TILE : 0);
            }
        } else {
            asm volatile("setmaxnreg.inc.sync.aligned.u32 216;");
            const int tl = 64 * (w & 1) + 8 * (w >> 1) + g;
            float gf[4];
            float* op = prm.out + (size_t)(chunk * 128 + tl) * D_ + dt * 128 + 4 * c;
            const int xr = 2 * (g & 3) + (g >> 2);
            uint32_t xs = sb + (32 * (w & 1) + 8 * (w >> 1) + xr) * 128 + (((c >> 1) ^ xr) << 4) + (c & 1) * 8;
            uint32_t gs = sb + OFF_G + 2 * tl;
            asm volatile("" : "+r"(gs), "+l"(op), "+r"(xs));
            float outA[64], outB[64];
            STAMPIF(at == 0, 9);
            mbar_wait(bar_order + 8);
            STAMPIF(at == 0, 35);
            run_entries<1>(sb, 32, NBIG, 32 % NST, outA, outB, [](int) {});
            uint32_t gp[4], om[4];
            uint2 xt[4][8], dk[8];
            auto load_x = [&](int q, int j) {
#pragma unroll
                for (int r = 0; r < 2; r++) xt[2 * q + r][j] = lds64((xs ^ ((j & 3) << 5)) + (q ? tail_c(0) : OFF_FT) + (j >> 2) * TILE + r * 2048);
                if (q == 0) dk[j] = lds64(sb + OFF_DK + c * 8 + 32 * j);
            };
            auto term = [&](int q, int j) {
#pragma unroll
                for (int r = 2 * q; r < 2 * q + 2; r++) {
                    xt[r][j].x = mul_bf2(xt[r][j].x, fma_bf2(gp[r], dk[j].x, om[r]));
                    xt[r][j].y = mul_bf2(xt[r][j].y, fma_bf2(gp[r], dk[j].y, om[r]));
                }
            };
            auto store = [&](int q, int u0, int u1) {
                const float (&acc)[64] = q ? outB : outA;
#pragma unroll
                for (int u = u0; u < u1; u++) {
                    const int j = u >> 1, r = u & 1;
                    const int o = 8 * j + 2 * r;
                    const float gv = fabsf(gf[2 * q + r]);
                    const uint2 t = xt[2 * q + r][j];
                    stg128(op + (r * 32 + q * 16) * D_ + 16 * j, __float_as_uint(fmaf(gv, acc[o], bf_lo(t.x))), __float_as_uint(fmaf(gv, acc[o + 1], bf_hi(t.x))),
                           __float_as_uint(fmaf(gv, acc[o + 4], bf_lo(t.y))), __float_as_uint(fmaf(gv, acc[o + 5], bf_hi(t.y))));
                }
            };
            uint64_t dh = desc64<1>(make_desc_h(sb)), dc = desc64<0>(make_desc(sb));
#pragma unroll
            for (int n = 0; n < 2 * NSPL; n++) {
                const int j = n % NSPL;
                if (n == 0) mbar_wait(bar_g);
                if (n == X0) mbar_wait(bar_x);
                mbar_wait(full + 8 * (NBIG + n));
                KSTAMP(NBIG + n);
                asm volatile("mov.b64 %0, %0; mov.b64 %1, %1;" : "+l"(dh), "+l"(dc));
                const uint64_t da = dh + (tail_h(n) >> 4), db = dc + (tail_c(j) >> 4);
                const int xj = n - X0;
                wgmma_fence();
#pragma unroll
                for (int kk = 0; kk < 4; kk++) {
                    wgmma_n128<1>(n < NSPL ? outA : outB, da + kk * 128, db + kk * 2);
                    if (kk == 0 && n == 0) {
#pragma unroll
                        for (int r = 0; r < 4; r++) {
                            uint32_t u;
                            asm volatile("ld.shared.u16 %0, [%1];" : "=r"(u) : "r"(gs + (r & 1) * 64 + (r >> 1) * 32) : "memory");
                            gf[r] = bf_lo(u);
                        }
                    }
                    if (kk == 0 && xj >= 0 && xj < 8) load_x(0, xj);
                }
                wgmma_commit();
                if (n <= 2 * NSPL - 7) {
                    wgmma_wait<1>();
                    if (lane == 0) mbar_arrive(empty + 8 * (NBIG + n - 1));
                    if (!j) { LSTAMP(at == 0, 96 + 12 + n / NSPL); GSTAMP(LT && at == 0, 195 + n / NSPL); }
                } else if (n == 2 * NSPL - 1) {
                    mbar_wait(bar_x + 8);
                    load_x(1, 0);
                } else cut();
                if (n == 0) {
#pragma unroll
                    for (int r = 0; r < 4; r++) {
                        const bool routed = (int)__float_as_uint(gf[r]) < 0;
                        gp[r] = routed ? 0u : pack_bf(gf[r], gf[r]); om[r] = routed ? 0u : pack_bf(1.0f - gf[r], 1.0f - gf[r]);
                    }
                }
                if (xj >= 0 && xj < 8) term(0, xj);
                if (n == NSPL) pin64(outA);
                if (n >= NSPL) store(0, (j * 16 + 4) / NSPL, j == NSPL - 1 ? 16 : ((j + 1) * 16 + 4) / NSPL);
            }
            term(1, 0);
            cut();
            wgmma_wait<0>();
            pin64(outB);
            LSTAMP(at == 0, 96 + 51); GSTAMP(LT && at == 0, 197);
#pragma unroll
            for (int j = 1; j < 8; j++) load_x(1, j);
            store(1, 0, 2);
#pragma unroll
            for (int j = 1; j < 8; j++) {
                cut();
                term(1, j);
                store(1, 2 * j, 2 * j + 2);
            }
            __syncwarp();
            if (lane == 0) mbar_arrive(bar_stored);
            LSTAMP(at == 0, 96 + 52);
        }
    } else if (warp < 12) {
        asm volatile("setmaxnreg.dec.sync.aligned.u32 64;");
        init_barriers(empty + min(80 + 160 * w, 8 * 67), 4, []() { return 20; });
#pragma unroll
        for (int i = 0; i < 2; i++) sts128(sb + OFF_LIST + i * 2048 + at * 16, 0u, 0u, 0u, 0u);
        uint32_t* keys = reinterpret_cast<uint32_t*>(smem + OFF_KEYS);
        keys[4] = 0;
        named_bar(0, 448);
        mbar_wait(bar_epoch);
        const uint32_t t2 = lds32(sb + OFF_EPOCH + 4), par = lds32(sb + OFF_EPOCH) & 1u;
        STAMPIF(at == 0, 20);
        float facc[4];
        const uint32_t dft = make_desc(sb + OFF_FT), dxs = make_desc(sb + OFF_XS);
#pragma unroll 1
        for (int u = 0; u < 4; u++) {
            mbar_wait(ffull + 8 * u);
            STAMPIF(at == 0, 4 + u);
            wgmma_fence();
            small_tile<0>(facc, dft + u * (TILE >> 4), dxs + u * 64, u == 0);
            wgmma_commit();
        }
        wgmma_wait<0>();
        pin4(facc);
        if (lane < 4) mbar_arrive(fempty + 8 * lane);
        auto gate_up = [&](auto rest) {
            uint32_t slot = 4, ph = 0, prev = full + 8 * 101, e4 = 4 * TN(GC0);
#pragma unroll 1
            for (int j = 0; j < 14; j++) {
                if (j == 2) rest();
                STAMPW(at == 0, 75 + j);
                mbar_wait(ffull + 8 * slot, ph);
                STAMPW(at == 0, 160 + j);
                mbar_wait(empty + 8 * (e4 >> 2));
                e4 += j < 8 ? TN(GCS) : TN(GCS4);
                wgmma_fence();
                small_tile<1>(facc, dft + slot * (TILE >> 4), dxs + j * 64, j == 0);
                wgmma_commit();
                wgmma_wait<1>();
                if (lane == 0) mbar_arrive(prev);
                prev = fempty + 8 * slot;
                if (++slot == NFT) { slot = 0; ph ^= 1; }
            }
            wgmma_wait<0>();
            if (lane == 0) mbar_arrive(prev);
            pin4(facc);
        };
        auto help = [&]() {
            uint32_t slot = 4, ph = 0, e4 = 4 * TN(GC0);
#pragma unroll 1
            for (int u = 0; u < 7; u++) {
                const uint32_t slot2 = slot == NFT - 1 ? 0 : slot + 1;
                mbar_wait(ffull + 8 * slot, ph);
                ph ^= slot2 == 0;
                mbar_wait(ffull + 8 * slot2, ph);
                mbar_wait(empty + 8 * (e4 >> 2));
                e4 += TN(GCH);
                wgmma_fence();
                small_tile<1>(facc, dft + slot * (TILE >> 4), dxs, true);
                small_tile<1>(facc, dft + slot2 * (TILE >> 4), dxs + 64, false);
                wgmma_commit();
                wgmma_wait<0>();
                pin4(facc);
                if (lane < 2) mbar_arrive(fempty + 8 * (lane ? slot2 : slot));
                st_relaxed4(&prm.s->part[((cta - 112) * 7 + u) * 128 + at], (__float_as_uint(facc[0]) & ~3u) | t2, __float_as_uint(facc[1]),
                            __float_as_uint(facc[2]), __float_as_uint(facc[3]));
                slot = slot2 == NFT - 1 ? 0 : slot2 + 1;
                ph ^= slot == 0;
            }
        };
        auto down = [&]() {
            const uint32_t dhid = make_desc(sb + OFF_HID);
#pragma unroll 1
            for (int j = 0; j < 7; j++) {
                mbar_wait(dfull + 8 * j);
                wgmma_fence();
                small_tile<1>(facc, dft + j * (TILE >> 4), dhid + j * 64, j == 0);
                wgmma_commit();
                if ((0x52 >> j) & 1) {
                    wgmma_wait<0>();
                    if (lane == 0) mbar_arrive(bar_dfree + 8 * (j / 3));
                }
            }
            wgmma_wait<0>();
            pin4(facc);
        };
        if ((c & 1) == (w >> 1)) {
            float* red = reinterpret_cast<float*>(smem + OFF_RED) + w * 32 + (c >> 1) * 16 + g;
            red[0] = (w & 1) ? facc[1] : facc[0];
            red[8] = (w & 1) ? facc[3] : facc[2];
        }
        named_bar(2, 128);
        STAMPIF(at == 0, 21);
        const uint32_t tpub = clk32();
        if (w < 2) {
            const float* red = reinterpret_cast<const float*>(smem + OFF_RED) + w * 16 + (lane & 15);
            const float v = rbf((red[0] + red[32]) + (red[64] + red[96]));
            if (w == 0) {
                uint32_t k = __float_as_uint(v);
                k = ((k ^ ((uint32_t)((int)k >> 31) | 0x80000000u)) & 0xFFFF0000u) | (t2 << 11) | (2047u - (uint32_t)(rid * 16 + (lane & 15)));
                int rank = 0;
#pragma unroll
                for (int i = 0; i < 8; i++) rank += __shfl_sync(0xffffffffu, k, (lane >> 4) * 8 + i) > k;
                rank += __shfl_xor_sync(0xffffffffu, rank, 16);
                if (rank < 8) st_relaxed(&prm.s->key[kslot * 8 + rank], k);
            } else if (lane < 16) st_relaxed(&prm.s->gate[rid * 16 + lane], __float_as_uint(rbf(sigmoidf_(v))) | t2);
            __syncwarp();
        }
        uint32_t it = 0;
        uint4 ka;
        sleep_until(cstart + TN(GT1));
        sleep_until(tpub + TN(G0));
        bool bad = true;
        while (true) {
            if (bad) ka = ld_relaxed4(&prm.s->key[at * 8]);
            bad = ((ka.x ^ (t2 << 11)) & 0x1800u) != 0;
            if (!__any_sync(0xffffffffu, bad)) break;
            if (++it > SPIN_LIMIT) __trap();
            __nanosleep(TN(T_RETRY));
        }
        STAMPIF(at == 0, 22);
        STAMPIF(at == 0 && it > 0, 23);
        const uint32_t m1 = __reduce_max_sync(0xffffffffu, ka.x), m2 = __reduce_max_sync(0xffffffffu, ka.x == m1 ? ka.y : ka.x);
        if (lane == 0) keys[w] = m2;
        named_bar(2, 128);
        const uint4 th4 = *reinterpret_cast<const uint4*>(keys);
        const uint32_t th = min(min(th4.x, th4.y), min(th4.z, th4.w));
        {
            uint32_t k8[8] = {ka.x, ka.y, ka.z, ka.w, 0u, 0u, 0u, 0u};
            auto append = [&](int lo, int hi) {
                uint32_t n = 0, pos = 0;
#pragma unroll
                for (int i = lo; i < hi; i++) n += k8[i] >= th;
                asm volatile("{ .reg .pred p; setp.ne.u32 p, %2, 0; @p atom.shared.add.u32 %0, [%1], %2; }" : "+r"(pos) : "r"(sb + OFF_KEYS + 16), "r"(n) : "memory");
#pragma unroll
                for (int i = lo; i < hi; i++)
                    if (k8[i] >= th) reinterpret_cast<uint32_t*>(smem + OFF_LIST)[pos + i - lo] = k8[i];
            };
            append(0, 2);
            if (__any_sync(0xffffffffu, k8[2] >= th)) {
                if (k8[3] >= th) {
                    const uint4 kb4 = ld_relaxed4(&prm.s->key[at * 8 + 4]);
                    k8[4] = kb4.x; k8[5] = kb4.y; k8[6] = kb4.z; k8[7] = kb4.w;
                }
                append(2, 8);
            }
        }
        named_bar(2, 128);
        {
            const uint32_t* list = reinterpret_cast<const uint32_t*>(smem + OFF_LIST);
            const int n = (int)keys[4];
#pragma unroll 1
            for (int i0 = w * 32; i0 < n; i0 += 128) {
                const uint32_t k = list[i0 + lane];
                int rank = 0;
#pragma unroll 2
                for (int o = 0; o < n; o += 4) {
                    const uint4 l4 = *reinterpret_cast<const uint4*>(list + o);
                    rank += (l4.x > k) + (l4.y > k) + (l4.z > k) + (l4.w > k);
                }
                if (rank < 8) reinterpret_cast<uint32_t*>(smem + OFF_SEL)[rank] = k;
            }
        }
        named_bar(2, 128);
        STAMPIF(at == 0, 24);
        const uint32_t* sel = reinterpret_cast<const uint32_t*>(smem + OFF_SEL);
        auto gates = [&]() {
            uint32_t gv;
            it = 0;
            while (true) {
                gv = ld_relaxed(&prm.s->gate[chunk * 128 + at]);
                if (__all_sync(0xffffffffu, (gv & 3u) == t2)) break;
                if (++it > SPIN_LIMIT) __trap();
            }
#pragma unroll
            for (int s = 0; s < 8; s++)
                if ((~sel[s] & 2047u) == (uint32_t)(chunk * 128 + at)) gv |= 0x80000000u;
            reinterpret_cast<uint16_t*>(smem + OFF_G)[at] = (uint16_t)(gv >> 16);
            __syncwarp();
            if (lane == 0) mbar_arrive(bar_g);
        };
        {
            const int tk = (at >> 3) & 7;
            const char* xt = (const char*)prm.x + (~sel[tk] & 2047u) * 2048 + (owner ? 256 : 0) + (at >> 6) * 128 + (at & 7) * 16;
#pragma unroll
            for (int i = 0; i < 7; i++) {
                if (i == 0 || owner) cp_async16(sb + OFF_XS + (2 * i + (at >> 6)) * 1024 + tk * 128 + (((at & 7) ^ tk) << 4), xt + i * 256);
                if (i == 0 || i == 6) asm volatile("cp.async.commit_group;" ::: "memory");
            }
            asm volatile("cp.async.wait_group 1;" ::: "memory");
            fence_async_smem();
            named_bar(2, 128);
            STAMPIF(at == 0, 25);
        }
        if (!owner) help();
        else {
            gate_up([&]() {
                asm volatile("cp.async.wait_all;" ::: "memory");
                fence_async_smem();
                named_bar(2, 128);
            });
            it = 0;
            while (true) {
                const uint4 v = ld_relaxed4(&prm.s->part[cta * 128 + at]);
                if (__all_sync(0xffffffffu, (v.x & 3u) == t2)) {
                    facc[0] += __uint_as_float(v.x); facc[1] += __uint_as_float(v.y); facc[2] += __uint_as_float(v.z); facc[3] += __uint_as_float(v.w);
                    break;
                }
                if (++it > SPIN_LIMIT) __trap();
                __nanosleep(TN(T_RETRY));
            }
            if (!(cta & 1)) {
#pragma unroll
                for (int u = 0; u < 4; u++) {
                    const float v = rbf(facc[u]);
                    facc[u] = __fdividef(v, 1.0f + __expf(-v));
                }
            }
            const uint32_t first = ((__float_as_uint(facc[0]) + (par ? 0u : 0x10000u)) >> 17) * 2 + par;
            st_relaxed2(&prm.s->hid[cta * 128 + at], __byte_perm(first, pack_bf(0.f, facc[1]), 0x7610), pack_bf(facc[2], facc[3]));
        }
        STAMPIF(at == 0, 26);
        gates();
        uint32_t mine = __ballot_sync(0xffffffffu, lane < 8 && (int)((~sel[lane & 7] & 2047u) >> 7) == chunk), tr;
        uint2 xr, xd;
        float gr, rs;
        auto skip = [&](int n) {
#pragma unroll 1
            for (int i = 0; i < n; i++) mine &= mine - 1;
            if (mine) {
                const uint32_t key = sel[__ffs(mine) - 1], kb = key >> 16;
                tr = ~key & 2047u;
                xr = __ldg(reinterpret_cast<const uint2*>(prm.x + (size_t)tr * D_ + dt * 128) + lane);
                rs = rbf(sigmoidf_(bf_lo((kb & 0x8000u) ? (kb & 0x7FFFu) : (~kb & 0xFFFFu))));
                gr = fabsf(__bfloat162float(reinterpret_cast<const __nv_bfloat16*>(smem + OFF_G)[tr & 127]));
                xd = lds64(sb + OFF_DK + 8 * lane);
            }
        };
        mbar_wait(bar_g);
        skip(w);
        {
            mbar_wait(empty + 8 * max(TN(HG), 31));
            const uint2* hp = &prm.s->hid[(cta >> 4) * 14 * 128 + at];
            uint32_t hv[16];
            it = 0;
            while (true) {
                uint32_t bad = 0;
#pragma unroll
                for (int j = 0; j < 7; j++) {
                    const uint2 hg = ld_relaxed2(hp + 256 * j), hu = ld_relaxed2(hp + 256 * j + 128);
                    bad |= (hg.x ^ par) | (hu.x ^ par);
                    hv[2 * j] = mul_bf2(hg.x, hu.x); hv[2 * j + 1] = mul_bf2(hg.y, hu.y);
                }
                if (!__any_sync(0xffffffffu, bad & 1u)) break;
                do {
                    if (++it > SPIN_LIMIT) __trap();
                } while (__any_sync(0xffffffffu, (ld_relaxed(hp + min(lane, 13) * 128 - lane) ^ par) & 1u));
            }
            STAMPIF(at == 0 && it > 0, 61);
            hv[14] = hv[15] = 0;
#pragma unroll
            for (int j = 0; j < 4; j++)
                asm volatile("stmatrix.sync.aligned.m8n8.x4.trans.shared.b16 [%0], {%1, %2, %3, %4};" ::"r"(
                                 sb + OFF_HID + (2 * j + (lane >> 4)) * 1024 + (lane & 7) * 128 + (((2 * w + ((lane >> 3) & 1)) ^ (lane & 7)) << 4)),
                             "r"(hv[4 * j]), "r"(hv[4 * j + 1]), "r"(hv[4 * j + 2]), "r"(hv[4 * j + 3]) : "memory");
        }
        fence_async_smem();
        named_bar(2, 128);
        STAMPIF(at == 0, 27);
        down();
#pragma unroll
        for (int u = 0; u < 4; u++)
            st_relaxed(&prm.s->y[((2 * c + (u & 1)) * 8 + (cta >> 4)) * D_ + (cta & 15) * 64 + w * 16 + g + 8 * (u >> 1)], (__float_as_uint(facc[u]) & ~3u) | t2);
        STAMPIF(at == 0, 28);
        sleep_until(clk32() + TN(T_Y));
        while (mine) {
            const uint32_t* yp = &prm.s->y[(__ffs(mine) - 1) * 8 * D_ + dt * 128 + 4 * lane];
            float y[4];
            it = 0;
            while (true) {
                uint32_t bad = 0;
                y[0] = y[1] = y[2] = y[3] = 0.f;
#pragma unroll
                for (int ks = 0; ks < 8; ks++) {
                    const uint4 v = ld_relaxed4(yp + ks * D_);
                    bad |= v.x ^ t2;
                    y[0] += __uint_as_float(v.x); y[1] += __uint_as_float(v.y); y[2] += __uint_as_float(v.z); y[3] += __uint_as_float(v.w);
                }
                if (__all_sync(0xffffffffu, (bad & 3u) == 0)) break;
                if (++it > SPIN_LIMIT) __trap();
            }
            STAMPIF(lane == 0 && it, 62);
#pragma unroll
            for (int u = 0; u < 4; u++) {
                const uint32_t x2 = (u & 2) ? xr.y : xr.x, d2 = mul_bf2(x2, (u & 2) ? xd.y : xd.x);
                y[u] = fmaf(gr, (u & 1) ? bf_hi(d2) : bf_lo(d2), rbf(rbf(1.0f - gr) * rbf(((u & 1) ? bf_hi(x2) : bf_lo(x2)) + rbf(rbf(y[u]) * rs))));
            }
            STAMPIF(lane == 0, 50);
            mbar_wait(bar_stored);
            asm volatile("red.global.add.v4.f32 [%0], {%1, %2, %3, %4};" ::"l"(prm.out + (size_t)tr * D_ + dt * 128 + 4 * lane), "f"(y[0]), "f"(y[1]), "f"(y[2]), "f"(y[3]) : "memory");
            skip(4);
        }
        LSTAMP(lane == 0, 96 + 29);
    } else {
        asm volatile("setmaxnreg.dec.sync.aligned.u32 40;");
        if (warp != 12) sleep_until(cstart + (warp == 13 ? TN(T_SMALL) : warp == 14 ? TN(PF0) - 250 : TN(T_W3)));
        auto behind = [&](int e) { mbar_wait(empty + 8 * e); };
        if (warp == 15) {
            prefetch_map(&mXr);
            named_bar(0, 448);
            asm volatile("bar.arrive 1, 64;" ::: "memory");
#pragma unroll 1
            for (int u = 0; u < 4; u++) {
                if (lane == 0) mbar_expect_tx(ffull + 8 * u, TILE);
                sleep_until(cstart + (u == 0 ? TN(RT0) : u == 1 ? TN(RT1) : u == 2 ? TN(RT2) : TN(RT3)));
                if (elect_one()) tma3(sb + OFF_FT + u * TILE, &mXr, u * 256, rid * 16, ffull + 8 * u);
                STAMP(53 + u);
            }
            if (sb & 1023) __trap();
            prefetch_map(&mWg);
            prefetch_map(&mWu);
            prefetch_map(&mWd);
            uint32_t slot = 4, par = 1;
#pragma unroll 1
            for (int j = 0; j < (DBG != 1 ? 14 : 0); j++) {
                const int o = owner ? cta : (cta - 112) * 7 + (j >> 1);
                mbar_wait(fempty + 8 * slot, par);
                if (lane == 0) mbar_expect_tx(ffull + 8 * slot, TILE);
                if (j < NFT) behind(TN(GU_E0) + j * TN(W_NUM) / 4);
                STAMPW(1, 176 + j);
                if (elect_one()) tma2(sb + OFF_FT + slot * TILE, (o & 1) ? &mWu : &mWg, (o >> 1) * 64, (owner ? j + 2 : j & 1) * 64, ffull + 8 * slot);
                if (++slot == NFT) { slot = 0; par ^= 1; }
            }
            if (lane < 9) mbar_expect_tx(lane < 7 ? dfull + 8 * lane : bar_x + 8 * (lane - 7), lane < 7 ? TILE : 2 * TILE);
#pragma unroll 1
            for (int j = 0; j < (DBG != 1 ? 7 : 0); j++) {
                if (j < 3) mbar_wait(fempty + 8 * j, 1);
                behind(min(TN(DL0) + j * TN(DLS) / 4, NBIG - 2));
                if (elect_one()) tma2(sb + OFF_FT + j * TILE, &mWd, (cta & 15) * 64, (cta >> 4) * 448 + j * 64, dfull + 8 * j);
            }
            prefetch_map(&mXe);
#pragma unroll 1
            for (int u = 0; u < 4; u++) {
                if (u == 2) {
                    mbar_wait(bar_dfree + 16);
                    if (elect_one()) tma5(sb + tail_c(8), &mCim, c_col(63), dt * 8, full + 8 * (NBIG + 8));
                }
                mbar_wait(bar_dfree);
                behind(u < 2 ? TN(DN_E0) + u : NBIG + NSPL);
                if (elect_one())
                    asm volatile("cp.async.bulk.tensor.5d.shared::cluster.global.mbarrier::complete_tx::bytes [%0], [%1, {%3, %6, %6, %4, %5}], [%2];"
                                 ::"r"(sb + (u < 2 ? OFF_FT : tail_c(0)) + (u & 1) * TILE), "l"(&mXe), "r"(bar_x + 4 * (u & 2)), "r"(dt * 128 + (u & 1) * 64),
                                 "r"(u & 2), "r"(chunk * 4), "r"(0) : "memory");
            }
        } else if (warp == 13) {
#pragma unroll
            for (int u = 0; u < 8; u++) {
                const int row = (u >> 2) * 4 + (lane >> 3);
                cp_async16(sb + OFF_XS + (u & 3) * 1024 + row * 128 + (((lane & 7) ^ row) << 4), (const char*)(u < 4 ? prm.w_r : prm.gate_w) + (u & 3) * 512 + lane * 16);
            }
            STAMP(57);
            const uint32_t tag = ld_relaxed(&prm.s->epoch[cta]) + 1;
            named_bar(1, 64);
            *reinterpret_cast<uint2*>(smem + OFF_EPOCH) = make_uint2(tag, tag % 3u + 1u);
            STAMPIF(tag, 58);
            asm volatile("cp.async.wait_all;" ::: "memory");
            STAMP(59);
            fence_async_smem();
            __syncwarp();
            if (lane == 0) {
                mbar_arrive(bar_epoch);
                prm.s->epoch[cta] = tag;
            }
            prefetch_map(&mCre);
            prefetch_map(&mCim);
            const char* src = reinterpret_cast<const char*>(prm.s->h) + (size_t)chunk * 524288;
            uint32_t slot = 32 % NST, hpar = 0, rpar = 0;
#pragma unroll 1
            for (int i = 32; i < NBIG; i++) {
                mbar_wait(hfull + 8 * slot, hpar);
                STAMPIF(i == 32 || i == 33, 14 + (i & 1));
                rpar = check_tile<16>(sb, sb + slot * SLOT, probe, src, tag, bar_retry, rpar, TN(T_RETRY));
                if (lane == 0) mbar_expect_tx(full + 8 * i, 2 * TILE);
                STAMPIF(i == 32 || i == 33, 16 + (i & 1));
                src += 2 * TILE;
                slot = slot == NST - 1 ? 0 : slot + 1;
                hpar ^= slot == 32 % NST;
            }
        } else if (warp == 14) {
            const char* pc = (const char*)((lane & 16) ? prm.c_im : prm.c_re) + (cta * 8 + (g & 3)) * 2048 + c * 128;
            auto pf_c = [&](int k) { prefetch_l2(pc + (k >> 1) * 512 + (k & 1) * 8192); };
            {
                const char* px = (const char*)prm.x + (rid * 16 + (lane >> 1)) * 2048 + (lane & 1) * 128;
                const char* pb = (const char*)((lane & 8) ? prm.b_im : prm.b_re) + (cta * 4 + ((lane >> 1) & 3)) * 2048 + (lane & 1) * 128;
#pragma unroll 1
                for (int k = 1; k < 8; k++) {
                    sleep_until(cstart + TN(PF0) + (k - 1) * TN(PF1));
                    prefetch_l2(px + k * 256);
                    if (lane < 16) prefetch_l2(pb + k * 256);
                }
            }
            named_bar(7, 160);
            mbar_wait(bar_epoch);
#pragma unroll 1
            for (int k = 0; k < 4; k++) {
                behind(TN(PB_E0) + TN(PB_STEP) * k);
                prefetch_l2((const char*)((lane & 16) ? prm.b_im : prm.b_re) + (512 + cta * 4 + (g & 3)) * 2048 + c * 128 + k * 512);
            }
#pragma unroll 1
            for (int k = 0; k < TN(PC_N); k++) {
                behind(min(TN(PC_E0) + TN(PC_STEP) * k / 2, 25));
                pf_c(k);
            }
            int pk = TN(PC_N), pe = TN(PC_E1);
            auto own_part = [&](int e) {
                if (!(TDBG & 16) && !mbar_test(bar_out + 8 * e, 0)) {
                    mbar_wait(bar_out + 8 * e);
                    sleep_until(clk32() + TN(T_OWN));
                    STAMP(11);
                }
            };
            const char* src = reinterpret_cast<const char*>(prm.s->h) + (size_t)chunk * 524288;
            uint32_t slot = 32 % NST;
#pragma unroll 1
            for (int i = 32; i < NBIG; i++) {
                if (!(i & 3)) own_part((i - 32) >> 2);
                mbar_wait(empty + 8 * (i - NST));
                PSTAMP(i);
                if (elect_one()) {
                    mbar_expect_tx(hfull + 8 * slot, 2 * TILE);
                    bulk_load(sb + slot * SLOT, src, 2 * TILE, hfull + 8 * slot);
                    tma5(sb + slot * SLOT + 2 * TILE, (i & 4) ? &mCim : &mCre, c_col(i), dt * 8, full + 8 * i);
                }
                if (i == pe && pk < 8) {
                    pf_c(pk);
                    pk++; pe += TN(PC_S1);
                }
                src += 2 * TILE;
                slot = slot == NST - 1 ? 0 : slot + 1;
            }
            src -= (NBIG - 32) * 2 * TILE;
#pragma unroll
            for (int k = 0; k < 2 * NSPL - 2; k++) {
                if (k == 0 || k == 2) own_part(6 + k / 2);
                mbar_wait(empty + 8 * (NBIG - NST + k));
                if (k >= 1 && k <= 4) {
                    if (elect_one()) {
#pragma unroll
                        for (int j = 2 * k - 2; j < 2 * k; j++)
                            tma5(sb + tail_c(j), ((NBIG + j) & 4) ? &mCim : &mCre, c_col(NBIG + j), dt * 8, full + 8 * (NBIG + j));
                    }
                }
                if (k == 4) continue;
                if (k == 2) mbar_wait(bar_dfree + 8);
                if (elect_one()) {
#pragma unroll
                    for (int n = k < 5 ? 2 * k : k + 2; n < (k < 3 ? 2 * k + 2 : k == 3 ? 7 : k + 3); n++) {
                        mbar_expect_tx(hfull + 8 * (NST + n % 7), TILE);
                        bulk_load(sb + tail_h(n), src + tail_src(n), TILE, hfull + 8 * (NST + n % 7));
                    }
                }
            }
        } else {
            if (elect_one()) {
#pragma unroll
                for (int i = 0; i < NST; i++) mbar_init(full + 8 * i, 1);
                fence_mbar_init();
            }
            __syncwarp();
            asm volatile("bar.arrive 5, 160;" ::: "memory");
            asm volatile("bar.arrive 0, 448;" ::: "memory");
#pragma unroll 1
            for (int i = 0; i < NST; i++) {
                if (elect_one()) {
                    mbar_expect_tx(full + 8 * i, SLOT);
                    tma5b(sb + i * SLOT, &mB, i * 64, dt * 4, full + 8 * i);
                    tma4(sb + i * SLOT + 2 * TILE, &mX, i * 64, chunk * 64, full + 8 * i);
                }
                STAMPIF(i == 0, 1);
            }
            STAMP(2);
            named_bar(6, 160);
            uint32_t dst = sb;
#pragma unroll 1
            for (int i = NST; i < 32; i++) {
                if (i == 2 * NST) mbar_wait(bar_epoch);
                if (lane == 0) mbar_expect_tx(full + 8 * i, SLOT);
                mbar_wait(empty + 8 * (i - NST));
                PSTAMP(i);
                if (elect_one()) {
                    tma5b(dst, &mB, (i & 15) * 64, (i >> 4) * 64 + dt * 4, full + 8 * i);
                    tma4(dst + 2 * TILE, &mX, (i & 15) * 64, chunk * 64, full + 8 * i);
                }
                dst = dst == sb + (NST - 1) * SLOT ? sb : dst + SLOT;
            }
        }
    }
}

typedef CUresult (*EncodeFn)(CUtensorMap*, CUtensorMapDataType, cuuint32_t, void*, const cuuint64_t*, const cuuint64_t*, const cuuint32_t*,
                             const cuuint32_t*, CUtensorMapInterleave, CUtensorMapSwizzle, CUtensorMapL2promotion, CUtensorMapFloatOOBfill);

bool encode(EncodeFn fn, CUtensorMap* m, const void* ptr, int rank, const cuuint64_t* dims, const cuuint64_t* strides, const cuuint32_t* box,
            CUtensorMapL2promotion promo = CU_TENSOR_MAP_L2_PROMOTION_NONE) {
    const cuuint32_t es[5] = {1, 1, 1, 1, 1};
    return fn(m, CU_TENSOR_MAP_DATA_TYPE_BFLOAT16, rank, const_cast<void*>(ptr), dims, strides, box, es, CU_TENSOR_MAP_INTERLEAVE_NONE,
              CU_TENSOR_MAP_SWIZZLE_128B, promo, CU_TENSOR_MAP_FLOAT_OOB_FILL_NONE) == CUDA_SUCCESS;
}

}

extern "C" void kernel_launch(void* const* d_in, const int* in_sizes, int n_in, void* d_out, int out_size) {
    (void)in_sizes; (void)n_in; (void)out_size;
    Params prm;
    prm.x = (const __nv_bfloat16*)d_in[0];
    prm.lam_re = (const __nv_bfloat16*)d_in[1];
    prm.lam_im = (const __nv_bfloat16*)d_in[2];
    prm.b_re = (const __nv_bfloat16*)d_in[3];
    prm.b_im = (const __nv_bfloat16*)d_in[4];
    prm.c_re = (const __nv_bfloat16*)d_in[5];
    prm.c_im = (const __nv_bfloat16*)d_in[6];
    prm.log_dt = (const __nv_bfloat16*)d_in[7];
    prm.dskip = (const __nv_bfloat16*)d_in[8];
    prm.w_r = (const __nv_bfloat16*)d_in[10];
    prm.gate_w = (const __nv_bfloat16*)d_in[14];
    prm.out = (float*)d_out;
    cudaGetSymbolAddress((void**)&prm.s, g_scratch);
    prm.swapped = prm.b_im < prm.b_re;

    void* fnp = nullptr;
    cudaDriverEntryPointQueryResult qr;
    cudaGetDriverEntryPoint("cuTensorMapEncodeTiled", &fnp, cudaEnableDefault, &qr);
    EncodeFn fn = (EncodeFn)fnp;
    cudaFuncSetAttribute(fused_kernel, cudaFuncAttributeMaxDynamicSharedMemorySize, SMEM_BYTES);

    CUtensorMap mX, mB, mCre, mCim, mWg, mWu, mWd, mXr, mXe;
    const cuuint64_t row = 2048;
    {
        const cuuint64_t dims[4] = {1024, 2, 4, 976}, st[3] = {row, 32 * row, 2 * row};
        const cuuint32_t box[4] = {64, 2, 4, 16};
        encode(fn, &mX, prm.x, 4, dims, st, box, PROMO);
    }
    {
        const char *lo = (const char*)(prm.swapped ? prm.b_im : prm.b_re), *hi = (const char*)(prm.swapped ? prm.b_re : prm.b_im);
        const cuuint64_t dims[5] = {1024, 8, 2, 96, 2}, st[4] = {row, (cuuint64_t)(hi - lo), 8 * row, 256 * row};
        const cuuint32_t box[5] = {64, 8, 2, 4, 2};
        encode(fn, &mB, lo, 5, dims, st, box, PROMO);
    }
    {
        const cuuint64_t dims[5] = {1024, 2, 4, 2, 64}, st[4] = {row, 4 * row, 2 * row, 16 * row};
        const cuuint32_t box[5] = {64, 2, 4, 2, 8};
        encode(fn, &mCre, prm.c_re, 5, dims, st, box);
        encode(fn, &mCim, prm.c_im, 5, dims, st, box);
    }
    {
        const cuuint64_t dims[2] = {F_, D_}, st[1] = {F_ * 2}, dimsd[2] = {D_, F_}, std_[1] = {row};
        const cuuint32_t box[2] = {64, 64};
        encode(fn, &mWg, d_in[11], 2, dims, st, box);
        encode(fn, &mWu, d_in[12], 2, dims, st, box);
        encode(fn, &mWd, d_in[13], 2, dimsd, std_, box);
    }
    {
        const cuuint64_t dims[3] = {D_ - 192, S_, 4}, st[2] = {row, 128};
        const cuuint32_t box[3] = {64, 16, 4};
        encode(fn, &mXr, prm.x, 3, dims, st, box);
    }
    {
        const cuuint64_t dims[5] = {1024, 2, 4, 4, S_ / 32}, st[4] = {4 * row, row, 8 * row, 32 * row};
        const cuuint32_t box[5] = {64, 2, 4, 2, 4};
        encode(fn, &mXe, prm.x, 5, dims, st, box);
    }
    fused_kernel<<<NCTA, 512, SMEM_BYTES, cudaStreamPerThread>>>(prm, mX, mB, mCre, mCim, mWg, mWu, mWd, mXr, mXe);
}
```
